```python
import torch

def _softmax(x, axis=-1):
    return torch.softmax(x, dim=axis)
def _gelu(x):
    return torch.nn.functional.gelu(x, approximate="tanh")
def _silu(x):
    return torch.nn.functional.silu(x)
def _sigmoid(x):
    return torch.sigmoid(x)
def _layernorm(x, axis=-1, eps=1e-5):
    m = x.mean(dim=axis, keepdim=True)
    v = x.var(dim=axis, keepdim=True, unbiased=False)
    return (x - m) / torch.sqrt(v + eps)
def _scatter_add(tgt, idx, src, axis=0):
    return tgt.clone().index_add_(axis, idx, src)
def _segment_sum(src, seg, n):
    out = torch.zeros((n,) + src.shape[1:], dtype=src.dtype)
    return out.index_add_(0, seg, src)
def _pad(x, pw):
    flat = tuple(v for pair in reversed(pw) for v in pair)
    return torch.nn.functional.pad(x, flat)

kernel_name = 'concat_heads__ssm_conv_h3__sliding_block__prompt'

def setup_inputs():

    _w = (lambda a: (lambda t: t.to(torch.bfloat16) if t.is_floating_point() else t)(torch.as_tensor(a)))
    def _A_setup():
        B, S, D = 1, 2048, 640
        ks = 4
        return {
            "q": _w((lambda *s: torch.randn(*s, dtype=torch.bfloat16) * 0.05)(B, S, D)),
            "k": _w((lambda *s: torch.randn(*s, dtype=torch.bfloat16) * 0.8)(B, S, D)),
            "v": _w((lambda *s: torch.randn(*s, dtype=torch.bfloat16) * 0.8)(B, S, D)),
            "shift_k": _w((lambda *s: torch.randn(*s, dtype=torch.bfloat16) * 0.8)(D, ks) * 0.5),
            "ssm_k": _w((lambda *s: torch.randn(*s, dtype=torch.bfloat16) * 3.2)(D, S) * (1.0 / S ** 0.5)),
            "ssm_D": _w((lambda *s: torch.randn(*s, dtype=torch.bfloat16) * 0.8)(D)),
        }
    _A_in = _A_setup()

    def _B_setup():
        B, S, D = 1, 2048, 640
        return {
            "x": _w((lambda *s: torch.randn(*s, dtype=torch.bfloat16) * 0.2)(B, S, D)),
            "wqkv": _w((lambda *s: torch.randn(*s, dtype=torch.bfloat16) * 0.2)(D, 3 * D)),
            "wo": _w((lambda *s: torch.randn(*s, dtype=torch.bfloat16) * 0.05)(D, D)),
        }
    _B_in = _B_setup()

    return {
        "A_q": _A_in["q"],
        "A_k": _A_in["k"],
        "A_v": _A_in["v"],
        "A_shift_k": _A_in["shift_k"],
        "A_ssm_k": _A_in["ssm_k"],
        "A_ssm_D": _A_in["ssm_D"],
        "B_x": _B_in["x"],
        "B_wqkv": _B_in["wqkv"],
        "B_wo": _B_in["wo"],
    }

def reference(A_q, A_k, A_v, A_shift_k, A_ssm_k, A_ssm_D, B_x, B_wqkv, B_wo):
    def _A_ref(q, k, v, shift_k, ssm_k, ssm_D):
        B, S, D = q.shape
        ks = shift_k.shape[-1]
        k_pad = _pad(k, ((0, 0), (ks - 1, 0), (0, 0)))
        k_shift = torch.zeros_like(k)
        for t in range(ks):
            k_shift = k_shift + k_pad[:, t:t + S, :] * shift_k[:, ks - 1 - t][None, None, :]
        kv = k_shift * v
        L = 2 * S
        kv_pad = _pad(kv, ((0, 0), (0, S), (0, 0)))
        kf_pad = _pad(ssm_k, ((0, 0), (0, S)))
        kv_f = (lambda x, axes=(-2,-1): torch.fft.rfft2(x.float(), dim=axes))(kv_pad[:, None, :, :], axes=(1, 2))
        kf_f = (lambda x, axes=(-2,-1): torch.fft.rfft2(x.float(), dim=axes))(kf_pad[:, None, :], axes=(1, 2))
        kf_f = (lambda x, *d: x.permute(*d))(kf_f, 1, 2, 0)
        y_f = kv_f * kf_f[None, :, :, :]
        y = (lambda x, s, axes=(-2,-1): torch.fft.irfft2(x, s=s, dim=axes).to(torch.bfloat16))(y_f, (1, L), axes=(1, 2))[:, 0, :S, :]
        y = y + kv * ssm_D[None, None, :]
        return q * y

    def _B_ref(x, wqkv, wo):
        B, S, D = x.shape
        H = 32; Dh = D // H; W = 256
        qkv = (lambda x, *d: x.permute(*d))((x @ wqkv).reshape(B, S, 3, H, Dh), 2, 0, 3, 1, 4)
        q, k, v = qkv[0], qkv[1], qkv[2]
        scores = torch.einsum("bhqd,bhkd->bhqk", q, k) * (Dh ** -0.5)
        idx = torch.arange(S)
        mask = (idx[:, None] - idx[None, :] >= 0) & (idx[:, None] - idx[None, :] < W)
        scores = torch.where(mask[None, None], scores, -1e9)
        p = _softmax(scores, axis=-1)
        o = torch.einsum("bhqk,bhkd->bhqd", p, v)
        return (lambda x, *d: x.permute(*d))(o, 0, 2, 1, 3).reshape(B, S, D) @ wo

    a = _A_ref(A_q, A_k, A_v, A_shift_k, A_ssm_k, A_ssm_D)
    b = _B_ref(B_x, B_wqkv, B_wo)
    return torch.concatenate([a, b], axis=-1)
```

```cpp
#include <cuda_runtime.h>
#include <cuda.h>
#include <cuda_bf16.h>
#include <stdint.h>

#define DEVINL __device__ __forceinline__

namespace {

constexpr int SEQ = 2048;
constexpr int DM = 640;

constexpr int ST1 = 47104;
constexpr int ST1_B128 = 16384;
constexpr int ST1_B32 = 40960;
constexpr int NST1 = 3;
constexpr int KVWIN = 30720;
constexpr int ST2 = 26624;
constexpr int NST2 = 5;
constexpr int OFF_CONV = NST1 * ST1;
constexpr int CH_U = 4352;
constexpr int CH_F = 8320;
constexpr int OFF_U = OFF_CONV;
constexpr int OFF_F = OFF_CONV + 5 * CH_U;
constexpr int OFF_STG = OFF_F + 5 * CH_F;
constexpr int OFF_BAR = OFF_STG + 20480;
constexpr int SMEM_BYTES = OFF_BAR + 256 + 1024;

constexpr int B_FULL1 = 0, B_EMPTY1 = 3, B_RINGFREE = 6, B_HALO = 7, B_FULL2 = 9, B_EMPTY2 = 14, B_U = 19, B_COUNT = 20;

__device__ __align__(1024) uint16_t g_kv[8 * 2 * 2 * SEQ * 40];
__device__ __align__(1024) uint16_t g_o[SEQ * DM];
__device__ __align__(1024) uint16_t g_kvT[DM * 2176];
__device__ __align__(1024) uint16_t g_yT[DM * SEQ];
constexpr int CS = 32;
constexpr int C_KV = 0, C_O = 128, C_PRE = 144, C_Y = 152, C_DONE = 160, C_NUM = 161;
__device__ unsigned g_cnt[C_NUM * CS];
__device__ unsigned g_err;
#define PROF(slot) do {} while (0)

DEVINL void mbar_init(uint32_t a, uint32_t c) { asm volatile("mbarrier.init.shared::cta.b64 [%0], %1;" ::"r"(a), "r"(c)); }
DEVINL void mbar_expect(uint32_t a, uint32_t b) {
  asm volatile("mbarrier.arrive.expect_tx.shared::cta.b64 _, [%0], %1;" ::"r"(a), "r"(b) : "memory");
}
DEVINL void mbar_arrive(uint32_t a) { asm volatile("mbarrier.arrive.shared::cta.b64 _, [%0];" ::"r"(a) : "memory"); }
DEVINL void mbar_arrive_cta(uint32_t a, uint32_t cta) {
  asm volatile("{\n.reg .b32 ra;\nmapa.shared::cluster.u32 ra, %0, %1;\nmbarrier.arrive.shared::cluster.b64 _, [ra];\n}"
               ::"r"(a), "r"(cta) : "memory");
}
DEVINL bool mbar_try(uint32_t a, uint32_t p) {
  uint32_t ok;
  asm volatile("{\n.reg .pred P;\nmbarrier.try_wait.parity.shared::cta.b64 P, [%1], %2;\nselp.u32 %0, 1, 0, P;\n}"
               : "=r"(ok) : "r"(a), "r"(p) : "memory");
  return ok;
}
DEVINL void mbar_wait(uint32_t a, uint32_t p) {
  if (mbar_try(a, p)) return;
  int n = 0;
  while (!mbar_try(a, p)) {
    if (++n > (1 << 18)) { g_err = 1; break; }
  }
}
DEVINL void poll_ge(const unsigned* p, unsigned target) {
  int n = 0;
  while (true) {
    unsigned v;
    asm volatile("ld.acquire.gpu.global.u32 %0, [%1];" : "=r"(v) : "l"(p) : "memory");
    if (v >= target) break;
    if (++n > (1 << 20)) { g_err = 2; break; }
  }
}
DEVINL void red_release(unsigned* p) { asm volatile("red.release.gpu.global.add.u32 [%0], 1;" ::"l"(p) : "memory"); }
DEVINL void fence_async() { asm volatile("fence.proxy.async;" ::: "memory"); }
DEVINL void fence_async_smem() { asm volatile("fence.proxy.async.shared::cta;" ::: "memory"); }
DEVINL void named_sync(int id, int n) { asm volatile("bar.sync %0, %1;" ::"r"(id), "r"(n) : "memory"); }

DEVINL void tma2d(uint32_t dst, const CUtensorMap* m, int c0, int c1, uint32_t bar) {
  asm volatile("cp.async.bulk.tensor.2d.shared::cluster.global.mbarrier::complete_tx::bytes [%0], [%1, {%3, %4}], [%2];"
               ::"r"(dst), "l"(m), "r"(bar), "r"(c0), "r"(c1) : "memory");
}
DEVINL void tma2d_mc(uint32_t dst, const CUtensorMap* m, int c0, int c1, uint32_t bar) {
  asm volatile("cp.async.bulk.tensor.2d.shared::cluster.global.mbarrier::complete_tx::bytes.multicast::cluster [%0], [%1, {%3, %4}], [%2], %5;"
               ::"r"(dst), "l"(m), "r"(bar), "r"(c0), "r"(c1), "h"((uint16_t)3) : "memory");
}
DEVINL void tma3d(uint32_t dst, const CUtensorMap* m, int c0, int c1, int c2, uint32_t bar) {
  asm volatile("cp.async.bulk.tensor.3d.shared::cluster.global.mbarrier::complete_tx::bytes [%0], [%1, {%3, %4, %5}], [%2];"
               ::"r"(dst), "l"(m), "r"(bar), "r"(c0), "r"(c1), "r"(c2) : "memory");
}
DEVINL void tma3d_mc(uint32_t dst, const CUtensorMap* m, int c0, int c1, int c2, uint32_t bar) {
  asm volatile("cp.async.bulk.tensor.3d.shared::cluster.global.mbarrier::complete_tx::bytes.multicast::cluster [%0], [%1, {%3, %4, %5}], [%2], %6;"
               ::"r"(dst), "l"(m), "r"(bar), "r"(c0), "r"(c1), "r"(c2), "h"((uint16_t)3) : "memory");
}
DEVINL void tma2d_store(const CUtensorMap* m, int c0, int c1, uint32_t src) {
  asm volatile("cp.async.bulk.tensor.2d.global.shared::cta.bulk_group [%0, {%2, %3}], [%1];"
               ::"l"(m), "r"(src), "r"(c0), "r"(c1) : "memory");
}
DEVINL void bulk_load(uint32_t dst, const void* src, uint32_t bytes, uint32_t bar) {
  asm volatile("cp.async.bulk.shared::cluster.global.mbarrier::complete_tx::bytes [%0], [%1], %2, [%3];"
               ::"r"(dst), "l"(src), "r"(bytes), "r"(bar) : "memory");
}
DEVINL void bulk_store(void* dst, uint32_t src, uint32_t bytes) {
  asm volatile("cp.async.bulk.global.shared::cta.bulk_group [%0], [%1], %2;" ::"l"(dst), "r"(src), "r"(bytes) : "memory");
}
DEVINL void bulk_commit() { asm volatile("cp.async.bulk.commit_group;" ::: "memory"); }
DEVINL void bulk_wait0() { asm volatile("cp.async.bulk.wait_group 0;" ::: "memory"); }
DEVINL void bulk_wait0_read() { asm volatile("cp.async.bulk.wait_group.read 0;" ::: "memory"); }
DEVINL void prefetch_tmap(const CUtensorMap* m) { asm volatile("prefetch.tensormap [%0];" ::"l"(m) : "memory"); }

DEVINL uint64_t make_desc(uint32_t addr, uint32_t lbo, uint32_t sbo, uint32_t swz) {
  return (uint64_t)((addr & 0x3FFFF) >> 4) | ((uint64_t)(lbo >> 4) << 16) | ((uint64_t)(sbo >> 4) << 32) | ((uint64_t)swz << 62);
}
DEVINL void wg_fence() { asm volatile("wgmma.fence.sync.aligned;" ::: "memory"); }
DEVINL void wg_commit() { asm volatile("wgmma.commit_group.sync.aligned;" ::: "memory"); }
template <int N> DEVINL void wg_wait() { asm volatile("wgmma.wait_group.sync.aligned %0;" ::"n"(N) : "memory"); }

DEVINL void mma16816(float (&d)[4], uint32_t a0, uint32_t a1, uint32_t a2, uint32_t a3, uint32_t b0, uint32_t b1) {
  asm volatile("mma.sync.aligned.m16n8k16.row.col.f32.bf16.bf16.f32 {%0,%1,%2,%3},{%4,%5,%6,%7},{%8,%9},{%0,%1,%2,%3};"
               : "+f"(d[0]), "+f"(d[1]), "+f"(d[2]), "+f"(d[3]) : "r"(a0), "r"(a1), "r"(a2), "r"(a3), "r"(b0), "r"(b1));
}
DEVINL void mma16816_z(float (&d)[4], uint32_t a0, uint32_t a1, uint32_t a2, uint32_t a3, uint32_t b0, uint32_t b1) {
  asm volatile("mma.sync.aligned.m16n8k16.row.col.f32.bf16.bf16.f32 {%0,%1,%2,%3},{%4,%5,%6,%7},{%8,%9},{%10,%10,%10,%10};"
               : "=f"(d[0]), "=f"(d[1]), "=f"(d[2]), "=f"(d[3]) : "r"(a0), "r"(a1), "r"(a2), "r"(a3), "r"(b0), "r"(b1), "f"(0.f));
}
DEVINL void mma1688(float (&d)[4], uint32_t a0, uint32_t a1, uint32_t b0) {
  asm volatile("mma.sync.aligned.m16n8k8.row.col.f32.bf16.bf16.f32 {%0,%1,%2,%3},{%4,%5},{%6},{%0,%1,%2,%3};"
               : "+f"(d[0]), "+f"(d[1]), "+f"(d[2]), "+f"(d[3]) : "r"(a0), "r"(a1), "r"(b0));
}
DEVINL void ldsm4(uint32_t& r0, uint32_t& r1, uint32_t& r2, uint32_t& r3, uint32_t a) {
  asm volatile("ldmatrix.sync.aligned.m8n8.x4.shared.b16 {%0,%1,%2,%3}, [%4];" : "=r"(r0), "=r"(r1), "=r"(r2), "=r"(r3) : "r"(a));
}
DEVINL void ldsm2(uint32_t& r0, uint32_t& r1, uint32_t a) {
  asm volatile("ldmatrix.sync.aligned.m8n8.x2.shared.b16 {%0,%1}, [%2];" : "=r"(r0), "=r"(r1) : "r"(a));
}
DEVINL void ldsm4t(uint32_t& r0, uint32_t& r1, uint32_t& r2, uint32_t& r3, uint32_t a) {
  asm volatile("ldmatrix.sync.aligned.m8n8.x4.trans.shared.b16 {%0,%1,%2,%3}, [%4];" : "=r"(r0), "=r"(r1), "=r"(r2), "=r"(r3) : "r"(a));
}
DEVINL void ldsm2t(uint32_t& r0, uint32_t& r1, uint32_t a) {
  asm volatile("ldmatrix.sync.aligned.m8n8.x2.trans.shared.b16 {%0,%1}, [%2];" : "=r"(r0), "=r"(r1) : "r"(a));
}
DEVINL void stsm4(uint32_t a, uint32_t r0, uint32_t r1, uint32_t r2, uint32_t r3) {
  asm volatile("stmatrix.sync.aligned.m8n8.x4.shared.b16 [%0], {%1,%2,%3,%4};" ::"r"(a), "r"(r0), "r"(r1), "r"(r2), "r"(r3) : "memory");
}
DEVINL void stsm4t(uint32_t a, uint32_t r0, uint32_t r1, uint32_t r2, uint32_t r3) {
  asm volatile("stmatrix.sync.aligned.m8n8.x4.trans.shared.b16 [%0], {%1,%2,%3,%4};" ::"r"(a), "r"(r0), "r"(r1), "r"(r2), "r"(r3) : "memory");
}
DEVINL uint32_t lds32(uint32_t a) { uint32_t v; asm volatile("ld.shared.u32 %0, [%1];" : "=r"(v) : "r"(a)); return v; }
DEVINL uint4 lds128(uint32_t a) {
  uint4 v; asm volatile("ld.shared.v4.u32 {%0,%1,%2,%3}, [%4];" : "=r"(v.x), "=r"(v.y), "=r"(v.z), "=r"(v.w) : "r"(a)); return v;
}
DEVINL void sts32(uint32_t a, uint32_t v) { asm volatile("st.shared.u32 [%0], %1;" ::"r"(a), "r"(v) : "memory"); }
DEVINL void sts128(uint32_t a, uint4 v) {
  asm volatile("st.shared.v4.u32 [%0], {%1,%2,%3,%4};" ::"r"(a), "r"(v.x), "r"(v.y), "r"(v.z), "r"(v.w) : "memory");
}
DEVINL uint4 ldg_nc(const void* p) {
  uint4 v; asm volatile("ld.global.nc.L1::no_allocate.v4.u32 {%0,%1,%2,%3}, [%4];" : "=r"(v.x), "=r"(v.y), "=r"(v.z), "=r"(v.w) : "l"(p)); return v;
}
DEVINL uint4 ldg_cg(const void* p) {
  uint4 v; asm volatile("ld.global.cg.v4.u32 {%0,%1,%2,%3}, [%4];" : "=r"(v.x), "=r"(v.y), "=r"(v.z), "=r"(v.w) : "l"(p) : "memory"); return v;
}
DEVINL void stg128(void* p, uint4 v) {
  asm volatile("st.global.v4.u32 [%0], {%1,%2,%3,%4};" ::"l"(p), "r"(v.x), "r"(v.y), "r"(v.z), "r"(v.w) : "memory");
}
DEVINL uint32_t pack_bf16(float lo, float hi) {
  uint32_t r; asm("cvt.rn.bf16x2.f32 %0, %1, %2;" : "=r"(r) : "f"(hi), "f"(lo)); return r;
}
DEVINL uint32_t hmul2(uint32_t a, uint32_t b) { uint32_t r; asm("mul.rn.bf16x2 %0, %1, %2;" : "=r"(r) : "r"(a), "r"(b)); return r; }
DEVINL uint32_t hadd2(uint32_t a, uint32_t b) { uint32_t r; asm("add.rn.bf16x2 %0, %1, %2;" : "=r"(r) : "r"(a), "r"(b)); return r; }
DEVINL float ex2(float x) { float r; asm("ex2.approx.ftz.f32 %0, %1;" : "=f"(r) : "f"(x)); return r; }

DEVINL void wgmma_n192(float (&d)[96], uint64_t da, uint64_t db, int scale_d) {
  asm volatile("{\n.reg .pred p;\nsetp.ne.b32 p, %98, 0;\n"
    "wgmma.mma_async.sync.aligned.m64n192k16.f32.bf16.bf16 "
    "{%0,%1,%2,%3,%4,%5,%6,%7,%8,%9,%10,%11,%12,%13,%14,%15,"
    "%16,%17,%18,%19,%20,%21,%22,%23,%24,%25,%26,%27,%28,%29,%30,%31,"
    "%32,%33,%34,%35,%36,%37,%38,%39,%40,%41,%42,%43,%44,%45,%46,%47,"
    "%48,%49,%50,%51,%52,%53,%54,%55,%56,%57,%58,%59,%60,%61,%62,%63,"
    "%64,%65,%66,%67,%68,%69,%70,%71,%72,%73,%74,%75,%76,%77,%78,%79,"
    "%80,%81,%82,%83,%84,%85,%86,%87,%88,%89,%90,%91,%92,%93,%94,%95}, "
    "%96, %97, p, 1, 1, 0, 1;\n}\n"
    : "+f"(d[0]), "+f"(d[1]), "+f"(d[2]), "+f"(d[3]), "+f"(d[4]), "+f"(d[5]), "+f"(d[6]), "+f"(d[7]),
      "+f"(d[8]), "+f"(d[9]), "+f"(d[10]), "+f"(d[11]), "+f"(d[12]), "+f"(d[13]), "+f"(d[14]), "+f"(d[15]),
      "+f"(d[16]), "+f"(d[17]), "+f"(d[18]), "+f"(d[19]), "+f"(d[20]), "+f"(d[21]), "+f"(d[22]), "+f"(d[23]),
      "+f"(d[24]), "+f"(d[25]), "+f"(d[26]), "+f"(d[27]), "+f"(d[28]), "+f"(d[29]), "+f"(d[30]), "+f"(d[31]),
      "+f"(d[32]), "+f"(d[33]), "+f"(d[34]), "+f"(d[35]), "+f"(d[36]), "+f"(d[37]), "+f"(d[38]), "+f"(d[39]),
      "+f"(d[40]), "+f"(d[41]), "+f"(d[42]), "+f"(d[43]), "+f"(d[44]), "+f"(d[45]), "+f"(d[46]), "+f"(d[47]),
      "+f"(d[48]), "+f"(d[49]), "+f"(d[50]), "+f"(d[51]), "+f"(d[52]), "+f"(d[53]), "+f"(d[54]), "+f"(d[55]),
      "+f"(d[56]), "+f"(d[57]), "+f"(d[58]), "+f"(d[59]), "+f"(d[60]), "+f"(d[61]), "+f"(d[62]), "+f"(d[63]),
      "+f"(d[64]), "+f"(d[65]), "+f"(d[66]), "+f"(d[67]), "+f"(d[68]), "+f"(d[69]), "+f"(d[70]), "+f"(d[71]),
      "+f"(d[72]), "+f"(d[73]), "+f"(d[74]), "+f"(d[75]), "+f"(d[76]), "+f"(d[77]), "+f"(d[78]), "+f"(d[79]),
      "+f"(d[80]), "+f"(d[81]), "+f"(d[82]), "+f"(d[83]), "+f"(d[84]), "+f"(d[85]), "+f"(d[86]), "+f"(d[87]),
      "+f"(d[88]), "+f"(d[89]), "+f"(d[90]), "+f"(d[91]), "+f"(d[92]), "+f"(d[93]), "+f"(d[94]), "+f"(d[95])
    : "l"(da), "l"(db), "r"(scale_d));
}

DEVINL void wgmma_n48(float (&d)[24], uint64_t da, uint64_t db, int scale_d) {
  asm volatile("{\n.reg .pred p;\nsetp.ne.b32 p, %26, 0;\n"
    "wgmma.mma_async.sync.aligned.m64n48k16.f32.bf16.bf16 "
    "{%0,%1,%2,%3,%4,%5,%6,%7,%8,%9,%10,%11,%12,%13,%14,%15,"
    "%16,%17,%18,%19,%20,%21,%22,%23}, "
    "%24, %25, p, 1, 1, 0, 1;\n}\n"
    : "+f"(d[0]), "+f"(d[1]), "+f"(d[2]), "+f"(d[3]), "+f"(d[4]), "+f"(d[5]), "+f"(d[6]), "+f"(d[7]),
      "+f"(d[8]), "+f"(d[9]), "+f"(d[10]), "+f"(d[11]), "+f"(d[12]), "+f"(d[13]), "+f"(d[14]), "+f"(d[15]),
      "+f"(d[16]), "+f"(d[17]), "+f"(d[18]), "+f"(d[19]), "+f"(d[20]), "+f"(d[21]), "+f"(d[22]), "+f"(d[23])
    : "l"(da), "l"(db), "r"(scale_d));
}

DEVINL void wgmma_n80(float (&d)[40], uint64_t da, uint64_t db, int scale_d) {
  asm volatile("{\n.reg .pred p;\nsetp.ne.b32 p, %42, 0;\n"
    "wgmma.mma_async.sync.aligned.m64n80k16.f32.bf16.bf16 "
    "{%0,%1,%2,%3,%4,%5,%6,%7,%8,%9,%10,%11,%12,%13,%14,%15,"
    "%16,%17,%18,%19,%20,%21,%22,%23,%24,%25,%26,%27,%28,%29,%30,%31,"
    "%32,%33,%34,%35,%36,%37,%38,%39}, "
    "%40, %41, p, 1, 1, 0, 1;\n}\n"
    : "+f"(d[0]), "+f"(d[1]), "+f"(d[2]), "+f"(d[3]), "+f"(d[4]), "+f"(d[5]), "+f"(d[6]), "+f"(d[7]),
      "+f"(d[8]), "+f"(d[9]), "+f"(d[10]), "+f"(d[11]), "+f"(d[12]), "+f"(d[13]), "+f"(d[14]), "+f"(d[15]),
      "+f"(d[16]), "+f"(d[17]), "+f"(d[18]), "+f"(d[19]), "+f"(d[20]), "+f"(d[21]), "+f"(d[22]), "+f"(d[23]),
      "+f"(d[24]), "+f"(d[25]), "+f"(d[26]), "+f"(d[27]), "+f"(d[28]), "+f"(d[29]), "+f"(d[30]), "+f"(d[31]),
      "+f"(d[32]), "+f"(d[33]), "+f"(d[34]), "+f"(d[35]), "+f"(d[36]), "+f"(d[37]), "+f"(d[38]), "+f"(d[39])
    : "l"(da), "l"(db), "r"(scale_d));
}

constexpr float SM_C = 0.22360679774997896f * 1.4426950408889634f;
constexpr float NEG_INF = -INFINITY;

DEVINL void qk_block(float (&s0)[4], float (&s1)[4], const uint32_t (&a)[4], const uint32_t (&a8)[2],
                     uint32_t kaddr, uint32_t t0, uint32_t t1) {
  uint32_t b0, b1, b2, b3;
  ldsm4(b0, b1, b2, b3, kaddr);
  mma16816_z(s0, a[0], a[1], a[2], a[3], b0, b1);
  mma16816_z(s1, a[0], a[1], a[2], a[3], b2, b3);
  mma1688(s0, a8[0], a8[1], t0);
  mma1688(s1, a8[0], a8[1], t1);
}
DEVINL void pv_block(float (&o)[3][4], uint32_t p0, uint32_t p1, uint32_t p2, uint32_t p3, uint32_t vaddr,
                     uint32_t t0, uint32_t t1) {
  uint32_t b0, b1, b2, b3;
  ldsm4t(b0, b1, b2, b3, vaddr);
  mma16816(o[0], p0, p1, p2, p3, b0, b1);
  mma16816(o[1], p0, p1, p2, p3, b2, b3);
  mma16816(o[2], p0, p1, p2, p3, t0, t1);
}

template <bool FULL>
DEVINL void attn_head(float (&o)[3][4], const uint32_t (&a)[4], const uint32_t (&a8)[2], uint32_t kA, uint32_t kT,
                      uint32_t vA, uint32_t vT, int jmin, uint32_t tri, float& inv0, float& inv1) {
  float s[16][4];
  float m0, m1, l0, l1;
  {
    uint32_t t0, t1, t2, t3;
#pragma unroll
    for (int jj = 0; jj < 3; ++jj) {
      const int j = 9 + 2 * jj;
      ldsm4(t0, t1, t2, t3, kT + 1280 * j);
      if (FULL || j >= jmin) qk_block(s[4 * jj], s[4 * jj + 1], a, a8, kA + 1280 * j, t0, t1);
      else { for (int e = 0; e < 4; ++e) { s[4 * jj][e] = NEG_INF; s[4 * jj + 1][e] = NEG_INF; } }
      if (FULL || j + 1 >= jmin) qk_block(s[4 * jj + 2], s[4 * jj + 3], a, a8, kA + 1280 * (j + 1), t2, t3);
      else { for (int e = 0; e < 4; ++e) { s[4 * jj + 2][e] = NEG_INF; s[4 * jj + 3][e] = NEG_INF; } }
    }
    ldsm4(t0, t1, t2, t3, kT + 1280 * 15);
    if (FULL || 15 >= jmin) qk_block(s[12], s[13], a, a8, kA + 1280 * 15, t0, t1);
    else { for (int e = 0; e < 4; ++e) { s[12][e] = NEG_INF; s[13][e] = NEG_INF; } }
    qk_block(s[14], s[15], a, a8, kA + 1280 * 16, t2, t3);
    float z0[4], z1[4];
    if (FULL || jmin == 0) {
      ldsm2(t0, t1, kT);
      qk_block(z0, z1, a, a8, kA, t0, t1);
    } else {
      for (int e = 0; e < 4; ++e) { z0[e] = NEG_INF; z1[e] = NEG_INF; }
    }
    const bool c0 = tri & 1, c1 = tri >> 16;
    s[14][0] = c0 ? z0[0] : s[14][0];
    s[14][1] = c1 ? z0[1] : s[14][1];
    s[15][0] = z1[0];
    s[15][1] = z1[1];
    s[15][2] = c0 ? z1[2] : s[15][2];
    s[15][3] = c1 ? z1[3] : s[15][3];
  }
  m0 = fmaxf(s[0][0], s[0][1]);
  m1 = fmaxf(s[0][2], s[0][3]);
#pragma unroll
  for (int i = 1; i < 16; ++i) {
    m0 = fmaxf(m0, fmaxf(s[i][0], s[i][1]));
    m1 = fmaxf(m1, fmaxf(s[i][2], s[i][3]));
  }
  m0 = fmaxf(m0, __shfl_xor_sync(0xffffffffu, m0, 1));
  m1 = fmaxf(m1, __shfl_xor_sync(0xffffffffu, m1, 1));
  m0 = fmaxf(m0, __shfl_xor_sync(0xffffffffu, m0, 2));
  m1 = fmaxf(m1, __shfl_xor_sync(0xffffffffu, m1, 2));
  uint32_t p[16][2];
  {
    const float n0 = -m0 * SM_C, n1 = -m1 * SM_C;
    l0 = 0.f; l1 = 0.f;
#pragma unroll
    for (int i = 0; i < 16; ++i) {
      const float e0 = ex2(fmaf(s[i][0], SM_C, n0)), e1 = ex2(fmaf(s[i][1], SM_C, n0));
      const float e2 = ex2(fmaf(s[i][2], SM_C, n1)), e3 = ex2(fmaf(s[i][3], SM_C, n1));
      l0 += e0 + e1; l1 += e2 + e3;
      p[i][0] = pack_bf16(e0, e1);
      p[i][1] = pack_bf16(e2, e3);
    }
  }
#pragma unroll
  for (int n = 0; n < 3; ++n) { o[n][0] = 0.f; o[n][1] = 0.f; o[n][2] = 0.f; o[n][3] = 0.f; }
  {
    uint32_t t0, t1, t2, t3;
#pragma unroll
    for (int jj = 0; jj < 3; ++jj) {
      const int j = 9 + 2 * jj;
      ldsm4t(t0, t1, t2, t3, vT + 1280 * j);
      if (FULL || j >= jmin) pv_block(o, p[4 * jj][0], p[4 * jj][1], p[4 * jj + 1][0], p[4 * jj + 1][1], vA + 1280 * j, t0, t1);
      if (FULL || j + 1 >= jmin)
        pv_block(o, p[4 * jj + 2][0], p[4 * jj + 2][1], p[4 * jj + 3][0], p[4 * jj + 3][1], vA + 1280 * (j + 1), t2, t3);
    }
    ldsm4t(t0, t1, t2, t3, vT + 1280 * 15);
    if (FULL || 15 >= jmin) pv_block(o, p[12][0], p[12][1], p[13][0], p[13][1], vA + 1280 * 15, t0, t1);
    pv_block(o, p[14][0] & ~tri, p[14][1], 0u, p[15][1] & ~tri, vA + 1280 * 16, t2, t3);
    if (FULL || jmin == 0) {
      ldsm2t(t0, t1, vT);
      pv_block(o, p[14][0] & tri, 0u, p[15][0], p[15][1] & tri, vA, t0, t1);
    }
  }
  if (FULL || jmin <= 8) {
    {
      uint32_t t0, t1, t2, t3;
#pragma unroll
      for (int jj = 0; jj < 4; ++jj) {
        const int j = 1 + 2 * jj;
        ldsm4(t0, t1, t2, t3, kT + 1280 * j);
        if (FULL || j >= jmin) qk_block(s[4 * jj], s[4 * jj + 1], a, a8, kA + 1280 * j, t0, t1);
        else { for (int e = 0; e < 4; ++e) { s[4 * jj][e] = NEG_INF; s[4 * jj + 1][e] = NEG_INF; } }
        if (FULL || j + 1 >= jmin) qk_block(s[4 * jj + 2], s[4 * jj + 3], a, a8, kA + 1280 * (j + 1), t2, t3);
        else { for (int e = 0; e < 4; ++e) { s[4 * jj + 2][e] = NEG_INF; s[4 * jj + 3][e] = NEG_INF; } }
      }
    }
    float x0 = fmaxf(s[0][0], s[0][1]);
    float x1 = fmaxf(s[0][2], s[0][3]);
#pragma unroll
    for (int i = 1; i < 16; ++i) {
      x0 = fmaxf(x0, fmaxf(s[i][0], s[i][1]));
      x1 = fmaxf(x1, fmaxf(s[i][2], s[i][3]));
    }
    x0 = fmaxf(x0, __shfl_xor_sync(0xffffffffu, x0, 1));
    x1 = fmaxf(x1, __shfl_xor_sync(0xffffffffu, x1, 1));
    x0 = fmaxf(x0, __shfl_xor_sync(0xffffffffu, x0, 2));
    x1 = fmaxf(x1, __shfl_xor_sync(0xffffffffu, x1, 2));
    x0 = fmaxf(x0, m0);
    x1 = fmaxf(x1, m1);
    const float al0 = ex2((m0 - x0) * SM_C), al1 = ex2((m1 - x1) * SM_C);
    const float n0 = -x0 * SM_C, n1 = -x1 * SM_C;
    l0 *= al0; l1 *= al1;
#pragma unroll
    for (int i = 0; i < 16; ++i) {
      const float e0 = ex2(fmaf(s[i][0], SM_C, n0)), e1 = ex2(fmaf(s[i][1], SM_C, n0));
      const float e2 = ex2(fmaf(s[i][2], SM_C, n1)), e3 = ex2(fmaf(s[i][3], SM_C, n1));
      l0 += e0 + e1; l1 += e2 + e3;
      p[i][0] = pack_bf16(e0, e1);
      p[i][1] = pack_bf16(e2, e3);
    }
#pragma unroll
    for (int n = 0; n < 3; ++n) { o[n][0] *= al0; o[n][1] *= al0; o[n][2] *= al1; o[n][3] *= al1; }
    uint32_t t0, t1, t2, t3;
#pragma unroll
    for (int jj = 0; jj < 4; ++jj) {
      const int j = 1 + 2 * jj;
      ldsm4t(t0, t1, t2, t3, vT + 1280 * j);
      if (FULL || j >= jmin) pv_block(o, p[4 * jj][0], p[4 * jj][1], p[4 * jj + 1][0], p[4 * jj + 1][1], vA + 1280 * j, t0, t1);
      if (FULL || j + 1 >= jmin)
        pv_block(o, p[4 * jj + 2][0], p[4 * jj + 2][1], p[4 * jj + 3][0], p[4 * jj + 3][1], vA + 1280 * (j + 1), t2, t3);
    }
  }
  l0 += __shfl_xor_sync(0xffffffffu, l0, 1);
  l1 += __shfl_xor_sync(0xffffffffu, l1, 1);
  l0 += __shfl_xor_sync(0xffffffffu, l0, 2);
  l1 += __shfl_xor_sync(0xffffffffu, l1, 2);
  inv0 = __frcp_rn(l0);
  inv1 = __frcp_rn(l1);
}

template <bool FULL>
DEVINL void attn_all(const uint32_t (&qf)[10][2], uint32_t ring, uint32_t stg, uint32_t bars, int wq, int lane, int jmin) {
  const int g = lane >> 2, t = lane & 3, mi = lane >> 3, r = lane & 7;
  const uint32_t tri = ((2 * t > g) ? 0xFFFFu : 0u) | ((2 * t + 1 > g) ? 0xFFFF0000u : 0u);
  const uint32_t rowK = (16 * wq + r + 8 * (mi >> 1)) * 80 + (mi & 1) * 16;
  const uint32_t rowV = (16 * wq + r + 8 * (mi & 1)) * 80 + (mi >> 1) * 16;
  const uint32_t rowT = (16 * wq + r + 8 * mi) * 80;
  const uint32_t mlo = t < 2 ? 0xFFFFFFFFu : 0u;
#pragma unroll
  for (int p = 0; p < 2; ++p) {
    mbar_wait(bars + 8 * (B_HALO + p), 0);
    const uint32_t kw = ring + (2 * p) * KVWIN, vw = ring + (2 * p + 1) * KVWIN;
    uint32_t ev[3][2];
#pragma unroll
    for (int odd = 0; odd < 2; ++odd) {
      uint32_t a[4], a8[2];
      const int tb = 5 * p + (odd ? 3 : 0);
      a[0] = qf[tb][0]; a[1] = qf[tb][1]; a[2] = qf[tb + 1][0]; a[3] = qf[tb + 1][1];
      const uint32_t msk = odd ? ~mlo : mlo;
      a8[0] = qf[5 * p + 2][0] & msk; a8[1] = qf[5 * p + 2][1] & msk;
      float o[3][4], i0, i1;
      attn_head<FULL>(o, a, a8, kw + rowK + (odd ? 48 : 0), kw + rowT + 32, vw + rowV + (odd ? 32 : 0),
                      vw + rowT + (odd ? 64 : 32), jmin, tri, i0, i1);
      uint32_t w[3][2];
#pragma unroll
      for (int n = 0; n < 3; ++n) {
        w[n][0] = pack_bf16(o[n][0] * i0, o[n][1] * i0);
        w[n][1] = pack_bf16(o[n][2] * i1, o[n][3] * i1);
      }
      if (odd == 0) {
#pragma unroll
        for (int n = 0; n < 3; ++n) { ev[n][0] = w[n][0]; ev[n][1] = w[n][1]; }
      } else {
        const uint32_t base = stg + (16 * wq + g) * 160 + p * 80 + t * 4;
        sts32(base, ev[0][0]);            sts32(base + 1280, ev[0][1]);
        sts32(base + 16, ev[1][0]);       sts32(base + 16 + 1280, ev[1][1]);
        sts32(base + 32, t < 2 ? ev[2][0] : w[0][0]);
        sts32(base + 32 + 1280, t < 2 ? ev[2][1] : w[0][1]);
        sts32(base + 48, w[1][0]);        sts32(base + 48 + 1280, w[1][1]);
        sts32(base + 64, w[2][0]);        sts32(base + 64 + 1280, w[2][1]);
      }
    }
  }
}

struct Params {
  const uint16_t* q; const uint16_t* k; const uint16_t* v; const uint16_t* shift_k; const uint16_t* ssm_k;
  const uint16_t* ssm_D; uint16_t* out;
};

DEVINL unsigned* cnt(int i) { return &g_cnt[i * CS]; }

DEVINL void finish_role() {
  unsigned old = atomicAdd(cnt(C_DONE), 1u);
  if (old == 255u) {
    __threadfence();
    for (int i = 0; i < C_NUM; ++i) *cnt(i) = 0u;
    __threadfence();
  }
}

__global__ void __cluster_dims__(2, 1, 1) __launch_bounds__(512, 1)
h3_swa_fused_kernel(const __grid_constant__ CUtensorMap tmX, const __grid_constant__ CUtensorMap tmW128,
                    const __grid_constant__ CUtensorMap tmW32, const __grid_constant__ CUtensorMap tmO,
                    const __grid_constant__ CUtensorMap tmWo, const __grid_constant__ CUtensorMap tmOst,
                    const __grid_constant__ CUtensorMap tmOut, const Params prm) {
  extern __shared__ uint8_t smem_raw[];
  const uint32_t sb = ((uint32_t)__cvta_generic_to_shared(smem_raw) + 1023u) & ~1023u;
  const uint32_t bars = sb + OFF_BAR;
  const int tid = threadIdx.x, warp = tid >> 5, lane = tid & 31, wg = tid >> 7;
  const int cta = blockIdx.x;
  const uint32_t rank = cta & 1;
  const int g8 = (cta >> 1) & 7, rp = cta >> 4;
  const int rb = 2 * rp + rank;
  const int rb2 = 2 * rp + (g8 & 1);
  const int c2 = 2 * (g8 >> 1) + rank;

  if (tid == 0) {
    PROF(0);
    for (int i = 0; i < NST1; ++i) { mbar_init(bars + 8 * (B_FULL1 + i), 1); mbar_init(bars + 8 * (B_EMPTY1 + i), 16); }
    mbar_init(bars + 8 * B_RINGFREE, 1);
    mbar_init(bars + 8 * B_HALO, 1); mbar_init(bars + 8 * (B_HALO + 1), 1);
    for (int i = 0; i < NST2; ++i) { mbar_init(bars + 8 * (B_FULL2 + i), 1); mbar_init(bars + 8 * (B_EMPTY2 + i), 16); }
    mbar_init(bars + 8 * B_U, 1);
    asm volatile("fence.mbarrier_init.release.cluster;" ::: "memory");
  }
  __syncthreads();
  asm volatile("barrier.cluster.arrive.release;\nbarrier.cluster.wait.acquire;" ::: "memory");

  if (wg == 3) {
    asm volatile("setmaxnreg.dec.sync.aligned.u32 40;");
    if (warp == 12 && lane == 0) {
      for (int it = 0; it < 10; ++it) {
        const int s = it % NST1;
        if (it >= NST1) mbar_wait(bars + 8 * (B_EMPTY1 + s), ((it / NST1) - 1) & 1);
        const uint32_t st = sb + s * ST1, fb = bars + 8 * (B_FULL1 + s);
        mbar_expect(fb, ST1);
        tma2d(st, &tmX, it * 64, rb * 128, fb);
        tma3d_mc(st + ST1_B128 + rank * 12288, &tmW128, g8 * 80, it * 64 + rank * 32, 0, fb);
        tma3d_mc(st + ST1_B32 + rank * 3072, &tmW32, g8 * 80 + 64, it * 64 + rank * 32, 0, fb);
      }
      PROF(1);
      mbar_wait(bars + 8 * B_RINGFREE, 0);
      const int nh = rb >= 2 ? 256 : rb * 128;
      if (rb >= 1) poll_ge(cnt(C_KV + g8 * 16 + rb - 1), 32);
      if (rb >= 2) poll_ge(cnt(C_KV + g8 * 16 + rb - 2), 32);
      fence_async();
      PROF(2);
      for (int p = 0; p < 2; ++p) {
        const uint32_t hb = bars + 8 * (B_HALO + p);
        if (nh == 0) { mbar_arrive(hb); continue; }
        mbar_expect(hb, 2 * nh * 80);
        for (int kv = 0; kv < 2; ++kv)
          bulk_load(sb + (2 * p + kv) * KVWIN + (256 - nh) * 80,
                    g_kv + ((size_t)((g8 * 2 + p) * 2 + kv) * SEQ + (rb * 128 - nh)) * 40, nh * 80, hb);
      }
      for (int s = 0; s < NST2; ++s) {
        mbar_wait(bars + 8 * (B_EMPTY2 + s), 0);
        const uint32_t fb = bars + 8 * (B_FULL2 + s);
        mbar_expect(fb, ST2);
        tma3d(sb + s * ST2 + 16384, &tmWo, 0, s * 64, c2 * 5, fb);
      }
      PROF(3);
      poll_ge(cnt(C_O + rb2), 64);
      fence_async();
      PROF(4);
      for (int s = 0; s < NST2; ++s)
        tma2d_mc(sb + s * ST2 + rank * 8192, &tmO, s * 64, rb2 * 128 + rank * 64, bars + 8 * (B_FULL2 + s));
      for (int it = NST2; it < 10; ++it) {
        const int s = it - NST2;
        mbar_wait(bars + 8 * (B_EMPTY2 + s), 1);
        const uint32_t fb = bars + 8 * (B_FULL2 + s);
        mbar_expect(fb, ST2);
        tma3d(sb + s * ST2 + 16384, &tmWo, 0, it * 64, c2 * 5, fb);
        tma2d_mc(sb + s * ST2 + rank * 8192, &tmO, it * 64, rb2 * 128 + rank * 64, fb);
      }
      finish_role();
    }
  } else if (wg == 2) {
    asm volatile("setmaxnreg.inc.sync.aligned.u32 136;");
    const int ct = tid - 256, wc = warp - 8;
    const int tau = cta & 15, jt = cta >> 4;
    const int t0 = tau * 128, c0 = jt * 80;
    const int mi = lane >> 3, r = lane & 7, g = lane >> 2, t = lane & 3;
    const uint32_t U = sb + OFF_U, F = sb + OFF_F;
    for (int item = ct; item < 160; item += 128) {
      const int c = item % 10, seg = item / 10;
      const int ts = t0 + seg * 8, ch = c0 + c * 8;
      uint4 kk[11], vv[8], wv[4];
#pragma unroll
      for (int i = 0; i < 11; ++i) {
        const int row = ts - 3 + i;
        kk[i] = row >= 0 ? ldg_nc(prm.k + (size_t)row * DM + ch) : make_uint4(0, 0, 0, 0);
      }
#pragma unroll
      for (int i = 0; i < 8; ++i) vv[i] = ldg_nc(prm.v + (size_t)(ts + i) * DM + ch);
#pragma unroll
      for (int u = 0; u < 4; ++u) wv[u] = ldg_nc(prm.shift_k + (size_t)(ch + 2 * u) * 4);
      uint32_t W[4][4];
#pragma unroll
      for (int u = 0; u < 4; ++u) {
        W[0][u] = __byte_perm(wv[u].x, wv[u].z, 0x5410);
        W[1][u] = __byte_perm(wv[u].x, wv[u].z, 0x7632);
        W[2][u] = __byte_perm(wv[u].y, wv[u].w, 0x5410);
        W[3][u] = __byte_perm(wv[u].y, wv[u].w, 0x7632);
      }
#pragma unroll
      for (int i = 0; i < 8; ++i) {
        uint32_t res[4];
#pragma unroll
        for (int u = 0; u < 4; ++u) {
          const uint32_t k0 = (&kk[i].x)[u], k1 = (&kk[i + 1].x)[u], k2 = (&kk[i + 2].x)[u], k3 = (&kk[i + 3].x)[u];
          uint32_t acc = hadd2(hmul2(k0, W[3][u]), hmul2(k1, W[2][u]));
          acc = hadd2(acc, hmul2(k2, W[1][u]));
          acc = hadd2(acc, hmul2(k3, W[0][u]));
          res[u] = hmul2(acc, (&vv[i].x)[u]);
        }
        sts128(U + (seg * 8 + i) * 160 + c * 16, make_uint4(res[0], res[1], res[2], res[3]));
      }
    }
    named_sync(3, 128);
    for (int it = wc; it < 40; it += 4) {
      const int c = it % 10, rest = it / 10, h = rest & 1, iq = rest >> 1;
      const int tl = 16 * (4 * iq + (r >> 1)) + 15 - (8 * h + 2 * mi + (r & 1));
      uint4 v4;
      ldsm4t(v4.x, v4.y, v4.z, v4.w, U + tl * 160 + c * 16);
      stg128(g_kvT + (size_t)(c0 + c * 8 + g) * 2176 + h * 1088 + (8 + 8 * tau + 4 * iq + t) * 8, v4);
    }
    if (tau == 0) {
      for (int i = ct; i < 80 * 16; i += 128)
        stg128(g_kvT + (size_t)(c0 + (i >> 4)) * 2176 + ((i >> 3) & 1) * 1088 + (i & 7) * 8, make_uint4(0, 0, 0, 0));
    }
    __threadfence();
    named_sync(3, 128);
    if (ct == 0) { red_release(cnt(C_PRE + jt)); PROF(8); }
    {
      const int chb = cta * 5;
      uint4 fv[10]; uint32_t pv[10];
#pragma unroll
      for (int i = 0; i < 10; ++i) {
        const int cl = i >> 1, qq = ct + (i & 1) * 128;
        const uint16_t* src = prm.ssm_k + (size_t)(chb + cl) * SEQ + qq * 8;
        fv[i] = ldg_nc(src);
        pv[i] = qq > 0 ? (uint32_t)__ldg(src - 1) : 0u;
      }
#pragma unroll
      for (int i = 0; i < 10; ++i) {
        const int cl = i >> 1, qq = ct + (i & 1) * 128;
        const uint32_t a = F + cl * CH_F + 32 + qq * 16;
        sts128(a, fv[i]);
        sts128(a + 4160, make_uint4(__byte_perm(pv[i], fv[i].x, 0x5410), __byte_perm(fv[i].x, fv[i].y, 0x5432),
                                    __byte_perm(fv[i].y, fv[i].z, 0x5432), __byte_perm(fv[i].z, fv[i].w, 0x5432)));
      }
      if (ct < 20) sts128(F + (ct >> 2) * CH_F + ((ct >> 1) & 1) * 4160 + (ct & 1) * 16, make_uint4(0, 0, 0, 0));
    }
    if (ct == 0) {
      poll_ge(cnt(C_PRE + jt), 16);
      fence_async();
      mbar_expect(bars + 8 * B_U, 5 * CH_U);
      bulk_load(U, g_kvT + (size_t)cta * 5 * 2176, 5 * CH_U, bars + 8 * B_U);
      PROF(9);
    }
    named_sync(3, 128);
    mbar_wait(bars + 8 * B_U, 0);
    if (ct == 0) PROF(10);
#pragma unroll 1
    for (int pass = 0; pass < 2; ++pass) {
      const int cl = pass == 0 ? wc : 4;
      const int r0 = pass == 0 ? 0 : 2 * wc, r1 = pass == 0 ? 8 : 2 * wc + 2;
      const uint32_t Ub = U + cl * CH_U, Fb = F + cl * CH_F;
      const uint32_t laneU = Ub + (mi & 1) * 2176 + (8 + 8 * (mi >> 1) + r) * 16;
      const uint32_t laneF = (g & 1) ? Fb + 4160 + 2 * (17 - g + 2 * t) : Fb + 2 * (16 - g + 2 * t);
      float acc[16][4];
#pragma unroll
      for (int i = 0; i < 16; ++i) { acc[i][0] = 0.f; acc[i][1] = 0.f; acc[i][2] = 0.f; acc[i][3] = 0.f; }
#pragma unroll 1
      for (int rho = r0; rho < r1; ++rho) {
        uint32_t uf[16][2];
#pragma unroll
        for (int jj = 0; jj < 8; ++jj)
          ldsm4(uf[2 * jj][0], uf[2 * jj][1], uf[2 * jj + 1][0], uf[2 * jj + 1][1], laneU + jj * 256 - rho * 16);
        const uint32_t fb = laneF + 32 * rho;
#pragma unroll
        for (int mu = 0; mu < 16; ++mu) {
          const uint32_t a0 = lds32(fb + 256 * mu), a1 = lds32(fb + 256 * mu - 16), a2 = lds32(fb + 256 * mu + 16);
#pragma unroll
          for (int i = mu; i < 16; ++i) mma16816(acc[i], a0, a1, a2, a0, uf[i - mu][0], uf[i - mu][1]);
        }
      }
      const uint32_t dv = (uint32_t)__ldg(prm.ssm_D + cta * 5 + cl);
      const uint32_t D2 = dv | (dv << 16);
      if (pass == 0) {
        uint32_t res[8][4];
#pragma unroll
        for (int jj = 0; jj < 8; ++jj) {
          uint32_t u0, u1, u2, u3;
          ldsm4t(u0, u1, u2, u3, laneU + jj * 256);
          res[jj][0] = hadd2(pack_bf16(acc[2 * jj][0], acc[2 * jj][1]), hmul2(u0, D2));
          res[jj][1] = hadd2(pack_bf16(acc[2 * jj][2], acc[2 * jj][3]), hmul2(u1, D2));
          res[jj][2] = hadd2(pack_bf16(acc[2 * jj + 1][0], acc[2 * jj + 1][1]), hmul2(u2, D2));
          res[jj][3] = hadd2(pack_bf16(acc[2 * jj + 1][2], acc[2 * jj + 1][3]), hmul2(u3, D2));
        }
        __syncwarp();
#pragma unroll
        for (int jj = 0; jj < 8; ++jj)
          stsm4t(Ub + ((8 * (2 * jj + (mi >> 1)) + r) * 16 + 8 * (mi & 1)) * 2, res[jj][0], res[jj][1], res[jj][2], res[jj][3]);
        fence_async_smem();
        __syncwarp();
        if (lane == 0) {
          bulk_store(g_yT + (size_t)(cta * 5 + cl) * SEQ, Ub, 4096);
          bulk_commit();
          bulk_wait0();
          red_release(cnt(C_Y + jt));
        }
        __syncwarp();
      } else {
        const uint32_t rbuf = F + wc * CH_F + lane * 16;
#pragma unroll
        for (int i = 0; i < 16; ++i)
          sts128(rbuf + i * 512, make_uint4(__float_as_uint(acc[i][0]), __float_as_uint(acc[i][1]),
                                            __float_as_uint(acc[i][2]), __float_as_uint(acc[i][3])));
        named_sync(3, 128);
        uint32_t res[2][4];
#pragma unroll
        for (int jj = 0; jj < 2; ++jj) {
          float sum[2][4];
#pragma unroll
          for (int hh = 0; hh < 2; ++hh) {
            const int tile = 4 * wc + 2 * jj + hh;
            sum[hh][0] = 0.f; sum[hh][1] = 0.f; sum[hh][2] = 0.f; sum[hh][3] = 0.f;
#pragma unroll
            for (int w = 0; w < 4; ++w) {
              const uint4 x = lds128(F + w * CH_F + lane * 16 + tile * 512);
              sum[hh][0] += __uint_as_float(x.x); sum[hh][1] += __uint_as_float(x.y);
              sum[hh][2] += __uint_as_float(x.z); sum[hh][3] += __uint_as_float(x.w);
            }
          }
          uint32_t u0, u1, u2, u3;
          ldsm4t(u0, u1, u2, u3, laneU + (2 * wc + jj) * 256);
          res[jj][0] = hadd2(pack_bf16(sum[0][0], sum[0][1]), hmul2(u0, D2));
          res[jj][1] = hadd2(pack_bf16(sum[0][2], sum[0][3]), hmul2(u1, D2));
          res[jj][2] = hadd2(pack_bf16(sum[1][0], sum[1][1]), hmul2(u2, D2));
          res[jj][3] = hadd2(pack_bf16(sum[1][2], sum[1][3]), hmul2(u3, D2));
        }
#pragma unroll
        for (int jj = 0; jj < 2; ++jj)
          stsm4t(U + ((8 * (2 * (2 * wc + jj) + (mi >> 1)) + r) * 16 + 8 * (mi & 1)) * 2, res[jj][0], res[jj][1], res[jj][2], res[jj][3]);
        fence_async_smem();
        named_sync(3, 128);
        if (ct == 0) {
          bulk_store(g_yT + (size_t)(cta * 5 + 4) * SEQ, U, 4096);
          bulk_commit();
          bulk_wait0();
          red_release(cnt(C_Y + jt));
          PROF(11);
        }
      }
    }
    uint4 qv[10];
#pragma unroll
    for (int i = 0; i < 10; ++i) {
      const int idx = ct + 128 * i, row = idx / 10, c = idx % 10;
      qv[i] = ldg_nc(prm.q + (size_t)(t0 + row) * DM + c0 + c * 8);
    }
    if (ct == 0) { poll_ge(cnt(C_Y + jt), 80); finish_role(); PROF(12); }
    named_sync(3, 128);
    const uint32_t YT = sb + OFF_U, YN = sb + OFF_F + 1024;
#pragma unroll
    for (int i = 0; i < 10; ++i) {
      const int idx = ct + 128 * i, ch = idx >> 4, cq = idx & 15;
      sts128(YT + ch * 272 + cq * 16, ldg_cg(g_yT + (size_t)(c0 + ch) * SEQ + t0 + cq * 8));
    }
    named_sync(3, 128);
    for (int it = wc; it < 40; it += 4) {
      const int c = it % 10, tq = it / 10;
      uint32_t x0, x1, x2, x3;
      ldsm4t(x0, x1, x2, x3, YT + (8 * c + r) * 272 + (4 * tq + mi) * 16);
      const int s = (8 * (4 * tq + mi) + r) ^ 15;
      stsm4(YN + s * 176 + c * 16, x0, x1, x2, x3);
    }
    named_sync(3, 128);
#pragma unroll
    for (int i = 0; i < 10; ++i) {
      const int idx = ct + 128 * i, row = idx / 10, c = idx % 10;
      const uint4 y = lds128(YN + row * 176 + c * 16);
      stg128(prm.out + (size_t)(t0 + row) * (2 * DM) + c0 + c * 8,
             make_uint4(hmul2(qv[i].x, y.x), hmul2(qv[i].y, y.y), hmul2(qv[i].z, y.z), hmul2(qv[i].w, y.w)));
    }
    if (ct == 0) PROF(13);
  } else {
    asm volatile("setmaxnreg.inc.sync.aligned.u32 168;");
    const int wq = warp;
    const int mi = lane >> 3, r = lane & 7;
    uint32_t qf[10][2];
    {
      float acc1[96], acc2[24];
#pragma unroll 1
      for (int it = 0; it < 10; ++it) {
        const int s = it % NST1;
        mbar_wait(bars + 8 * (B_FULL1 + s), (it / NST1) & 1);
        if (it == 0 && tid == 0) PROF(16);
        const uint32_t st = sb + s * ST1;
        wg_fence();
#pragma unroll
        for (int kk = 0; kk < 4; ++kk) {
          const uint64_t da = make_desc(st + wg * 8192 + kk * 32, 16, 1024, 1);
          const uint64_t db1 = make_desc(st + ST1_B128 + (kk >> 1) * 12288 + (kk & 1) * 2048, 4096, 1024, 1);
          const uint64_t db2 = make_desc(st + ST1_B32 + (kk >> 1) * 3072 + (kk & 1) * 512, 1024, 256, 3);
          wgmma_n192(acc1, da, db1, (it | kk) != 0);
          wgmma_n48(acc2, da, db2, (it | kk) != 0);
        }
        wg_commit();
        if (it > 0) {
          wg_wait<1>();
          if (it - 1 + NST1 < 10 && lane < 2) mbar_arrive_cta(bars + 8 * (B_EMPTY1 + (it - 1) % NST1), lane);
        }
      }
      wg_wait<0>();
      if (tid == 0) PROF(17);
      named_sync(1, 256);
      if (tid == 0) mbar_arrive(bars + 8 * B_RINGFREE);
#pragma unroll
      for (int j = 0; j < 8; ++j) { qf[j][0] = pack_bf16(acc1[4 * j], acc1[4 * j + 1]); qf[j][1] = pack_bf16(acc1[4 * j + 2], acc1[4 * j + 3]); }
#pragma unroll
      for (int j = 0; j < 2; ++j) { qf[8 + j][0] = pack_bf16(acc2[4 * j], acc2[4 * j + 1]); qf[8 + j][1] = pack_bf16(acc2[4 * j + 2], acc2[4 * j + 3]); }
      const uint32_t rowa = sb + (256 + 16 * wq + 8 * (mi & 1) + r) * 80;
#pragma unroll
      for (int kv = 0; kv < 2; ++kv) {
#pragma unroll
        for (int tp = 0; tp < 5; ++tp) {
          uint32_t w[4];
#pragma unroll
          for (int hh = 0; hh < 2; ++hh) {
            const int tile = 2 * tp + hh;
            if (tile < 8) {
              const int o = 32 * (kv + 1) + 4 * tile;
              w[2 * hh] = pack_bf16(acc1[o], acc1[o + 1]); w[2 * hh + 1] = pack_bf16(acc1[o + 2], acc1[o + 3]);
            } else {
              const int o = 8 * (kv + 1) + 4 * (tile - 8);
              w[2 * hh] = pack_bf16(acc2[o], acc2[o + 1]); w[2 * hh + 1] = pack_bf16(acc2[o + 2], acc2[o + 3]);
            }
          }
          const int tA = 2 * tp, tB = 2 * tp + 1;
          const uint32_t offA = ((tA / 5) * 2 + kv) * KVWIN + (tA % 5) * 16;
          const uint32_t offB = ((tB / 5) * 2 + kv) * KVWIN + (tB % 5) * 16;
          stsm4(rowa + ((mi >> 1) ? offB : offA), w[0], w[1], w[2], w[3]);
        }
      }
    }
    fence_async_smem();
    __syncwarp();
    if (lane < 4) {
      const int p = lane >> 1, kv = lane & 1;
      bulk_store(g_kv + ((size_t)((g8 * 2 + p) * 2 + kv) * SEQ + rb * 128 + 16 * wq) * 40,
                 sb + (2 * p + kv) * KVWIN + (256 + 16 * wq) * 80, 1280);
      bulk_commit();
      bulk_wait0();
      red_release(cnt(C_KV + g8 * 16 + rb));
    }
    named_sync(2, 256);
    if (tid == 0) PROF(18);
    const uint32_t stg = sb + OFF_STG;
    if (rb >= 2) attn_all<true>(qf, sb, stg, bars, wq, lane, 0);
    else attn_all<false>(qf, sb, stg, bars, wq, lane, max(0, 16 - 8 * rb - wq));
    if (tid == 0) PROF(19);
    fence_async_smem();
    __syncwarp();
    if (lane < 2 * NST2) mbar_arrive_cta(bars + 8 * (B_EMPTY2 + (lane >> 1)), lane & 1);
    if (lane == 0) {
      tma2d_store(&tmOst, g8 * 80, rb * 128 + 16 * wq, stg + wq * 2560);
      bulk_commit();
      bulk_wait0();
      red_release(cnt(C_O + rb));
    }
    __syncwarp();
    if (tid == 0) PROF(20);
    float acc[40];
#pragma unroll 1
    for (int it = 0; it < 10; ++it) {
      const int s = it % NST2;
      mbar_wait(bars + 8 * (B_FULL2 + s), (it / NST2) & 1);
      if (it == 0 && tid == 0) PROF(21);
      const uint32_t st = sb + s * ST2;
      wg_fence();
#pragma unroll
      for (int kk = 0; kk < 4; ++kk)
        wgmma_n80(acc, make_desc(st + wg * 8192 + kk * 32, 16, 1024, 1), make_desc(st + 16384 + kk * 512, 2048, 256, 3), (it | kk) != 0);
      wg_commit();
      if (it > 0) {
        wg_wait<1>();
        if (it - 1 + NST2 < 10 && lane < 2) mbar_arrive_cta(bars + 8 * (B_EMPTY2 + (it - 1) % NST2), lane);
      }
    }
    wg_wait<0>();
    if (tid == 0) PROF(22);
    {
      const uint32_t rowa = stg + (16 * wq + 8 * (mi & 1) + r) * 160 + (mi >> 1) * 16;
#pragma unroll
      for (int tp = 0; tp < 5; ++tp)
        stsm4(rowa + tp * 32, pack_bf16(acc[8 * tp], acc[8 * tp + 1]), pack_bf16(acc[8 * tp + 2], acc[8 * tp + 3]),
              pack_bf16(acc[8 * tp + 4], acc[8 * tp + 5]), pack_bf16(acc[8 * tp + 6], acc[8 * tp + 7]));
      fence_async_smem();
      __syncwarp();
      if (lane == 0) {
        tma2d_store(&tmOut, DM + c2 * 80, rb2 * 128 + 16 * wq, stg + wq * 2560);
        bulk_commit();
        bulk_wait0_read();
      }
    }
    if (tid == 0) PROF(23);
  }
}

typedef CUresult (*EncodeFn)(CUtensorMap*, CUtensorMapDataType, cuuint32_t, void*, const cuuint64_t*, const cuuint64_t*,
                             const cuuint32_t*, const cuuint32_t*, CUtensorMapInterleave, CUtensorMapSwizzle,
                             CUtensorMapL2promotion, CUtensorMapFloatOOBfill);

CUtensorMap make_map(EncodeFn enc, const void* p, int rank, const cuuint64_t* dims, const cuuint64_t* strides,
                     const cuuint32_t* box, CUtensorMapSwizzle sw) {
  CUtensorMap m;
  const cuuint32_t es[3] = {1, 1, 1};
  enc(&m, CU_TENSOR_MAP_DATA_TYPE_BFLOAT16, rank, const_cast<void*>(p), dims, strides, box, es,
      CU_TENSOR_MAP_INTERLEAVE_NONE, sw, CU_TENSOR_MAP_L2_PROMOTION_L2_128B, CU_TENSOR_MAP_FLOAT_OOB_FILL_NONE);
  return m;
}

}

extern "C" void kernel_launch(void* const* d_in, const int* in_sizes, int n_in, void* d_out, int out_size) {
  (void)in_sizes; (void)n_in; (void)out_size;
  static EncodeFn enc = nullptr;
  static void* o_ptr = nullptr;
  if (!enc) {
    void* fn = nullptr;
    cudaDriverEntryPointQueryResult qr;
    cudaGetDriverEntryPoint("cuTensorMapEncodeTiled", &fn, cudaEnableDefault, &qr);
    enc = (EncodeFn)fn;
    cudaGetSymbolAddress(&o_ptr, g_o);
    cudaFuncSetAttribute(h3_swa_fused_kernel, cudaFuncAttributeMaxDynamicSharedMemorySize, SMEM_BYTES);
  }
  const void* x = d_in[6];
  const void* wqkv = d_in[7];
  const void* wo = d_in[8];
  CUtensorMap tmX, tmW128, tmW32, tmO, tmWo, tmOst, tmOut;
  { cuuint64_t d[2] = {640, 2048}, s[1] = {1280}; cuuint32_t b[2] = {64, 128};
    tmX = make_map(enc, x, 2, d, s, b, CU_TENSOR_MAP_SWIZZLE_128B); }
  { cuuint64_t d[3] = {640, 640, 3}, s[2] = {3840, 1280}; cuuint32_t b[3] = {64, 32, 3};
    tmW128 = make_map(enc, wqkv, 3, d, s, b, CU_TENSOR_MAP_SWIZZLE_128B); }
  { cuuint64_t d[3] = {640, 640, 3}, s[2] = {3840, 1280}; cuuint32_t b[3] = {16, 32, 3};
    tmW32 = make_map(enc, wqkv, 3, d, s, b, CU_TENSOR_MAP_SWIZZLE_32B); }
  { cuuint64_t d[2] = {640, 2048}, s[1] = {1280}; cuuint32_t b[2] = {64, 64};
    tmO = make_map(enc, o_ptr, 2, d, s, b, CU_TENSOR_MAP_SWIZZLE_128B); }
  { cuuint64_t d[3] = {16, 640, 40}, s[2] = {1280, 32}; cuuint32_t b[3] = {16, 64, 5};
    tmWo = make_map(enc, wo, 3, d, s, b, CU_TENSOR_MAP_SWIZZLE_32B); }
  { cuuint64_t d[2] = {640, 2048}, s[1] = {1280}; cuuint32_t b[2] = {80, 16};
    tmOst = make_map(enc, o_ptr, 2, d, s, b, CU_TENSOR_MAP_SWIZZLE_NONE); }
  { cuuint64_t d[2] = {1280, 2048}, s[1] = {2560}; cuuint32_t b[2] = {80, 16};
    tmOut = make_map(enc, d_out, 2, d, s, b, CU_TENSOR_MAP_SWIZZLE_NONE); }
  Params prm;
  prm.q = (const uint16_t*)d_in[0]; prm.k = (const uint16_t*)d_in[1]; prm.v = (const uint16_t*)d_in[2];
  prm.shift_k = (const uint16_t*)d_in[3]; prm.ssm_k = (const uint16_t*)d_in[4]; prm.ssm_D = (const uint16_t*)d_in[5];
  prm.out = (uint16_t*)d_out;
  h3_swa_fused_kernel<<<128, 512, SMEM_BYTES>>>(tmX, tmW128, tmW32, tmO, tmWo, tmOst, tmOut, prm);
}
```

```cpp
#include <cuda_runtime.h>
#include <cuda.h>
#include <cuda_bf16.h>
#include <stdint.h>

#define DEVINL __device__ __forceinline__

namespace {

constexpr int SEQ = 2048;
constexpr int DM = 640;

constexpr int ST1 = 47104;
constexpr int ST1_B128 = 16384;
constexpr int ST1_B32 = 40960;
constexpr int NST1 = 3;
constexpr int KVWIN = 30720;
constexpr int ST2 = 26624;
constexpr int NST2 = 5;
constexpr int OFF_CONV = NST1 * ST1;
constexpr int CH_U = 4352;
constexpr int CH_F = 8320;
constexpr int OFF_U = OFF_CONV;
constexpr int OFF_F = OFF_CONV + 5 * CH_U;
constexpr int OFF_STG = OFF_F + 5 * CH_F;
constexpr int OFF_BAR = OFF_STG + 20480;
constexpr int SMEM_BYTES = OFF_BAR + 256 + 1024;

constexpr int B_FULL1 = 0, B_EMPTY1 = 3, B_RINGFREE = 6, B_HALO = 7, B_FULL2 = 9, B_EMPTY2 = 14, B_U = 19, B_COUNT = 20;

__device__ __align__(1024) uint16_t g_kv[8 * 2 * 2 * SEQ * 40];
__device__ __align__(1024) uint16_t g_o[SEQ * DM];
__device__ __align__(1024) uint16_t g_kvT[DM * 2176];
__device__ __align__(1024) uint16_t g_yT[DM * SEQ];
constexpr int CS = 32;
constexpr int C_KV = 0, C_O = 128, C_PRE = 144, C_Y = 152, C_DONE = 160, C_NUM = 161;
__device__ unsigned g_cnt[C_NUM * CS];
__device__ unsigned g_err;
#define PROF(slot) do {} while (0)

DEVINL void mbar_init(uint32_t a, uint32_t c) { asm volatile("mbarrier.init.shared::cta.b64 [%0], %1;" ::"r"(a), "r"(c)); }
DEVINL void mbar_expect(uint32_t a, uint32_t b) {
  asm volatile("mbarrier.arrive.expect_tx.shared::cta.b64 _, [%0], %1;" ::"r"(a), "r"(b) : "memory");
}
DEVINL void mbar_arrive(uint32_t a) { asm volatile("mbarrier.arrive.shared::cta.b64 _, [%0];" ::"r"(a) : "memory"); }
DEVINL void mbar_arrive_cta(uint32_t a, uint32_t cta) {
  asm volatile("{\n.reg .b32 ra;\nmapa.shared::cluster.u32 ra, %0, %1;\nmbarrier.arrive.shared::cluster.b64 _, [ra];\n}"
               ::"r"(a), "r"(cta) : "memory");
}
DEVINL bool mbar_try(uint32_t a, uint32_t p) {
  uint32_t ok;
  asm volatile("{\n.reg .pred P;\nmbarrier.try_wait.parity.shared::cta.b64 P, [%1], %2;\nselp.u32 %0, 1, 0, P;\n}"
               : "=r"(ok) : "r"(a), "r"(p) : "memory");
  return ok;
}
DEVINL void mbar_wait(uint32_t a, uint32_t p) {
  if (mbar_try(a, p)) return;
  int n = 0;
  while (!mbar_try(a, p)) {
    if (++n > (1 << 18)) { g_err = 1; break; }
  }
}
DEVINL void poll_ge(const unsigned* p, unsigned target) {
  int n = 0;
  while (true) {
    unsigned v;
    asm volatile("ld.acquire.gpu.global.u32 %0, [%1];" : "=r"(v) : "l"(p) : "memory");
    if (v >= target) break;
    if (++n > (1 << 20)) { g_err = 2; break; }
  }
}
DEVINL void red_release(unsigned* p) { asm volatile("red.release.gpu.global.add.u32 [%0], 1;" ::"l"(p) : "memory"); }
DEVINL void fence_async() { asm volatile("fence.proxy.async;" ::: "memory"); }
DEVINL void fence_async_smem() { asm volatile("fence.proxy.async.shared::cta;" ::: "memory"); }
DEVINL void named_sync(int id, int n) { asm volatile("bar.sync %0, %1;" ::"r"(id), "r"(n) : "memory"); }

DEVINL void tma2d(uint32_t dst, const CUtensorMap* m, int c0, int c1, uint32_t bar) {
  asm volatile("cp.async.bulk.tensor.2d.shared::cluster.global.mbarrier::complete_tx::bytes [%0], [%1, {%3, %4}], [%2];"
               ::"r"(dst), "l"(m), "r"(bar), "r"(c0), "r"(c1) : "memory");
}
DEVINL void tma2d_mc(uint32_t dst, const CUtensorMap* m, int c0, int c1, uint32_t bar) {
  asm volatile("cp.async.bulk.tensor.2d.shared::cluster.global.mbarrier::complete_tx::bytes.multicast::cluster [%0], [%1, {%3, %4}], [%2], %5;"
               ::"r"(dst), "l"(m), "r"(bar), "r"(c0), "r"(c1), "h"((uint16_t)3) : "memory");
}
DEVINL void tma3d(uint32_t dst, const CUtensorMap* m, int c0, int c1, int c2, uint32_t bar) {
  asm volatile("cp.async.bulk.tensor.3d.shared::cluster.global.mbarrier::complete_tx::bytes [%0], [%1, {%3, %4, %5}], [%2];"
               ::"r"(dst), "l"(m), "r"(bar), "r"(c0), "r"(c1), "r"(c2) : "memory");
}
DEVINL void tma3d_mc(uint32_t dst, const CUtensorMap* m, int c0, int c1, int c2, uint32_t bar) {
  asm volatile("cp.async.bulk.tensor.3d.shared::cluster.global.mbarrier::complete_tx::bytes.multicast::cluster [%0], [%1, {%3, %4, %5}], [%2], %6;"
               ::"r"(dst), "l"(m), "r"(bar), "r"(c0), "r"(c1), "r"(c2), "h"((uint16_t)3) : "memory");
}
DEVINL void tma2d_store(const CUtensorMap* m, int c0, int c1, uint32_t src) {
  asm volatile("cp.async.bulk.tensor.2d.global.shared::cta.bulk_group [%0, {%2, %3}], [%1];"
               ::"l"(m), "r"(src), "r"(c0), "r"(c1) : "memory");
}
DEVINL void bulk_load(uint32_t dst, const void* src, uint32_t bytes, uint32_t bar) {
  asm volatile("cp.async.bulk.shared::cluster.global.mbarrier::complete_tx::bytes [%0], [%1], %2, [%3];"
               ::"r"(dst), "l"(src), "r"(bytes), "r"(bar) : "memory");
}
DEVINL void bulk_store(void* dst, uint32_t src, uint32_t bytes) {
  asm volatile("cp.async.bulk.global.shared::cta.bulk_group [%0], [%1], %2;" ::"l"(dst), "r"(src), "r"(bytes) : "memory");
}
DEVINL void bulk_commit() { asm volatile("cp.async.bulk.commit_group;" ::: "memory"); }
DEVINL void bulk_wait0() { asm volatile("cp.async.bulk.wait_group 0;" ::: "memory"); }
DEVINL void bulk_wait0_read() { asm volatile("cp.async.bulk.wait_group.read 0;" ::: "memory"); }
DEVINL void prefetch_tmap(const CUtensorMap* m) { asm volatile("prefetch.tensormap [%0];" ::"l"(m) : "memory"); }

DEVINL uint64_t make_desc(uint32_t addr, uint32_t lbo, uint32_t sbo, uint32_t swz) {
  return (uint64_t)((addr & 0x3FFFF) >> 4) | ((uint64_t)(lbo >> 4) << 16) | ((uint64_t)(sbo >> 4) << 32) | ((uint64_t)swz << 62);
}
DEVINL void wg_fence() { asm volatile("wgmma.fence.sync.aligned;" ::: "memory"); }
DEVINL void wg_commit() { asm volatile("wgmma.commit_group.sync.aligned;" ::: "memory"); }
template <int N> DEVINL void wg_wait() { asm volatile("wgmma.wait_group.sync.aligned %0;" ::"n"(N) : "memory"); }

DEVINL void mma16816(float (&d)[4], uint32_t a0, uint32_t a1, uint32_t a2, uint32_t a3, uint32_t b0, uint32_t b1) {
  asm volatile("mma.sync.aligned.m16n8k16.row.col.f32.bf16.bf16.f32 {%0,%1,%2,%3},{%4,%5,%6,%7},{%8,%9},{%0,%1,%2,%3};"
               : "+f"(d[0]), "+f"(d[1]), "+f"(d[2]), "+f"(d[3]) : "r"(a0), "r"(a1), "r"(a2), "r"(a3), "r"(b0), "r"(b1));
}
DEVINL void mma16816_z(float (&d)[4], uint32_t a0, uint32_t a1, uint32_t a2, uint32_t a3, uint32_t b0, uint32_t b1) {
  asm volatile("mma.sync.aligned.m16n8k16.row.col.f32.bf16.bf16.f32 {%0,%1,%2,%3},{%4,%5,%6,%7},{%8,%9},{%10,%10,%10,%10};"
               : "=f"(d[0]), "=f"(d[1]), "=f"(d[2]), "=f"(d[3]) : "r"(a0), "r"(a1), "r"(a2), "r"(a3), "r"(b0), "r"(b1), "f"(0.f));
}
DEVINL void mma1688(float (&d)[4], uint32_t a0, uint32_t a1, uint32_t b0) {
  asm volatile("mma.sync.aligned.m16n8k8.row.col.f32.bf16.bf16.f32 {%0,%1,%2,%3},{%4,%5},{%6},{%0,%1,%2,%3};"
               : "+f"(d[0]), "+f"(d[1]), "+f"(d[2]), "+f"(d[3]) : "r"(a0), "r"(a1), "r"(b0));
}
DEVINL void ldsm4(uint32_t& r0, uint32_t& r1, uint32_t& r2, uint32_t& r3, uint32_t a) {
  asm volatile("ldmatrix.sync.aligned.m8n8.x4.shared.b16 {%0,%1,%2,%3}, [%4];" : "=r"(r0), "=r"(r1), "=r"(r2), "=r"(r3) : "r"(a));
}
DEVINL void ldsm2(uint32_t& r0, uint32_t& r1, uint32_t a) {
  asm volatile("ldmatrix.sync.aligned.m8n8.x2.shared.b16 {%0,%1}, [%2];" : "=r"(r0), "=r"(r1) : "r"(a));
}
DEVINL void ldsm4t(uint32_t& r0, uint32_t& r1, uint32_t& r2, uint32_t& r3, uint32_t a) {
  asm volatile("ldmatrix.sync.aligned.m8n8.x4.trans.shared.b16 {%0,%1,%2,%3}, [%4];" : "=r"(r0), "=r"(r1), "=r"(r2), "=r"(r3) : "r"(a));
}
DEVINL void ldsm2t(uint32_t& r0, uint32_t& r1, uint32_t a) {
  asm volatile("ldmatrix.sync.aligned.m8n8.x2.trans.shared.b16 {%0,%1}, [%2];" : "=r"(r0), "=r"(r1) : "r"(a));
}
DEVINL void stsm4(uint32_t a, uint32_t r0, uint32_t r1, uint32_t r2, uint32_t r3) {
  asm volatile("stmatrix.sync.aligned.m8n8.x4.shared.b16 [%0], {%1,%2,%3,%4};" ::"r"(a), "r"(r0), "r"(r1), "r"(r2), "r"(r3) : "memory");
}
DEVINL void stsm4t(uint32_t a, uint32_t r0, uint32_t r1, uint32_t r2, uint32_t r3) {
  asm volatile("stmatrix.sync.aligned.m8n8.x4.trans.shared.b16 [%0], {%1,%2,%3,%4};" ::"r"(a), "r"(r0), "r"(r1), "r"(r2), "r"(r3) : "memory");
}
DEVINL uint32_t lds32(uint32_t a) { uint32_t v; asm volatile("ld.shared.u32 %0, [%1];" : "=r"(v) : "r"(a)); return v; }
DEVINL uint4 lds128(uint32_t a) {
  uint4 v; asm volatile("ld.shared.v4.u32 {%0,%1,%2,%3}, [%4];" : "=r"(v.x), "=r"(v.y), "=r"(v.z), "=r"(v.w) : "r"(a)); return v;
}
DEVINL void sts32(uint32_t a, uint32_t v) { asm volatile("st.shared.u32 [%0], %1;" ::"r"(a), "r"(v) : "memory"); }
DEVINL void sts128(uint32_t a, uint4 v) {
  asm volatile("st.shared.v4.u32 [%0], {%1,%2,%3,%4};" ::"r"(a), "r"(v.x), "r"(v.y), "r"(v.z), "r"(v.w) : "memory");
}
DEVINL uint4 ldg_nc(const void* p) {
  uint4 v; asm volatile("ld.global.nc.L1::no_allocate.v4.u32 {%0,%1,%2,%3}, [%4];" : "=r"(v.x), "=r"(v.y), "=r"(v.z), "=r"(v.w) : "l"(p)); return v;
}
DEVINL uint4 ldg_cg(const void* p) {
  uint4 v; asm volatile("ld.global.cg.v4.u32 {%0,%1,%2,%3}, [%4];" : "=r"(v.x), "=r"(v.y), "=r"(v.z), "=r"(v.w) : "l"(p) : "memory"); return v;
}
DEVINL void stg128(void* p, uint4 v) {
  asm volatile("st.global.v4.u32 [%0], {%1,%2,%3,%4};" ::"l"(p), "r"(v.x), "r"(v.y), "r"(v.z), "r"(v.w) : "memory");
}
DEVINL uint32_t pack_bf16(float lo, float hi) {
  uint32_t r; asm("cvt.rn.bf16x2.f32 %0, %1, %2;" : "=r"(r) : "f"(hi), "f"(lo)); return r;
}
DEVINL uint32_t hmul2(uint32_t a, uint32_t b) { uint32_t r; asm("mul.rn.bf16x2 %0, %1, %2;" : "=r"(r) : "r"(a), "r"(b)); return r; }
DEVINL uint32_t hadd2(uint32_t a, uint32_t b) { uint32_t r; asm("add.rn.bf16x2 %0, %1, %2;" : "=r"(r) : "r"(a), "r"(b)); return r; }
DEVINL float ex2(float x) { float r; asm("ex2.approx.ftz.f32 %0, %1;" : "=f"(r) : "f"(x)); return r; }

DEVINL void wgmma_n192(float (&d)[96], uint64_t da, uint64_t db, int scale_d) {
  asm volatile("{\n.reg .pred p;\nsetp.ne.b32 p, %98, 0;\n"
    "wgmma.mma_async.sync.aligned.m64n192k16.f32.bf16.bf16 "
    "{%0,%1,%2,%3,%4,%5,%6,%7,%8,%9,%10,%11,%12,%13,%14,%15,"
    "%16,%17,%18,%19,%20,%21,%22,%23,%24,%25,%26,%27,%28,%29,%30,%31,"
    "%32,%33,%34,%35,%36,%37,%38,%39,%40,%41,%42,%43,%44,%45,%46,%47,"
    "%48,%49,%50,%51,%52,%53,%54,%55,%56,%57,%58,%59,%60,%61,%62,%63,"
    "%64,%65,%66,%67,%68,%69,%70,%71,%72,%73,%74,%75,%76,%77,%78,%79,"
    "%80,%81,%82,%83,%84,%85,%86,%87,%88,%89,%90,%91,%92,%93,%94,%95}, "
    "%96, %97, p, 1, 1, 0, 1;\n}\n"
    : "+f"(d[0]), "+f"(d[1]), "+f"(d[2]), "+f"(d[3]), "+f"(d[4]), "+f"(d[5]), "+f"(d[6]), "+f"(d[7]),
      "+f"(d[8]), "+f"(d[9]), "+f"(d[10]), "+f"(d[11]), "+f"(d[12]), "+f"(d[13]), "+f"(d[14]), "+f"(d[15]),
      "+f"(d[16]), "+f"(d[17]), "+f"(d[18]), "+f"(d[19]), "+f"(d[20]), "+f"(d[21]), "+f"(d[22]), "+f"(d[23]),
      "+f"(d[24]), "+f"(d[25]), "+f"(d[26]), "+f"(d[27]), "+f"(d[28]), "+f"(d[29]), "+f"(d[30]), "+f"(d[31]),
      "+f"(d[32]), "+f"(d[33]), "+f"(d[34]), "+f"(d[35]), "+f"(d[36]), "+f"(d[37]), "+f"(d[38]), "+f"(d[39]),
      "+f"(d[40]), "+f"(d[41]), "+f"(d[42]), "+f"(d[43]), "+f"(d[44]), "+f"(d[45]), "+f"(d[46]), "+f"(d[47]),
      "+f"(d[48]), "+f"(d[49]), "+f"(d[50]), "+f"(d[51]), "+f"(d[52]), "+f"(d[53]), "+f"(d[54]), "+f"(d[55]),
      "+f"(d[56]), "+f"(d[57]), "+f"(d[58]), "+f"(d[59]), "+f"(d[60]), "+f"(d[61]), "+f"(d[62]), "+f"(d[63]),
      "+f"(d[64]), "+f"(d[65]), "+f"(d[66]), "+f"(d[67]), "+f"(d[68]), "+f"(d[69]), "+f"(d[70]), "+f"(d[71]),
      "+f"(d[72]), "+f"(d[73]), "+f"(d[74]), "+f"(d[75]), "+f"(d[76]), "+f"(d[77]), "+f"(d[78]), "+f"(d[79]),
      "+f"(d[80]), "+f"(d[81]), "+f"(d[82]), "+f"(d[83]), "+f"(d[84]), "+f"(d[85]), "+f"(d[86]), "+f"(d[87]),
      "+f"(d[88]), "+f"(d[89]), "+f"(d[90]), "+f"(d[91]), "+f"(d[92]), "+f"(d[93]), "+f"(d[94]), "+f"(d[95])
    : "l"(da), "l"(db), "r"(scale_d));
}

DEVINL void wgmma_n48(float (&d)[24], uint64_t da, uint64_t db, int scale_d) {
  asm volatile("{\n.reg .pred p;\nsetp.ne.b32 p, %26, 0;\n"
    "wgmma.mma_async.sync.aligned.m64n48k16.f32.bf16.bf16 "
    "{%0,%1,%2,%3,%4,%5,%6,%7,%8,%9,%10,%11,%12,%13,%14,%15,"
    "%16,%17,%18,%19,%20,%21,%22,%23}, "
    "%24, %25, p, 1, 1, 0, 1;\n}\n"
    : "+f"(d[0]), "+f"(d[1]), "+f"(d[2]), "+f"(d[3]), "+f"(d[4]), "+f"(d[5]), "+f"(d[6]), "+f"(d[7]),
      "+f"(d[8]), "+f"(d[9]), "+f"(d[10]), "+f"(d[11]), "+f"(d[12]), "+f"(d[13]), "+f"(d[14]), "+f"(d[15]),
      "+f"(d[16]), "+f"(d[17]), "+f"(d[18]), "+f"(d[19]), "+f"(d[20]), "+f"(d[21]), "+f"(d[22]), "+f"(d[23])
    : "l"(da), "l"(db), "r"(scale_d));
}

DEVINL void wgmma_n80(float (&d)[40], uint64_t da, uint64_t db, int scale_d) {
  asm volatile("{\n.reg .pred p;\nsetp.ne.b32 p, %42, 0;\n"
    "wgmma.mma_async.sync.aligned.m64n80k16.f32.bf16.bf16 "
    "{%0,%1,%2,%3,%4,%5,%6,%7,%8,%9,%10,%11,%12,%13,%14,%15,"
    "%16,%17,%18,%19,%20,%21,%22,%23,%24,%25,%26,%27,%28,%29,%30,%31,"
    "%32,%33,%34,%35,%36,%37,%38,%39}, "
    "%40, %41, p, 1, 1, 0, 1;\n}\n"
    : "+f"(d[0]), "+f"(d[1]), "+f"(d[2]), "+f"(d[3]), "+f"(d[4]), "+f"(d[5]), "+f"(d[6]), "+f"(d[7]),
      "+f"(d[8]), "+f"(d[9]), "+f"(d[10]), "+f"(d[11]), "+f"(d[12]), "+f"(d[13]), "+f"(d[14]), "+f"(d[15]),
      "+f"(d[16]), "+f"(d[17]), "+f"(d[18]), "+f"(d[19]), "+f"(d[20]), "+f"(d[21]), "+f"(d[22]), "+f"(d[23]),
      "+f"(d[24]), "+f"(d[25]), "+f"(d[26]), "+f"(d[27]), "+f"(d[28]), "+f"(d[29]), "+f"(d[30]), "+f"(d[31]),
      "+f"(d[32]), "+f"(d[33]), "+f"(d[34]), "+f"(d[35]), "+f"(d[36]), "+f"(d[37]), "+f"(d[38]), "+f"(d[39])
    : "l"(da), "l"(db), "r"(scale_d));
}

constexpr float SM_C = 0.22360679774997896f * 1.4426950408889634f;
constexpr float NEG_INF = -INFINITY;

DEVINL void qk_block(float (&s0)[4], float (&s1)[4], const uint32_t (&a)[4], const uint32_t (&a8)[2],
                     uint32_t kaddr, uint32_t t0, uint32_t t1) {
  uint32_t b0, b1, b2, b3;
  ldsm4(b0, b1, b2, b3, kaddr);
  mma16816_z(s0, a[0], a[1], a[2], a[3], b0, b1);
  mma16816_z(s1, a[0], a[1], a[2], a[3], b2, b3);
  mma1688(s0, a8[0], a8[1], t0);
  mma1688(s1, a8[0], a8[1], t1);
}
DEVINL void pv_block(float (&o)[3][4], uint32_t p0, uint32_t p1, uint32_t p2, uint32_t p3, uint32_t vaddr,
                     uint32_t t0, uint32_t t1) {
  uint32_t b0, b1, b2, b3;
  ldsm4t(b0, b1, b2, b3, vaddr);
  mma16816(o[0], p0, p1, p2, p3, b0, b1);
  mma16816(o[1], p0, p1, p2, p3, b2, b3);
  mma16816(o[2], p0, p1, p2, p3, t0, t1);
}

template <bool FULL>
DEVINL void attn_all(uint32_t ring, uint32_t stg, uint32_t bars, int wq, int lane, int jmin) {
  const int g = lane >> 2, t = lane & 3, mi = lane >> 3, r = lane & 7;
  const uint32_t tri = ((2 * t > g) ? 0xFFFFu : 0u) | ((2 * t + 1 > g) ? 0xFFFF0000u : 0u);
  const uint32_t rowK = (16 * wq + r + 8 * (mi >> 1)) * 80 + (mi & 1) * 16;
  const uint32_t rowV = (16 * wq + r + 8 * (mi & 1)) * 80 + (mi >> 1) * 16;
  const uint32_t rowT = (16 * wq + r + 8 * mi) * 80;
  const uint32_t rowQ = stg + (16 * wq + r + 8 * (mi & 1)) * 160 + (mi >> 1) * 16;
#pragma unroll 1
  for (int h = 0; h < 4; ++h) {
    const int p = h >> 1, odd = h & 1;
    if (!odd) mbar_wait(bars + 8 * (B_HALO + p), 0);
    const uint32_t kw = ring + (2 * p) * KVWIN, vw = kw + KVWIN;
    const uint32_t kA = kw + rowK + odd * 48, kT = kw + rowT + 32;
    const uint32_t vA = vw + rowV + odd * 32, vT = vw + rowT + 32 + odd * 32;
    uint32_t a[4], a8[2];
    ldsm4(a[0], a[1], a[2], a[3], rowQ + p * 80 + odd * 48);
    ldsm2(a8[0], a8[1], stg + (16 * wq + (lane & 15)) * 160 + p * 80 + 32);
    if ((t >= 2) != (odd != 0)) { a8[0] = 0u; a8[1] = 0u; }
    float o[3][4];
#pragma unroll
    for (int n = 0; n < 3; ++n) { o[n][0] = 0.f; o[n][1] = 0.f; o[n][2] = 0.f; o[n][3] = 0.f; }
    float m0 = NEG_INF, m1 = NEG_INF, l0 = 0.f, l1 = 0.f;
#pragma unroll 1
    for (int c = 0; c < 2; ++c) {
      if (!FULL && c == 1 && jmin > 8) break;
      const int jb = c == 0 ? 9 : 1;
      const uint32_t jo = jb * 1280;
      float s[16][4];
      uint32_t t0, t1, t2, t3;
#pragma unroll
      for (int jj = 0; jj < 4; ++jj) {
        ldsm4(t0, t1, t2, t3, kT + jo + 2560 * jj);
        qk_block(s[4 * jj], s[4 * jj + 1], a, a8, kA + jo + 2560 * jj, t0, t1);
        qk_block(s[4 * jj + 2], s[4 * jj + 3], a, a8, kA + jo + 2560 * jj + 1280, t2, t3);
      }
      if (c == 0) {
        float z0[4], z1[4];
        ldsm2(t0, t1, kT);
        qk_block(z0, z1, a, a8, kA, t0, t1);
        if (!FULL && jmin > 0) {
#pragma unroll
          for (int e = 0; e < 4; ++e) { z0[e] = NEG_INF; z1[e] = NEG_INF; }
        }
        const bool c0 = tri & 1, c1 = tri >> 16;
        s[14][0] = c0 ? z0[0] : s[14][0];
        s[14][1] = c1 ? z0[1] : s[14][1];
        s[15][0] = z1[0];
        s[15][1] = z1[1];
        s[15][2] = c0 ? z1[2] : s[15][2];
        s[15][3] = c1 ? z1[3] : s[15][3];
      }
      if (!FULL) {
#pragma unroll
        for (int i = 0; i < 8; ++i) {
          if (jb + i < jmin) {
#pragma unroll
            for (int e = 0; e < 4; ++e) { s[2 * i][e] = NEG_INF; s[2 * i + 1][e] = NEG_INF; }
          }
        }
      }
      float x0 = fmaxf(s[0][0], s[0][1]);
      float x1 = fmaxf(s[0][2], s[0][3]);
#pragma unroll
      for (int i = 1; i < 16; ++i) {
        x0 = fmaxf(x0, fmaxf(s[i][0], s[i][1]));
        x1 = fmaxf(x1, fmaxf(s[i][2], s[i][3]));
      }
      x0 = fmaxf(x0, __shfl_xor_sync(0xffffffffu, x0, 1));
      x1 = fmaxf(x1, __shfl_xor_sync(0xffffffffu, x1, 1));
      x0 = fmaxf(x0, __shfl_xor_sync(0xffffffffu, x0, 2));
      x1 = fmaxf(x1, __shfl_xor_sync(0xffffffffu, x1, 2));
      x0 = fmaxf(x0, m0);
      x1 = fmaxf(x1, m1);
      const float al0 = ex2((m0 - x0) * SM_C), al1 = ex2((m1 - x1) * SM_C);
      m0 = x0; m1 = x1;
      const float n0 = -x0 * SM_C, n1 = -x1 * SM_C;
      l0 *= al0; l1 *= al1;
      uint32_t pp[16][2];
#pragma unroll
      for (int i = 0; i < 16; ++i) {
        const float e0 = ex2(fmaf(s[i][0], SM_C, n0)), e1 = ex2(fmaf(s[i][1], SM_C, n0));
        const float e2 = ex2(fmaf(s[i][2], SM_C, n1)), e3 = ex2(fmaf(s[i][3], SM_C, n1));
        l0 += e0 + e1; l1 += e2 + e3;
        pp[i][0] = pack_bf16(e0, e1);
        pp[i][1] = pack_bf16(e2, e3);
      }
#pragma unroll
      for (int n = 0; n < 3; ++n) { o[n][0] *= al0; o[n][1] *= al0; o[n][2] *= al1; o[n][3] *= al1; }
      if (c == 0) {
        ldsm2t(t0, t1, vT);
        pv_block(o, pp[14][0] & tri, 0u, pp[15][0], pp[15][1] & tri, vA, t0, t1);
        pp[14][0] &= ~tri; pp[15][0] = 0u; pp[15][1] &= ~tri;
      }
#pragma unroll
      for (int jj = 0; jj < 4; ++jj) {
        ldsm4t(t0, t1, t2, t3, vT + jo + 2560 * jj);
        pv_block(o, pp[4 * jj][0], pp[4 * jj][1], pp[4 * jj + 1][0], pp[4 * jj + 1][1], vA + jo + 2560 * jj, t0, t1);
        pv_block(o, pp[4 * jj + 2][0], pp[4 * jj + 2][1], pp[4 * jj + 3][0], pp[4 * jj + 3][1], vA + jo + 2560 * jj + 1280, t2, t3);
      }
    }
    l0 += __shfl_xor_sync(0xffffffffu, l0, 1);
    l1 += __shfl_xor_sync(0xffffffffu, l1, 1);
    l0 += __shfl_xor_sync(0xffffffffu, l0, 2);
    l1 += __shfl_xor_sync(0xffffffffu, l1, 2);
    const float i0 = __frcp_rn(l0), i1 = __frcp_rn(l1);
    const uint32_t ob = stg + (16 * wq + g) * 160 + p * 80 + odd * 32 + t * 4;
    __syncwarp();
    const bool w0 = !odd || t >= 2, w2 = odd || t < 2;
    if (w0) { sts32(ob, pack_bf16(o[0][0] * i0, o[0][1] * i0)); sts32(ob + 1280, pack_bf16(o[0][2] * i1, o[0][3] * i1)); }
    sts32(ob + 16, pack_bf16(o[1][0] * i0, o[1][1] * i0)); sts32(ob + 16 + 1280, pack_bf16(o[1][2] * i1, o[1][3] * i1));
    if (w2) { sts32(ob + 32, pack_bf16(o[2][0] * i0, o[2][1] * i0)); sts32(ob + 32 + 1280, pack_bf16(o[2][2] * i1, o[2][3] * i1)); }
    __syncwarp();
  }
}

struct Params {
  const uint16_t* q; const uint16_t* k; const uint16_t* v; const uint16_t* shift_k; const uint16_t* ssm_k;
  const uint16_t* ssm_D; uint16_t* out;
};

DEVINL unsigned* cnt(int i) { return &g_cnt[i * CS]; }

DEVINL void finish_role() {
  unsigned old = atomicAdd(cnt(C_DONE), 1u);
  if (old == 255u) {
    __threadfence();
    for (int i = 0; i < C_NUM; ++i) *cnt(i) = 0u;
    __threadfence();
  }
}

__global__ void __cluster_dims__(2, 1, 1) __launch_bounds__(512, 1)
h3_swa_fused_kernel(const __grid_constant__ CUtensorMap tmX, const __grid_constant__ CUtensorMap tmW128,
                    const __grid_constant__ CUtensorMap tmW32, const __grid_constant__ CUtensorMap tmO,
                    const __grid_constant__ CUtensorMap tmWo, const __grid_constant__ CUtensorMap tmOst,
                    const __grid_constant__ CUtensorMap tmOut, const Params prm) {
  extern __shared__ uint8_t smem_raw[];
  const uint32_t sb = ((uint32_t)__cvta_generic_to_shared(smem_raw) + 1023u) & ~1023u;
  const uint32_t bars = sb + OFF_BAR;
  const int tid = threadIdx.x, warp = tid >> 5, lane = tid & 31, wg = tid >> 7;
  const int cta = blockIdx.x;
  const uint32_t rank = cta & 1;
  const int g8 = (cta >> 1) & 7, rp = cta >> 4;
  const int rb = 2 * rp + rank;
  const int rb2 = 2 * rp + (g8 & 1);
  const int c2 = 2 * (g8 >> 1) + rank;

  if (tid == 0) {
    PROF(0);
    for (int i = 0; i < NST1; ++i) { mbar_init(bars + 8 * (B_FULL1 + i), 1); mbar_init(bars + 8 * (B_EMPTY1 + i), 16); }
    mbar_init(bars + 8 * B_RINGFREE, 1);
    mbar_init(bars + 8 * B_HALO, 1); mbar_init(bars + 8 * (B_HALO + 1), 1);
    for (int i = 0; i < NST2; ++i) { mbar_init(bars + 8 * (B_FULL2 + i), 1); mbar_init(bars + 8 * (B_EMPTY2 + i), 16); }
    mbar_init(bars + 8 * B_U, 1);
    asm volatile("fence.mbarrier_init.release.cluster;" ::: "memory");
  }
  __syncthreads();
  asm volatile("barrier.cluster.arrive.release;\nbarrier.cluster.wait.acquire;" ::: "memory");

  if (wg == 3) {
    asm volatile("setmaxnreg.dec.sync.aligned.u32 40;");
    if (warp == 12 && lane == 0) {
      for (int it = 0; it < 10; ++it) {
        const int s = it % NST1;
        if (it >= NST1) mbar_wait(bars + 8 * (B_EMPTY1 + s), ((it / NST1) - 1) & 1);
        const uint32_t st = sb + s * ST1, fb = bars + 8 * (B_FULL1 + s);
        mbar_expect(fb, ST1);
        tma2d(st, &tmX, it * 64, rb * 128, fb);
        tma3d_mc(st + ST1_B128 + rank * 12288, &tmW128, g8 * 80, it * 64 + rank * 32, 0, fb);
        tma3d_mc(st + ST1_B32 + rank * 3072, &tmW32, g8 * 80 + 64, it * 64 + rank * 32, 0, fb);
      }
      PROF(1);
      mbar_wait(bars + 8 * B_RINGFREE, 0);
      const int nh = rb >= 2 ? 256 : rb * 128;
      if (rb >= 1) poll_ge(cnt(C_KV + g8 * 16 + rb - 1), 32);
      if (rb >= 2) poll_ge(cnt(C_KV + g8 * 16 + rb - 2), 32);
      fence_async();
      PROF(2);
      for (int p = 0; p < 2; ++p) {
        const uint32_t hb = bars + 8 * (B_HALO + p);
        if (nh == 0) { mbar_arrive(hb); continue; }
        mbar_expect(hb, 2 * nh * 80);
        for (int kv = 0; kv < 2; ++kv)
          bulk_load(sb + (2 * p + kv) * KVWIN + (256 - nh) * 80,
                    g_kv + ((size_t)((g8 * 2 + p) * 2 + kv) * SEQ + (rb * 128 - nh)) * 40, nh * 80, hb);
      }
      for (int s = 0; s < NST2; ++s) {
        mbar_wait(bars + 8 * (B_EMPTY2 + s), 0);
        const uint32_t fb = bars + 8 * (B_FULL2 + s);
        mbar_expect(fb, ST2);
        tma3d(sb + s * ST2 + 16384, &tmWo, 0, s * 64, c2 * 5, fb);
      }
      PROF(3);
      poll_ge(cnt(C_O + rb2), 64);
      fence_async();
      PROF(4);
      for (int s = 0; s < NST2; ++s)
        tma2d_mc(sb + s * ST2 + rank * 8192, &tmO, s * 64, rb2 * 128 + rank * 64, bars + 8 * (B_FULL2 + s));
      for (int it = NST2; it < 10; ++it) {
        const int s = it - NST2;
        mbar_wait(bars + 8 * (B_EMPTY2 + s), 1);
        const uint32_t fb = bars + 8 * (B_FULL2 + s);
        mbar_expect(fb, ST2);
        tma3d(sb + s * ST2 + 16384, &tmWo, 0, it * 64, c2 * 5, fb);
        tma2d_mc(sb + s * ST2 + rank * 8192, &tmO, it * 64, rb2 * 128 + rank * 64, fb);
      }
      finish_role();
    }
  } else if (wg == 2) {
    asm volatile("setmaxnreg.inc.sync.aligned.u32 136;");
    const int ct = tid - 256, wc = warp - 8;
    const int tau = cta & 15, jt = cta >> 4;
    const int t0 = tau * 128, c0 = jt * 80;
    const int mi = lane >> 3, r = lane & 7, g = lane >> 2, t = lane & 3;
    const uint32_t U = sb + OFF_U, F = sb + OFF_F;
    for (int item = ct; item < 160; item += 128) {
      const int c = item % 10, seg = item / 10;
      const int ts = t0 + seg * 8, ch = c0 + c * 8;
      uint4 kk[11], vv[8], wv[4];
#pragma unroll
      for (int i = 0; i < 11; ++i) {
        const int row = ts - 3 + i;
        kk[i] = row >= 0 ? ldg_nc(prm.k + (size_t)row * DM + ch) : make_uint4(0, 0, 0, 0);
      }
#pragma unroll
      for (int i = 0; i < 8; ++i) vv[i] = ldg_nc(prm.v + (size_t)(ts + i) * DM + ch);
#pragma unroll
      for (int u = 0; u < 4; ++u) wv[u] = ldg_nc(prm.shift_k + (size_t)(ch + 2 * u) * 4);
      uint32_t W[4][4];
#pragma unroll
      for (int u = 0; u < 4; ++u) {
        W[0][u] = __byte_perm(wv[u].x, wv[u].z, 0x5410);
        W[1][u] = __byte_perm(wv[u].x, wv[u].z, 0x7632);
        W[2][u] = __byte_perm(wv[u].y, wv[u].w, 0x5410);
        W[3][u] = __byte_perm(wv[u].y, wv[u].w, 0x7632);
      }
#pragma unroll
      for (int i = 0; i < 8; ++i) {
        uint32_t res[4];
#pragma unroll
        for (int u = 0; u < 4; ++u) {
          const uint32_t k0 = (&kk[i].x)[u], k1 = (&kk[i + 1].x)[u], k2 = (&kk[i + 2].x)[u], k3 = (&kk[i + 3].x)[u];
          uint32_t acc = hadd2(hmul2(k0, W[3][u]), hmul2(k1, W[2][u]));
          acc = hadd2(acc, hmul2(k2, W[1][u]));
          acc = hadd2(acc, hmul2(k3, W[0][u]));
          res[u] = hmul2(acc, (&vv[i].x)[u]);
        }
        sts128(U + (seg * 8 + i) * 160 + c * 16, make_uint4(res[0], res[1], res[2], res[3]));
      }
    }
    named_sync(3, 128);
    for (int it = wc; it < 40; it += 4) {
      const int c = it % 10, rest = it / 10, h = rest & 1, iq = rest >> 1;
      const int tl = 16 * (4 * iq + (r >> 1)) + 15 - (8 * h + 2 * mi + (r & 1));
      uint4 v4;
      ldsm4t(v4.x, v4.y, v4.z, v4.w, U + tl * 160 + c * 16);
      stg128(g_kvT + (size_t)(c0 + c * 8 + g) * 2176 + h * 1088 + (8 + 8 * tau + 4 * iq + t) * 8, v4);
    }
    if (tau == 0) {
      for (int i = ct; i < 80 * 16; i += 128)
        stg128(g_kvT + (size_t)(c0 + (i >> 4)) * 2176 + ((i >> 3) & 1) * 1088 + (i & 7) * 8, make_uint4(0, 0, 0, 0));
    }
    __threadfence();
    named_sync(3, 128);
    if (ct == 0) { red_release(cnt(C_PRE + jt)); PROF(8); }
    {
      const int chb = cta * 5;
      uint4 fv[10]; uint32_t pv[10];
#pragma unroll
      for (int i = 0; i < 10; ++i) {
        const int cl = i >> 1, qq = ct + (i & 1) * 128;
        const uint16_t* src = prm.ssm_k + (size_t)(chb + cl) * SEQ + qq * 8;
        fv[i] = ldg_nc(src);
        pv[i] = qq > 0 ? (uint32_t)__ldg(src - 1) : 0u;
      }
#pragma unroll
      for (int i = 0; i < 10; ++i) {
        const int cl = i >> 1, qq = ct + (i & 1) * 128;
        const uint32_t a = F + cl * CH_F + 32 + qq * 16;
        sts128(a, fv[i]);
        sts128(a + 4160, make_uint4(__byte_perm(pv[i], fv[i].x, 0x5410), __byte_perm(fv[i].x, fv[i].y, 0x5432),
                                    __byte_perm(fv[i].y, fv[i].z, 0x5432), __byte_perm(fv[i].z, fv[i].w, 0x5432)));
      }
      if (ct < 20) sts128(F + (ct >> 2) * CH_F + ((ct >> 1) & 1) * 4160 + (ct & 1) * 16, make_uint4(0, 0, 0, 0));
    }
    if (ct == 0) {
      poll_ge(cnt(C_PRE + jt), 16);
      fence_async();
      mbar_expect(bars + 8 * B_U, 5 * CH_U);
      bulk_load(U, g_kvT + (size_t)cta * 5 * 2176, 5 * CH_U, bars + 8 * B_U);
      PROF(9);
    }
    named_sync(3, 128);
    mbar_wait(bars + 8 * B_U, 0);
    if (ct == 0) PROF(10);
#pragma unroll 1
    for (int pass = 0; pass < 2; ++pass) {
      const int cl = pass == 0 ? wc : 4;
      const int r0 = pass == 0 ? 0 : 2 * wc, r1 = pass == 0 ? 8 : 2 * wc + 2;
      const uint32_t Ub = U + cl * CH_U, Fb = F + cl * CH_F;
      const uint32_t laneU = Ub + (mi & 1) * 2176 + (8 + 8 * (mi >> 1) + r) * 16;
      const uint32_t laneF = (g & 1) ? Fb + 4160 + 2 * (17 - g + 2 * t) : Fb + 2 * (16 - g + 2 * t);
      float acc[16][4];
#pragma unroll
      for (int i = 0; i < 16; ++i) { acc[i][0] = 0.f; acc[i][1] = 0.f; acc[i][2] = 0.f; acc[i][3] = 0.f; }
#pragma unroll 1
      for (int rho = r0; rho < r1; ++rho) {
        uint32_t uf[16][2];
#pragma unroll
        for (int jj = 0; jj < 8; ++jj)
          ldsm4(uf[2 * jj][0], uf[2 * jj][1], uf[2 * jj + 1][0], uf[2 * jj + 1][1], laneU + jj * 256 - rho * 16);
        const uint32_t fb = laneF + 32 * rho;
#pragma unroll
        for (int mu = 0; mu < 16; ++mu) {
          const uint32_t a0 = lds32(fb + 256 * mu), a1 = lds32(fb + 256 * mu - 16), a2 = lds32(fb + 256 * mu + 16);
#pragma unroll
          for (int i = mu; i < 16; ++i) mma16816(acc[i], a0, a1, a2, a0, uf[i - mu][0], uf[i - mu][1]);
        }
      }
      const uint32_t dv = (uint32_t)__ldg(prm.ssm_D + cta * 5 + cl);
      const uint32_t D2 = dv | (dv << 16);
      if (pass == 0) {
        uint32_t res[8][4];
#pragma unroll
        for (int jj = 0; jj < 8; ++jj) {
          uint32_t u0, u1, u2, u3;
          ldsm4t(u0, u1, u2, u3, laneU + jj * 256);
          res[jj][0] = hadd2(pack_bf16(acc[2 * jj][0], acc[2 * jj][1]), hmul2(u0, D2));
          res[jj][1] = hadd2(pack_bf16(acc[2 * jj][2], acc[2 * jj][3]), hmul2(u1, D2));
          res[jj][2] = hadd2(pack_bf16(acc[2 * jj + 1][0], acc[2 * jj + 1][1]), hmul2(u2, D2));
          res[jj][3] = hadd2(pack_bf16(acc[2 * jj + 1][2], acc[2 * jj + 1][3]), hmul2(u3, D2));
        }
        __syncwarp();
#pragma unroll
        for (int jj = 0; jj < 8; ++jj)
          stsm4t(Ub + ((8 * (2 * jj + (mi >> 1)) + r) * 16 + 8 * (mi & 1)) * 2, res[jj][0], res[jj][1], res[jj][2], res[jj][3]);
        fence_async_smem();
        __syncwarp();
        if (lane == 0) {
          bulk_store(g_yT + (size_t)(cta * 5 + cl) * SEQ, Ub, 4096);
          bulk_commit();
          bulk_wait0();
          red_release(cnt(C_Y + jt));
        }
        __syncwarp();
      } else {
        const uint32_t rbuf = F + wc * CH_F + lane * 16;
#pragma unroll
        for (int i = 0; i < 16; ++i)
          sts128(rbuf + i * 512, make_uint4(__float_as_uint(acc[i][0]), __float_as_uint(acc[i][1]),
                                            __float_as_uint(acc[i][2]), __float_as_uint(acc[i][3])));
        named_sync(3, 128);
        uint32_t res[2][4];
#pragma unroll
        for (int jj = 0; jj < 2; ++jj) {
          float sum[2][4];
#pragma unroll
          for (int hh = 0; hh < 2; ++hh) {
            const int tile = 4 * wc + 2 * jj + hh;
            sum[hh][0] = 0.f; sum[hh][1] = 0.f; sum[hh][2] = 0.f; sum[hh][3] = 0.f;
#pragma unroll
            for (int w = 0; w < 4; ++w) {
              const uint4 x = lds128(F + w * CH_F + lane * 16 + tile * 512);
              sum[hh][0] += __uint_as_float(x.x); sum[hh][1] += __uint_as_float(x.y);
              sum[hh][2] += __uint_as_float(x.z); sum[hh][3] += __uint_as_float(x.w);
            }
          }
          uint32_t u0, u1, u2, u3;
          ldsm4t(u0, u1, u2, u3, laneU + (2 * wc + jj) * 256);
          res[jj][0] = hadd2(pack_bf16(sum[0][0], sum[0][1]), hmul2(u0, D2));
          res[jj][1] = hadd2(pack_bf16(sum[0][2], sum[0][3]), hmul2(u1, D2));
          res[jj][2] = hadd2(pack_bf16(sum[1][0], sum[1][1]), hmul2(u2, D2));
          res[jj][3] = hadd2(pack_bf16(sum[1][2], sum[1][3]), hmul2(u3, D2));
        }
#pragma unroll
        for (int jj = 0; jj < 2; ++jj)
          stsm4t(U + ((8 * (2 * (2 * wc + jj) + (mi >> 1)) + r) * 16 + 8 * (mi & 1)) * 2, res[jj][0], res[jj][1], res[jj][2], res[jj][3]);
        fence_async_smem();
        named_sync(3, 128);
        if (ct == 0) {
          bulk_store(g_yT + (size_t)(cta * 5 + 4) * SEQ, U, 4096);
          bulk_commit();
          bulk_wait0();
          red_release(cnt(C_Y + jt));
          PROF(11);
        }
      }
    }
    uint4 qv[10];
#pragma unroll
    for (int i = 0; i < 10; ++i) {
      const int idx = ct + 128 * i, row = idx / 10, c = idx % 10;
      qv[i] = ldg_nc(prm.q + (size_t)(t0 + row) * DM + c0 + c * 8);
    }
    if (ct == 0) { poll_ge(cnt(C_Y + jt), 80); finish_role(); PROF(12); }
    named_sync(3, 128);
    const uint32_t YT = sb + OFF_U, YN = sb + OFF_F + 1024;
#pragma unroll
    for (int i = 0; i < 10; ++i) {
      const int idx = ct + 128 * i, ch = idx >> 4, cq = idx & 15;
      sts128(YT + ch * 272 + cq * 16, ldg_cg(g_yT + (size_t)(c0 + ch) * SEQ + t0 + cq * 8));
    }
    named_sync(3, 128);
    for (int it = wc; it < 40; it += 4) {
      const int c = it % 10, tq = it / 10;
      uint32_t x0, x1, x2, x3;
      ldsm4t(x0, x1, x2, x3, YT + (8 * c + r) * 272 + (4 * tq + mi) * 16);
      const int s = (8 * (4 * tq + mi) + r) ^ 15;
      stsm4(YN + s * 176 + c * 16, x0, x1, x2, x3);
    }
    named_sync(3, 128);
#pragma unroll
    for (int i = 0; i < 10; ++i) {
      const int idx = ct + 128 * i, row = idx / 10, c = idx % 10;
      const uint4 y = lds128(YN + row * 176 + c * 16);
      stg128(prm.out + (size_t)(t0 + row) * (2 * DM) + c0 + c * 8,
             make_uint4(hmul2(qv[i].x, y.x), hmul2(qv[i].y, y.y), hmul2(qv[i].z, y.z), hmul2(qv[i].w, y.w)));
    }
    if (ct == 0) PROF(13);
  } else {
    asm volatile("setmaxnreg.inc.sync.aligned.u32 168;");
    const int wq = warp;
    const int mi = lane >> 3, r = lane & 7;
    {
      float acc1[96], acc2[24];
#pragma unroll 1
      for (int it = 0; it < 10; ++it) {
        const int s = it % NST1;
        mbar_wait(bars + 8 * (B_FULL1 + s), (it / NST1) & 1);
        if (it == 0 && tid == 0) PROF(16);
        const uint32_t st = sb + s * ST1;
        wg_fence();
#pragma unroll
        for (int kk = 0; kk < 4; ++kk) {
          const uint64_t da = make_desc(st + wg * 8192 + kk * 32, 16, 1024, 1);
          const uint64_t db1 = make_desc(st + ST1_B128 + (kk >> 1) * 12288 + (kk & 1) * 2048, 4096, 1024, 1);
          const uint64_t db2 = make_desc(st + ST1_B32 + (kk >> 1) * 3072 + (kk & 1) * 512, 1024, 256, 3);
          wgmma_n192(acc1, da, db1, (it | kk) != 0);
          wgmma_n48(acc2, da, db2, (it | kk) != 0);
        }
        wg_commit();
        if (it > 0) {
          wg_wait<1>();
          if (it - 1 + NST1 < 10 && lane < 2) mbar_arrive_cta(bars + 8 * (B_EMPTY1 + (it - 1) % NST1), lane);
        }
      }
      wg_wait<0>();
      if (tid == 0) PROF(17);
      named_sync(1, 256);
      if (tid == 0) mbar_arrive(bars + 8 * B_RINGFREE);
      {
        const uint32_t rq = sb + OFF_STG + (16 * wq + 8 * (mi & 1) + r) * 160 + (mi >> 1) * 16;
#pragma unroll
        for (int tp = 0; tp < 4; ++tp)
          stsm4(rq + tp * 32, pack_bf16(acc1[8 * tp], acc1[8 * tp + 1]), pack_bf16(acc1[8 * tp + 2], acc1[8 * tp + 3]),
                pack_bf16(acc1[8 * tp + 4], acc1[8 * tp + 5]), pack_bf16(acc1[8 * tp + 6], acc1[8 * tp + 7]));
        stsm4(rq + 128, pack_bf16(acc2[0], acc2[1]), pack_bf16(acc2[2], acc2[3]), pack_bf16(acc2[4], acc2[5]), pack_bf16(acc2[6], acc2[7]));
      }
      const uint32_t rowa = sb + (256 + 16 * wq + 8 * (mi & 1) + r) * 80;
#pragma unroll
      for (int kv = 0; kv < 2; ++kv) {
#pragma unroll
        for (int tp = 0; tp < 5; ++tp) {
          uint32_t w[4];
#pragma unroll
          for (int hh = 0; hh < 2; ++hh) {
            const int tile = 2 * tp + hh;
            if (tile < 8) {
              const int o = 32 * (kv + 1) + 4 * tile;
              w[2 * hh] = pack_bf16(acc1[o], acc1[o + 1]); w[2 * hh + 1] = pack_bf16(acc1[o + 2], acc1[o + 3]);
            } else {
              const int o = 8 * (kv + 1) + 4 * (tile - 8);
              w[2 * hh] = pack_bf16(acc2[o], acc2[o + 1]); w[2 * hh + 1] = pack_bf16(acc2[o + 2], acc2[o + 3]);
            }
          }
          const int tA = 2 * tp, tB = 2 * tp + 1;
          const uint32_t offA = ((tA / 5) * 2 + kv) * KVWIN + (tA % 5) * 16;
          const uint32_t offB = ((tB / 5) * 2 + kv) * KVWIN + (tB % 5) * 16;
          stsm4(rowa + ((mi >> 1) ? offB : offA), w[0], w[1], w[2], w[3]);
        }
      }
    }
    if (rb < 2) {
      const int nz = (2 - rb) * 128 * 5;
#pragma unroll 1
      for (int i = tid; i < 4 * nz; i += 256) {
        const int w = i / nz;
        sts128(sb + w * KVWIN + (i - w * nz) * 16, make_uint4(0, 0, 0, 0));
      }
    }
    fence_async_smem();
    __syncwarp();
    if (lane < 4) {
      const int p = lane >> 1, kv = lane & 1;
      bulk_store(g_kv + ((size_t)((g8 * 2 + p) * 2 + kv) * SEQ + rb * 128 + 16 * wq) * 40,
                 sb + (2 * p + kv) * KVWIN + (256 + 16 * wq) * 80, 1280);
      bulk_commit();
      bulk_wait0();
      red_release(cnt(C_KV + g8 * 16 + rb));
    }
    named_sync(2, 256);
    if (tid == 0) PROF(18);
    const uint32_t stg = sb + OFF_STG;
    if (rb >= 2) attn_all<true>(sb, stg, bars, wq, lane, 0);
    else attn_all<false>(sb, stg, bars, wq, lane, max(0, 16 - 8 * rb - wq));
    if (tid == 0) PROF(19);
    fence_async_smem();
    __syncwarp();
    if (lane < 2 * NST2) mbar_arrive_cta(bars + 8 * (B_EMPTY2 + (lane >> 1)), lane & 1);
    if (lane == 0) {
      tma2d_store(&tmOst, g8 * 80, rb * 128 + 16 * wq, stg + wq * 2560);
      bulk_commit();
      bulk_wait0();
      red_release(cnt(C_O + rb));
    }
    __syncwarp();
    if (tid == 0) PROF(20);
    float acc[40];
#pragma unroll 1
    for (int it = 0; it < 10; ++it) {
      const int s = it % NST2;
      mbar_wait(bars + 8 * (B_FULL2 + s), (it / NST2) & 1);
      if (it == 0 && tid == 0) PROF(21);
      const uint32_t st = sb + s * ST2;
      wg_fence();
#pragma unroll
      for (int kk = 0; kk < 4; ++kk)
        wgmma_n80(acc, make_desc(st + wg * 8192 + kk * 32, 16, 1024, 1), make_desc(st + 16384 + kk * 512, 2048, 256, 3), (it | kk) != 0);
      wg_commit();
      if (it > 0) {
        wg_wait<1>();
        if (it - 1 + NST2 < 10 && lane < 2) mbar_arrive_cta(bars + 8 * (B_EMPTY2 + (it - 1) % NST2), lane);
      }
    }
    wg_wait<0>();
    if (tid == 0) PROF(22);
    {
      const uint32_t rowa = stg + (16 * wq + 8 * (mi & 1) + r) * 160 + (mi >> 1) * 16;
#pragma unroll
      for (int tp = 0; tp < 5; ++tp)
        stsm4(rowa + tp * 32, pack_bf16(acc[8 * tp], acc[8 * tp + 1]), pack_bf16(acc[8 * tp + 2], acc[8 * tp + 3]),
              pack_bf16(acc[8 * tp + 4], acc[8 * tp + 5]), pack_bf16(acc[8 * tp + 6], acc[8 * tp + 7]));
      fence_async_smem();
      __syncwarp();
      if (lane == 0) {
        tma2d_store(&tmOut, DM + c2 * 80, rb2 * 128 + 16 * wq, stg + wq * 2560);
        bulk_commit();
        bulk_wait0_read();
      }
    }
    if (tid == 0) PROF(23);
  }
}

typedef CUresult (*EncodeFn)(CUtensorMap*, CUtensorMapDataType, cuuint32_t, void*, const cuuint64_t*, const cuuint64_t*,
                             const cuuint32_t*, const cuuint32_t*, CUtensorMapInterleave, CUtensorMapSwizzle,
                             CUtensorMapL2promotion, CUtensorMapFloatOOBfill);

CUtensorMap make_map(EncodeFn enc, const void* p, int rank, const cuuint64_t* dims, const cuuint64_t* strides,
                     const cuuint32_t* box, CUtensorMapSwizzle sw) {
  CUtensorMap m;
  const cuuint32_t es[3] = {1, 1, 1};
  enc(&m, CU_TENSOR_MAP_DATA_TYPE_BFLOAT16, rank, const_cast<void*>(p), dims, strides, box, es,
      CU_TENSOR_MAP_INTERLEAVE_NONE, sw, CU_TENSOR_MAP_L2_PROMOTION_L2_128B, CU_TENSOR_MAP_FLOAT_OOB_FILL_NONE);
  return m;
}

}

extern "C" void kernel_launch(void* const* d_in, const int* in_sizes, int n_in, void* d_out, int out_size) {
  (void)in_sizes; (void)n_in; (void)out_size;
  static EncodeFn enc = nullptr;
  static void* o_ptr = nullptr;
  if (!enc) {
    void* fn = nullptr;
    cudaDriverEntryPointQueryResult qr;
    cudaGetDriverEntryPoint("cuTensorMapEncodeTiled", &fn, cudaEnableDefault, &qr);
    enc = (EncodeFn)fn;
    cudaGetSymbolAddress(&o_ptr, g_o);
    cudaFuncSetAttribute(h3_swa_fused_kernel, cudaFuncAttributeMaxDynamicSharedMemorySize, SMEM_BYTES);
  }
  const void* x = d_in[6];
  const void* wqkv = d_in[7];
  const void* wo = d_in[8];
  CUtensorMap tmX, tmW128, tmW32, tmO, tmWo, tmOst, tmOut;
  { cuuint64_t d[2] = {640, 2048}, s[1] = {1280}; cuuint32_t b[2] = {64, 128};
    tmX = make_map(enc, x, 2, d, s, b, CU_TENSOR_MAP_SWIZZLE_128B); }
  { cuuint64_t d[3] = {640, 640, 3}, s[2] = {3840, 1280}; cuuint32_t b[3] = {64, 32, 3};
    tmW128 = make_map(enc, wqkv, 3, d, s, b, CU_TENSOR_MAP_SWIZZLE_128B); }
  { cuuint64_t d[3] = {640, 640, 3}, s[2] = {3840, 1280}; cuuint32_t b[3] = {16, 32, 3};
    tmW32 = make_map(enc, wqkv, 3, d, s, b, CU_TENSOR_MAP_SWIZZLE_32B); }
  { cuuint64_t d[2] = {640, 2048}, s[1] = {1280}; cuuint32_t b[2] = {64, 64};
    tmO = make_map(enc, o_ptr, 2, d, s, b, CU_TENSOR_MAP_SWIZZLE_128B); }
  { cuuint64_t d[3] = {16, 640, 40}, s[2] = {1280, 32}; cuuint32_t b[3] = {16, 64, 5};
    tmWo = make_map(enc, wo, 3, d, s, b, CU_TENSOR_MAP_SWIZZLE_32B); }
  { cuuint64_t d[2] = {640, 2048}, s[1] = {1280}; cuuint32_t b[2] = {80, 16};
    tmOst = make_map(enc, o_ptr, 2, d, s, b, CU_TENSOR_MAP_SWIZZLE_NONE); }
  { cuuint64_t d[2] = {1280, 2048}, s[1] = {2560}; cuuint32_t b[2] = {80, 16};
    tmOut = make_map(enc, d_out, 2, d, s, b, CU_TENSOR_MAP_SWIZZLE_NONE); }
  Params prm;
  prm.q = (const uint16_t*)d_in[0]; prm.k = (const uint16_t*)d_in[1]; prm.v = (const uint16_t*)d_in[2];
  prm.shift_k = (const uint16_t*)d_in[3]; prm.ssm_k = (const uint16_t*)d_in[4]; prm.ssm_D = (const uint16_t*)d_in[5];
  prm.out = (uint16_t*)d_out;
  h3_swa_fused_kernel<<<128, 512, SMEM_BYTES>>>(tmX, tmW128, tmW32, tmO, tmWo, tmOst, tmOut, prm);
}
```

```cpp
#include <cuda_runtime.h>
#include <cuda.h>
#include <cuda_bf16.h>
#include <stdint.h>

#define DEVINL __device__ __forceinline__

namespace {

constexpr int SEQ = 2048;
constexpr int DM = 640;

constexpr int ST1 = 47104;
constexpr int ST1_B128 = 16384;
constexpr int ST1_B32 = 40960;
constexpr int NST1 = 3;
constexpr int KVWIN = 30720;
constexpr int ST2 = 26624;
constexpr int NST2 = 5;
constexpr int OFF_CONV = NST1 * ST1;
constexpr int CH_U = 4352;
constexpr int CH_F = 8320;
constexpr int OFF_U = OFF_CONV;
constexpr int OFF_F = OFF_CONV + 5 * CH_U;
constexpr int OFF_STG = OFF_F + 5 * CH_F;
constexpr int OFF_BAR = OFF_STG + 20480;
constexpr int SMEM_BYTES = OFF_BAR + 256 + 1024;

constexpr int B_FULL1 = 0, B_EMPTY1 = 3, B_RINGFREE = 6, B_HALO = 7, B_FULL2 = 9, B_EMPTY2 = 14, B_U = 19, B_KVST = 20;

__device__ __align__(1024) uint16_t g_kv[8 * 2 * 2 * SEQ * 40];
__device__ __align__(1024) uint16_t g_o[SEQ * DM];
__device__ __align__(1024) uint16_t g_kvT[DM * SEQ];
__device__ __align__(1024) uint16_t g_yT[DM * SEQ];
constexpr int CS = 32;
constexpr int C_KV = 0, C_O = 128, C_PRE = 144, C_Y = 152, C_DONE = 160, C_NUM = 161;
__device__ unsigned g_cnt[C_NUM * CS];
__device__ unsigned g_err;
#define PROF(slot) do {} while (0)

DEVINL void mbar_init(uint32_t a, uint32_t c) { asm volatile("mbarrier.init.shared::cta.b64 [%0], %1;" ::"r"(a), "r"(c)); }
DEVINL void mbar_expect(uint32_t a, uint32_t b) {
  asm volatile("mbarrier.arrive.expect_tx.shared::cta.b64 _, [%0], %1;" ::"r"(a), "r"(b) : "memory");
}
DEVINL void mbar_arrive(uint32_t a) { asm volatile("mbarrier.arrive.shared::cta.b64 _, [%0];" ::"r"(a) : "memory"); }
DEVINL void mbar_arrive_cta(uint32_t a, uint32_t cta) {
  asm volatile("{\n.reg .b32 ra;\nmapa.shared::cluster.u32 ra, %0, %1;\nmbarrier.arrive.shared::cluster.b64 _, [ra];\n}"
               ::"r"(a), "r"(cta) : "memory");
}
DEVINL bool mbar_try(uint32_t a, uint32_t p) {
  uint32_t ok;
  asm volatile("{\n.reg .pred P;\nmbarrier.try_wait.parity.shared::cta.b64 P, [%1], %2;\nselp.u32 %0, 1, 0, P;\n}"
               : "=r"(ok) : "r"(a), "r"(p) : "memory");
  return ok;
}
DEVINL void mbar_wait(uint32_t a, uint32_t p) {
  if (mbar_try(a, p)) return;
  int n = 0;
  while (!mbar_try(a, p)) {
    if (++n > (1 << 18)) { g_err = 1; break; }
  }
}
DEVINL void poll_ge(const unsigned* p, unsigned target) {
  int n = 0;
  while (true) {
    unsigned v;
    asm volatile("ld.acquire.gpu.global.u32 %0, [%1];" : "=r"(v) : "l"(p) : "memory");
    if (v >= target) break;
    if (++n > (1 << 20)) { g_err = 2; break; }
  }
}
DEVINL void red_publish(unsigned* p) { asm volatile("red.relaxed.gpu.global.add.u32 [%0], 1;" ::"l"(p) : "memory"); }
DEVINL void fence_async() { asm volatile("fence.proxy.async;" ::: "memory"); }
DEVINL void fence_async_smem() { asm volatile("fence.proxy.async.shared::cta;" ::: "memory"); }
DEVINL void named_sync(int id, int n) { asm volatile("bar.sync %0, %1;" ::"r"(id), "r"(n) : "memory"); }
DEVINL void named_arrive(int id, int n) { asm volatile("bar.arrive %0, %1;" ::"r"(id), "r"(n) : "memory"); }

DEVINL void tma2d(uint32_t dst, const CUtensorMap* m, int c0, int c1, uint32_t bar) {
  asm volatile("cp.async.bulk.tensor.2d.shared::cluster.global.mbarrier::complete_tx::bytes [%0], [%1, {%3, %4}], [%2];"
               ::"r"(dst), "l"(m), "r"(bar), "r"(c0), "r"(c1) : "memory");
}
DEVINL void tma2d_mc(uint32_t dst, const CUtensorMap* m, int c0, int c1, uint32_t bar) {
  asm volatile("cp.async.bulk.tensor.2d.shared::cluster.global.mbarrier::complete_tx::bytes.multicast::cluster [%0], [%1, {%3, %4}], [%2], %5;"
               ::"r"(dst), "l"(m), "r"(bar), "r"(c0), "r"(c1), "h"((uint16_t)3) : "memory");
}
DEVINL void tma3d(uint32_t dst, const CUtensorMap* m, int c0, int c1, int c2, uint32_t bar) {
  asm volatile("cp.async.bulk.tensor.3d.shared::cluster.global.mbarrier::complete_tx::bytes [%0], [%1, {%3, %4, %5}], [%2];"
               ::"r"(dst), "l"(m), "r"(bar), "r"(c0), "r"(c1), "r"(c2) : "memory");
}
DEVINL void tma3d_mc(uint32_t dst, const CUtensorMap* m, int c0, int c1, int c2, uint32_t bar) {
  asm volatile("cp.async.bulk.tensor.3d.shared::cluster.global.mbarrier::complete_tx::bytes.multicast::cluster [%0], [%1, {%3, %4, %5}], [%2], %6;"
               ::"r"(dst), "l"(m), "r"(bar), "r"(c0), "r"(c1), "r"(c2), "h"((uint16_t)3) : "memory");
}
DEVINL void tma2d_store(const CUtensorMap* m, int c0, int c1, uint32_t src) {
  asm volatile("cp.async.bulk.tensor.2d.global.shared::cta.bulk_group [%0, {%2, %3}], [%1];"
               ::"l"(m), "r"(src), "r"(c0), "r"(c1) : "memory");
}
DEVINL void tma3d_store(const CUtensorMap* m, int c0, int c1, int c2, uint32_t src) {
  asm volatile("cp.async.bulk.tensor.3d.global.shared::cta.bulk_group [%0, {%2, %3, %4}], [%1];"
               ::"l"(m), "r"(src), "r"(c0), "r"(c1), "r"(c2) : "memory");
}
DEVINL void bulk_load(uint32_t dst, const void* src, uint32_t bytes, uint32_t bar) {
  asm volatile("cp.async.bulk.shared::cluster.global.mbarrier::complete_tx::bytes [%0], [%1], %2, [%3];"
               ::"r"(dst), "l"(src), "r"(bytes), "r"(bar) : "memory");
}
DEVINL void bulk_store(void* dst, uint32_t src, uint32_t bytes) {
  asm volatile("cp.async.bulk.global.shared::cta.bulk_group [%0], [%1], %2;" ::"l"(dst), "r"(src), "r"(bytes) : "memory");
}
DEVINL void bulk_commit() { asm volatile("cp.async.bulk.commit_group;" ::: "memory"); }
DEVINL void bulk_wait0() { asm volatile("cp.async.bulk.wait_group 0;" ::: "memory"); }
DEVINL void bulk_wait0_read() { asm volatile("cp.async.bulk.wait_group.read 0;" ::: "memory"); }
DEVINL void prefetch_tmap(const CUtensorMap* m) { asm volatile("prefetch.tensormap [%0];" ::"l"(m) : "memory"); }

DEVINL uint64_t make_desc(uint32_t addr, uint32_t lbo, uint32_t sbo, uint32_t swz) {
  return (uint64_t)((addr & 0x3FFFF) >> 4) | ((uint64_t)(lbo >> 4) << 16) | ((uint64_t)(sbo >> 4) << 32) | ((uint64_t)swz << 62);
}
DEVINL void wg_fence() { asm volatile("wgmma.fence.sync.aligned;" ::: "memory"); }
DEVINL void wg_commit() { asm volatile("wgmma.commit_group.sync.aligned;" ::: "memory"); }
template <int N> DEVINL void wg_wait() { asm volatile("wgmma.wait_group.sync.aligned %0;" ::"n"(N) : "memory"); }

DEVINL void mma16816(float (&d)[4], uint32_t a0, uint32_t a1, uint32_t a2, uint32_t a3, uint32_t b0, uint32_t b1) {
  asm volatile("mma.sync.aligned.m16n8k16.row.col.f32.bf16.bf16.f32 {%0,%1,%2,%3},{%4,%5,%6,%7},{%8,%9},{%0,%1,%2,%3};"
               : "+f"(d[0]), "+f"(d[1]), "+f"(d[2]), "+f"(d[3]) : "r"(a0), "r"(a1), "r"(a2), "r"(a3), "r"(b0), "r"(b1));
}
DEVINL void mma16816_z(float (&d)[4], uint32_t a0, uint32_t a1, uint32_t a2, uint32_t a3, uint32_t b0, uint32_t b1) {
  asm volatile("mma.sync.aligned.m16n8k16.row.col.f32.bf16.bf16.f32 {%0,%1,%2,%3},{%4,%5,%6,%7},{%8,%9},{%10,%10,%10,%10};"
               : "=f"(d[0]), "=f"(d[1]), "=f"(d[2]), "=f"(d[3]) : "r"(a0), "r"(a1), "r"(a2), "r"(a3), "r"(b0), "r"(b1), "f"(0.f));
}
DEVINL void mma1688(float (&d)[4], uint32_t a0, uint32_t a1, uint32_t b0) {
  asm volatile("mma.sync.aligned.m16n8k8.row.col.f32.bf16.bf16.f32 {%0,%1,%2,%3},{%4,%5},{%6},{%0,%1,%2,%3};"
               : "+f"(d[0]), "+f"(d[1]), "+f"(d[2]), "+f"(d[3]) : "r"(a0), "r"(a1), "r"(b0));
}
DEVINL void ldsm4(uint32_t& r0, uint32_t& r1, uint32_t& r2, uint32_t& r3, uint32_t a) {
  asm volatile("ldmatrix.sync.aligned.m8n8.x4.shared.b16 {%0,%1,%2,%3}, [%4];" : "=r"(r0), "=r"(r1), "=r"(r2), "=r"(r3) : "r"(a));
}
DEVINL void ldsm2(uint32_t& r0, uint32_t& r1, uint32_t a) {
  asm volatile("ldmatrix.sync.aligned.m8n8.x2.shared.b16 {%0,%1}, [%2];" : "=r"(r0), "=r"(r1) : "r"(a));
}
DEVINL void ldsm4t(uint32_t& r0, uint32_t& r1, uint32_t& r2, uint32_t& r3, uint32_t a) {
  asm volatile("ldmatrix.sync.aligned.m8n8.x4.trans.shared.b16 {%0,%1,%2,%3}, [%4];" : "=r"(r0), "=r"(r1), "=r"(r2), "=r"(r3) : "r"(a));
}
DEVINL void ldsm2t(uint32_t& r0, uint32_t& r1, uint32_t a) {
  asm volatile("ldmatrix.sync.aligned.m8n8.x2.trans.shared.b16 {%0,%1}, [%2];" : "=r"(r0), "=r"(r1) : "r"(a));
}
DEVINL void stsm4(uint32_t a, uint32_t r0, uint32_t r1, uint32_t r2, uint32_t r3) {
  asm volatile("stmatrix.sync.aligned.m8n8.x4.shared.b16 [%0], {%1,%2,%3,%4};" ::"r"(a), "r"(r0), "r"(r1), "r"(r2), "r"(r3) : "memory");
}
DEVINL void stsm4t(uint32_t a, uint32_t r0, uint32_t r1, uint32_t r2, uint32_t r3) {
  asm volatile("stmatrix.sync.aligned.m8n8.x4.trans.shared.b16 [%0], {%1,%2,%3,%4};" ::"r"(a), "r"(r0), "r"(r1), "r"(r2), "r"(r3) : "memory");
}
DEVINL uint32_t lds32(uint32_t a) { uint32_t v; asm volatile("ld.shared.u32 %0, [%1];" : "=r"(v) : "r"(a)); return v; }
DEVINL uint4 lds128(uint32_t a) {
  uint4 v; asm volatile("ld.shared.v4.u32 {%0,%1,%2,%3}, [%4];" : "=r"(v.x), "=r"(v.y), "=r"(v.z), "=r"(v.w) : "r"(a)); return v;
}
DEVINL void sts32(uint32_t a, uint32_t v) { asm volatile("st.shared.u32 [%0], %1;" ::"r"(a), "r"(v) : "memory"); }
DEVINL void sts128(uint32_t a, uint4 v) {
  asm volatile("st.shared.v4.u32 [%0], {%1,%2,%3,%4};" ::"r"(a), "r"(v.x), "r"(v.y), "r"(v.z), "r"(v.w) : "memory");
}
DEVINL uint4 ldg_nc(const void* p) {
  uint4 v; asm volatile("ld.global.nc.L1::no_allocate.v4.u32 {%0,%1,%2,%3}, [%4];" : "=r"(v.x), "=r"(v.y), "=r"(v.z), "=r"(v.w) : "l"(p)); return v;
}
DEVINL uint4 ldg_cg(const void* p) {
  uint4 v; asm volatile("ld.global.cg.v4.u32 {%0,%1,%2,%3}, [%4];" : "=r"(v.x), "=r"(v.y), "=r"(v.z), "=r"(v.w) : "l"(p) : "memory"); return v;
}
DEVINL void stg128(void* p, uint4 v) {
  asm volatile("st.global.v4.u32 [%0], {%1,%2,%3,%4};" ::"l"(p), "r"(v.x), "r"(v.y), "r"(v.z), "r"(v.w) : "memory");
}
DEVINL uint32_t pack_bf16(float lo, float hi) {
  uint32_t r; asm("cvt.rn.bf16x2.f32 %0, %1, %2;" : "=r"(r) : "f"(hi), "f"(lo)); return r;
}
DEVINL uint32_t hmul2(uint32_t a, uint32_t b) { uint32_t r; asm("mul.rn.bf16x2 %0, %1, %2;" : "=r"(r) : "r"(a), "r"(b)); return r; }
DEVINL uint32_t hadd2(uint32_t a, uint32_t b) { uint32_t r; asm("add.rn.bf16x2 %0, %1, %2;" : "=r"(r) : "r"(a), "r"(b)); return r; }
DEVINL float ex2(float x) { float r; asm("ex2.approx.ftz.f32 %0, %1;" : "=f"(r) : "f"(x)); return r; }

DEVINL void wgmma_n192(float (&d)[96], uint64_t da, uint64_t db, int scale_d) {
  asm volatile("{\n.reg .pred p;\nsetp.ne.b32 p, %98, 0;\n"
    "wgmma.mma_async.sync.aligned.m64n192k16.f32.bf16.bf16 "
    "{%0,%1,%2,%3,%4,%5,%6,%7,%8,%9,%10,%11,%12,%13,%14,%15,"
    "%16,%17,%18,%19,%20,%21,%22,%23,%24,%25,%26,%27,%28,%29,%30,%31,"
    "%32,%33,%34,%35,%36,%37,%38,%39,%40,%41,%42,%43,%44,%45,%46,%47,"
    "%48,%49,%50,%51,%52,%53,%54,%55,%56,%57,%58,%59,%60,%61,%62,%63,"
    "%64,%65,%66,%67,%68,%69,%70,%71,%72,%73,%74,%75,%76,%77,%78,%79,"
    "%80,%81,%82,%83,%84,%85,%86,%87,%88,%89,%90,%91,%92,%93,%94,%95}, "
    "%96, %97, p, 1, 1, 0, 1;\n}\n"
    : "+f"(d[0]), "+f"(d[1]), "+f"(d[2]), "+f"(d[3]), "+f"(d[4]), "+f"(d[5]), "+f"(d[6]), "+f"(d[7]),
      "+f"(d[8]), "+f"(d[9]), "+f"(d[10]), "+f"(d[11]), "+f"(d[12]), "+f"(d[13]), "+f"(d[14]), "+f"(d[15]),
      "+f"(d[16]), "+f"(d[17]), "+f"(d[18]), "+f"(d[19]), "+f"(d[20]), "+f"(d[21]), "+f"(d[22]), "+f"(d[23]),
      "+f"(d[24]), "+f"(d[25]), "+f"(d[26]), "+f"(d[27]), "+f"(d[28]), "+f"(d[29]), "+f"(d[30]), "+f"(d[31]),
      "+f"(d[32]), "+f"(d[33]), "+f"(d[34]), "+f"(d[35]), "+f"(d[36]), "+f"(d[37]), "+f"(d[38]), "+f"(d[39]),
      "+f"(d[40]), "+f"(d[41]), "+f"(d[42]), "+f"(d[43]), "+f"(d[44]), "+f"(d[45]), "+f"(d[46]), "+f"(d[47]),
      "+f"(d[48]), "+f"(d[49]), "+f"(d[50]), "+f"(d[51]), "+f"(d[52]), "+f"(d[53]), "+f"(d[54]), "+f"(d[55]),
      "+f"(d[56]), "+f"(d[57]), "+f"(d[58]), "+f"(d[59]), "+f"(d[60]), "+f"(d[61]), "+f"(d[62]), "+f"(d[63]),
      "+f"(d[64]), "+f"(d[65]), "+f"(d[66]), "+f"(d[67]), "+f"(d[68]), "+f"(d[69]), "+f"(d[70]), "+f"(d[71]),
      "+f"(d[72]), "+f"(d[73]), "+f"(d[74]), "+f"(d[75]), "+f"(d[76]), "+f"(d[77]), "+f"(d[78]), "+f"(d[79]),
      "+f"(d[80]), "+f"(d[81]), "+f"(d[82]), "+f"(d[83]), "+f"(d[84]), "+f"(d[85]), "+f"(d[86]), "+f"(d[87]),
      "+f"(d[88]), "+f"(d[89]), "+f"(d[90]), "+f"(d[91]), "+f"(d[92]), "+f"(d[93]), "+f"(d[94]), "+f"(d[95])
    : "l"(da), "l"(db), "r"(scale_d));
}

DEVINL void wgmma_n48(float (&d)[24], uint64_t da, uint64_t db, int scale_d) {
  asm volatile("{\n.reg .pred p;\nsetp.ne.b32 p, %26, 0;\n"
    "wgmma.mma_async.sync.aligned.m64n48k16.f32.bf16.bf16 "
    "{%0,%1,%2,%3,%4,%5,%6,%7,%8,%9,%10,%11,%12,%13,%14,%15,"
    "%16,%17,%18,%19,%20,%21,%22,%23}, "
    "%24, %25, p, 1, 1, 0, 1;\n}\n"
    : "+f"(d[0]), "+f"(d[1]), "+f"(d[2]), "+f"(d[3]), "+f"(d[4]), "+f"(d[5]), "+f"(d[6]), "+f"(d[7]),
      "+f"(d[8]), "+f"(d[9]), "+f"(d[10]), "+f"(d[11]), "+f"(d[12]), "+f"(d[13]), "+f"(d[14]), "+f"(d[15]),
      "+f"(d[16]), "+f"(d[17]), "+f"(d[18]), "+f"(d[19]), "+f"(d[20]), "+f"(d[21]), "+f"(d[22]), "+f"(d[23])
    : "l"(da), "l"(db), "r"(scale_d));
}

DEVINL void wgmma_n80(float (&d)[40], uint64_t da, uint64_t db, int scale_d) {
  asm volatile("{\n.reg .pred p;\nsetp.ne.b32 p, %42, 0;\n"
    "wgmma.mma_async.sync.aligned.m64n80k16.f32.bf16.bf16 "
    "{%0,%1,%2,%3,%4,%5,%6,%7,%8,%9,%10,%11,%12,%13,%14,%15,"
    "%16,%17,%18,%19,%20,%21,%22,%23,%24,%25,%26,%27,%28,%29,%30,%31,"
    "%32,%33,%34,%35,%36,%37,%38,%39}, "
    "%40, %41, p, 1, 1, 0, 1;\n}\n"
    : "+f"(d[0]), "+f"(d[1]), "+f"(d[2]), "+f"(d[3]), "+f"(d[4]), "+f"(d[5]), "+f"(d[6]), "+f"(d[7]),
      "+f"(d[8]), "+f"(d[9]), "+f"(d[10]), "+f"(d[11]), "+f"(d[12]), "+f"(d[13]), "+f"(d[14]), "+f"(d[15]),
      "+f"(d[16]), "+f"(d[17]), "+f"(d[18]), "+f"(d[19]), "+f"(d[20]), "+f"(d[21]), "+f"(d[22]), "+f"(d[23]),
      "+f"(d[24]), "+f"(d[25]), "+f"(d[26]), "+f"(d[27]), "+f"(d[28]), "+f"(d[29]), "+f"(d[30]), "+f"(d[31]),
      "+f"(d[32]), "+f"(d[33]), "+f"(d[34]), "+f"(d[35]), "+f"(d[36]), "+f"(d[37]), "+f"(d[38]), "+f"(d[39])
    : "l"(da), "l"(db), "r"(scale_d));
}

constexpr float SM_C = 0.22360679774997896f * 1.4426950408889634f;
constexpr float NEG_INF = -INFINITY;

DEVINL void qk_block(float (&s0)[4], float (&s1)[4], const uint32_t (&a)[4], const uint32_t (&a8)[2],
                     uint32_t kaddr, uint32_t t0, uint32_t t1) {
  uint32_t b0, b1, b2, b3;
  ldsm4(b0, b1, b2, b3, kaddr);
  mma16816_z(s0, a[0], a[1], a[2], a[3], b0, b1);
  mma16816_z(s1, a[0], a[1], a[2], a[3], b2, b3);
  mma1688(s0, a8[0], a8[1], t0);
  mma1688(s1, a8[0], a8[1], t1);
}
DEVINL void pv_block(float (&o)[3][4], uint32_t p0, uint32_t p1, uint32_t p2, uint32_t p3, uint32_t vaddr,
                     uint32_t t0, uint32_t t1) {
  uint32_t b0, b1, b2, b3;
  ldsm4t(b0, b1, b2, b3, vaddr);
  mma16816(o[0], p0, p1, p2, p3, b0, b1);
  mma16816(o[1], p0, p1, p2, p3, b2, b3);
  mma16816(o[2], p0, p1, p2, p3, t0, t1);
}

template <bool FULL>
DEVINL void attn_all(uint32_t ring, uint32_t stg, uint32_t bars, int wq, int lane, int jmin) {
  const int g = lane >> 2, t = lane & 3, mi = lane >> 3, r = lane & 7;
  const uint32_t tri = ((2 * t > g) ? 0xFFFFu : 0u) | ((2 * t + 1 > g) ? 0xFFFF0000u : 0u);
  const uint32_t rowK = (16 * wq + r + 8 * (mi >> 1)) * 80 + (mi & 1) * 16;
  const uint32_t rowV = (16 * wq + r + 8 * (mi & 1)) * 80 + (mi >> 1) * 16;
  const uint32_t rowT = (16 * wq + r + 8 * mi) * 80;
  const uint32_t rowQ = stg + (16 * wq + r + 8 * (mi & 1)) * 160 + (mi >> 1) * 16;
  const int bar_me = 4 + 2 * (wq & 3) + (wq >> 2), bar_other = 4 + 2 * (wq & 3) + ((wq >> 2) ^ 1);
  if (FULL && wq >= 4) named_arrive(bar_other, 64);
#pragma unroll 1
  for (int h = 0; h < 4; ++h) {
    const int p = h >> 1, odd = h & 1;
    if (!odd) mbar_wait(bars + 8 * (B_HALO + p), 0);
    const uint32_t kw = ring + (2 * p) * KVWIN, vw = kw + KVWIN;
    const uint32_t kA = kw + rowK + odd * 48, kT = kw + rowT + 32;
    const uint32_t vA = vw + rowV + odd * 32, vT = vw + rowT + 32 + odd * 32;
    uint32_t a[4], a8[2];
    ldsm4(a[0], a[1], a[2], a[3], rowQ + p * 80 + odd * 48);
    ldsm2(a8[0], a8[1], stg + (16 * wq + (lane & 15)) * 160 + p * 80 + 32);
    if ((t >= 2) != (odd != 0)) { a8[0] = 0u; a8[1] = 0u; }
    float o[3][4];
#pragma unroll
    for (int n = 0; n < 3; ++n) { o[n][0] = 0.f; o[n][1] = 0.f; o[n][2] = 0.f; o[n][3] = 0.f; }
    float m0 = NEG_INF, m1 = NEG_INF, l0 = 0.f, l1 = 0.f;
#pragma unroll 1
    for (int c = 0; c < 2; ++c) {
      if (!FULL && c == 1 && jmin > 8) break;
      const int jb = c == 0 ? 9 : 1;
      const uint32_t jo = jb * 1280;
      float s[16][4];
      uint32_t t0, t1, t2, t3;
#pragma unroll
      for (int jj = 0; jj < 4; ++jj) {
        ldsm4(t0, t1, t2, t3, kT + jo + 2560 * jj);
        qk_block(s[4 * jj], s[4 * jj + 1], a, a8, kA + jo + 2560 * jj, t0, t1);
        qk_block(s[4 * jj + 2], s[4 * jj + 3], a, a8, kA + jo + 2560 * jj + 1280, t2, t3);
      }
      if (c == 0) {
        float z0[4], z1[4];
        ldsm2(t0, t1, kT);
        qk_block(z0, z1, a, a8, kA, t0, t1);
        if (!FULL && jmin > 0) {
#pragma unroll
          for (int e = 0; e < 4; ++e) { z0[e] = NEG_INF; z1[e] = NEG_INF; }
        }
        const bool c0 = tri & 1, c1 = tri >> 16;
        s[14][0] = c0 ? z0[0] : s[14][0];
        s[14][1] = c1 ? z0[1] : s[14][1];
        s[15][0] = z1[0];
        s[15][1] = z1[1];
        s[15][2] = c0 ? z1[2] : s[15][2];
        s[15][3] = c1 ? z1[3] : s[15][3];
      }
      if (!FULL) {
#pragma unroll
        for (int i = 0; i < 8; ++i) {
          if (jb + i < jmin) {
#pragma unroll
            for (int e = 0; e < 4; ++e) { s[2 * i][e] = NEG_INF; s[2 * i + 1][e] = NEG_INF; }
          }
        }
      }
      float x0 = fmaxf(s[0][0], s[0][1]);
      float x1 = fmaxf(s[0][2], s[0][3]);
#pragma unroll
      for (int i = 1; i < 16; ++i) {
        x0 = fmaxf(x0, fmaxf(s[i][0], s[i][1]));
        x1 = fmaxf(x1, fmaxf(s[i][2], s[i][3]));
      }
      x0 = fmaxf(x0, __shfl_xor_sync(0xffffffffu, x0, 1));
      x1 = fmaxf(x1, __shfl_xor_sync(0xffffffffu, x1, 1));
      x0 = fmaxf(x0, __shfl_xor_sync(0xffffffffu, x0, 2));
      x1 = fmaxf(x1, __shfl_xor_sync(0xffffffffu, x1, 2));
      x0 = fmaxf(x0, m0);
      x1 = fmaxf(x1, m1);
      const float al0 = ex2((m0 - x0) * SM_C), al1 = ex2((m1 - x1) * SM_C);
      m0 = x0; m1 = x1;
      const float n0 = -x0 * SM_C, n1 = -x1 * SM_C;
      l0 *= al0; l1 *= al1;
      uint32_t pp[16][2];
      if (FULL) named_sync(bar_me, 64);
#pragma unroll
      for (int i = 0; i < 16; ++i) {
        const float e0 = ex2(fmaf(s[i][0], SM_C, n0)), e1 = ex2(fmaf(s[i][1], SM_C, n0));
        const float e2 = ex2(fmaf(s[i][2], SM_C, n1)), e3 = ex2(fmaf(s[i][3], SM_C, n1));
        l0 += e0 + e1; l1 += e2 + e3;
        pp[i][0] = pack_bf16(e0, e1);
        pp[i][1] = pack_bf16(e2, e3);
      }
      if (FULL && !(wq >= 4 && h == 3 && c == 1)) named_arrive(bar_other, 64);
#pragma unroll
      for (int n = 0; n < 3; ++n) { o[n][0] *= al0; o[n][1] *= al0; o[n][2] *= al1; o[n][3] *= al1; }
      if (c == 0) {
        ldsm2t(t0, t1, vT);
        pv_block(o, pp[14][0] & tri, 0u, pp[15][0], pp[15][1] & tri, vA, t0, t1);
        pp[14][0] &= ~tri; pp[15][0] = 0u; pp[15][1] &= ~tri;
      }
#pragma unroll
      for (int jj = 0; jj < 4; ++jj) {
        ldsm4t(t0, t1, t2, t3, vT + jo + 2560 * jj);
        pv_block(o, pp[4 * jj][0], pp[4 * jj][1], pp[4 * jj + 1][0], pp[4 * jj + 1][1], vA + jo + 2560 * jj, t0, t1);
        pv_block(o, pp[4 * jj + 2][0], pp[4 * jj + 2][1], pp[4 * jj + 3][0], pp[4 * jj + 3][1], vA + jo + 2560 * jj + 1280, t2, t3);
      }
    }
    l0 += __shfl_xor_sync(0xffffffffu, l0, 1);
    l1 += __shfl_xor_sync(0xffffffffu, l1, 1);
    l0 += __shfl_xor_sync(0xffffffffu, l0, 2);
    l1 += __shfl_xor_sync(0xffffffffu, l1, 2);
    const float i0 = __frcp_rn(l0), i1 = __frcp_rn(l1);
    const uint32_t ob = stg + (16 * wq + g) * 160 + p * 80 + odd * 32 + t * 4;
    __syncwarp();
    const bool w0 = !odd || t >= 2, w2 = odd || t < 2;
    if (w0) { sts32(ob, pack_bf16(o[0][0] * i0, o[0][1] * i0)); sts32(ob + 1280, pack_bf16(o[0][2] * i1, o[0][3] * i1)); }
    sts32(ob + 16, pack_bf16(o[1][0] * i0, o[1][1] * i0)); sts32(ob + 16 + 1280, pack_bf16(o[1][2] * i1, o[1][3] * i1));
    if (w2) { sts32(ob + 32, pack_bf16(o[2][0] * i0, o[2][1] * i0)); sts32(ob + 32 + 1280, pack_bf16(o[2][2] * i1, o[2][3] * i1)); }
    __syncwarp();
  }
}

#define PRE_WAIT 0

struct Params {
  const uint16_t* q; const uint16_t* k; const uint16_t* v; const uint16_t* shift_k; const uint16_t* ssm_k;
  const uint16_t* ssm_D; uint16_t* out;
};

DEVINL unsigned* cnt(int i) { return &g_cnt[i * CS]; }

DEVINL void finish_role() {
  unsigned old = atomicAdd(cnt(C_DONE), 1u);
  if (old == 255u) {
    __threadfence();
    for (int i = 0; i < C_NUM; ++i) *cnt(i) = 0u;
    __threadfence();
  }
}

__global__ void __cluster_dims__(2, 1, 1) __launch_bounds__(512, 1)
h3_swa_fused_kernel(const __grid_constant__ CUtensorMap tmX, const __grid_constant__ CUtensorMap tmW128,
                    const __grid_constant__ CUtensorMap tmW32, const __grid_constant__ CUtensorMap tmO,
                    const __grid_constant__ CUtensorMap tmWo, const __grid_constant__ CUtensorMap tmOst,
                    const __grid_constant__ CUtensorMap tmOut, const __grid_constant__ CUtensorMap tmKT,
                    const Params prm) {
  extern __shared__ uint8_t smem_raw[];
  const uint32_t sb = ((uint32_t)__cvta_generic_to_shared(smem_raw) + 1023u) & ~1023u;
  const uint32_t bars = sb + OFF_BAR;
  const int tid = threadIdx.x, warp = tid >> 5, lane = tid & 31, wg = tid >> 7;
  const int cta = blockIdx.x;
  const uint32_t rank = cta & 1;
  const int g8 = (cta >> 1) & 7, rp = cta >> 4;
  const int rb = 2 * rp + rank;
  const int rb2 = 2 * rp + (g8 & 1);
  const int c2 = 2 * (g8 >> 1) + rank;

  if (tid == 384) {
    prefetch_tmap(&tmX); prefetch_tmap(&tmW128); prefetch_tmap(&tmW32);
  }
  if (tid == 0) {
    PROF(0);
    for (int i = 0; i < NST1; ++i) { mbar_init(bars + 8 * (B_FULL1 + i), 1); mbar_init(bars + 8 * (B_EMPTY1 + i), 16); }
    mbar_init(bars + 8 * B_RINGFREE, 1);
    mbar_init(bars + 8 * B_HALO, 1); mbar_init(bars + 8 * (B_HALO + 1), 1);
    for (int i = 0; i < NST2; ++i) { mbar_init(bars + 8 * (B_FULL2 + i), 1); mbar_init(bars + 8 * (B_EMPTY2 + i), 16); }
    mbar_init(bars + 8 * B_U, 1);
    mbar_init(bars + 8 * B_KVST, 8);
    asm volatile("fence.mbarrier_init.release.cluster;" ::: "memory");
  }
  __syncthreads();
  asm volatile("barrier.cluster.arrive.relaxed.aligned;\nbarrier.cluster.wait.aligned;" ::: "memory");

  if (wg == 3) {
    asm volatile("setmaxnreg.dec.sync.aligned.u32 40;");
    if (warp == 12 && lane == 0) {
      PROF(15);
      for (int it = 0; it < 10; ++it) {
        const int s = it % NST1;
        if (it >= NST1) mbar_wait(bars + 8 * (B_EMPTY1 + s), ((it / NST1) - 1) & 1);
        PROF(44 + it);
        const uint32_t st = sb + s * ST1, fb = bars + 8 * (B_FULL1 + s);
        mbar_expect(fb, ST1);
        tma2d(st, &tmX, it * 64, rb * 128, fb);
        tma3d_mc(st + ST1_B128 + rank * 12288, &tmW128, g8 * 80, it * 64 + rank * 32, 0, fb);
        tma3d_mc(st + ST1_B32 + rank * 3072, &tmW32, g8 * 80 + 64, it * 64 + rank * 32, 0, fb);
      }
      PROF(1);
      mbar_wait(bars + 8 * B_RINGFREE, 0);
      const int nh = rb >= 2 ? 256 : rb * 128;
      if (rb >= 1) poll_ge(cnt(C_KV + g8 * 16 + rb - 1), 1);
      if (rb >= 2) poll_ge(cnt(C_KV + g8 * 16 + rb - 2), 1);
      fence_async();
      PROF(2);
      for (int p = 0; p < 2; ++p) {
        const uint32_t hb = bars + 8 * (B_HALO + p);
        if (nh == 0) { mbar_arrive(hb); continue; }
        mbar_expect(hb, 2 * nh * 80);
        for (int kv = 0; kv < 2; ++kv)
          bulk_load(sb + (2 * p + kv) * KVWIN + (256 - nh) * 80,
                    g_kv + ((size_t)((g8 * 2 + p) * 2 + kv) * SEQ + (rb * 128 - nh)) * 40, nh * 80, hb);
      }
      for (int s = 0; s < NST2; ++s) {
        mbar_wait(bars + 8 * (B_EMPTY2 + s), 0);
        const uint32_t fb = bars + 8 * (B_FULL2 + s);
        mbar_expect(fb, ST2);
        tma3d(sb + s * ST2 + 16384, &tmWo, 0, s * 64, c2 * 5, fb);
      }
      PROF(3);
      poll_ge(cnt(C_O + rb2), 64);
      fence_async();
      PROF(4);
      for (int s = 0; s < NST2; ++s)
        tma2d_mc(sb + s * ST2 + rank * 8192, &tmO, s * 64, rb2 * 128 + rank * 64, bars + 8 * (B_FULL2 + s));
      for (int it = NST2; it < 10; ++it) {
        const int s = it - NST2;
        mbar_wait(bars + 8 * (B_EMPTY2 + s), 1);
        const uint32_t fb = bars + 8 * (B_FULL2 + s);
        mbar_expect(fb, ST2);
        tma3d(sb + s * ST2 + 16384, &tmWo, 0, it * 64, c2 * 5, fb);
        tma2d_mc(sb + s * ST2 + rank * 8192, &tmO, it * 64, rb2 * 128 + rank * 64, fb);
      }
      finish_role();
    } else if (warp == 13 && lane == 0) {
      prefetch_tmap(&tmO); prefetch_tmap(&tmWo); prefetch_tmap(&tmOst); prefetch_tmap(&tmOut);
      mbar_wait(bars + 8 * B_KVST, 0);
      for (int w = 0; w < 4; ++w)
        bulk_store(g_kv + ((size_t)(g8 * 4 + w) * SEQ + rb * 128) * 40, sb + w * KVWIN + 256 * 80, 128 * 80);
      bulk_commit();
      bulk_wait0();
      red_publish(cnt(C_KV + g8 * 16 + rb));
      PROF(24);
    }
  } else if (wg == 2) {
    asm volatile("setmaxnreg.inc.sync.aligned.u32 136;");
    const int ct = tid - 256, wc = warp - 8;
    const int tau = cta & 15, jt = cta >> 4;
    const int t0 = tau * 128, c0 = jt * 80;
    const int mi = lane >> 3, r = lane & 7, g = lane >> 2, t = lane & 3;
    const uint32_t U = sb + OFF_U, F = sb + OFF_F;
    if (ct == 0) PROF(14);
    mbar_wait(bars + 8 * (B_FULL1 + PRE_WAIT), 0);
    for (int item = ct; item < 160; item += 128) {
      const int c = item % 10, seg = item / 10;
      const int ts = t0 + seg * 8, ch = c0 + c * 8;
      uint4 kk[11], vv[8], wv[4];
#pragma unroll
      for (int i = 0; i < 11; ++i) {
        const int row = ts - 3 + i;
        kk[i] = row >= 0 ? ldg_nc(prm.k + (size_t)row * DM + ch) : make_uint4(0, 0, 0, 0);
      }
#pragma unroll
      for (int i = 0; i < 8; ++i) vv[i] = ldg_nc(prm.v + (size_t)(ts + i) * DM + ch);
#pragma unroll
      for (int u = 0; u < 4; ++u) wv[u] = ldg_nc(prm.shift_k + (size_t)(ch + 2 * u) * 4);
      uint32_t W[4][4];
#pragma unroll
      for (int u = 0; u < 4; ++u) {
        W[0][u] = __byte_perm(wv[u].x, wv[u].z, 0x5410);
        W[1][u] = __byte_perm(wv[u].x, wv[u].z, 0x7632);
        W[2][u] = __byte_perm(wv[u].y, wv[u].w, 0x5410);
        W[3][u] = __byte_perm(wv[u].y, wv[u].w, 0x7632);
      }
#pragma unroll
      for (int i = 0; i < 8; ++i) {
        uint32_t res[4];
#pragma unroll
        for (int u = 0; u < 4; ++u) {
          const uint32_t k0 = (&kk[i].x)[u], k1 = (&kk[i + 1].x)[u], k2 = (&kk[i + 2].x)[u], k3 = (&kk[i + 3].x)[u];
          uint32_t acc = hadd2(hmul2(k0, W[3][u]), hmul2(k1, W[2][u]));
          acc = hadd2(acc, hmul2(k2, W[1][u]));
          acc = hadd2(acc, hmul2(k3, W[0][u]));
          res[u] = hmul2(acc, (&vv[i].x)[u]);
        }
        sts128(U + (seg * 8 + i) * 160 + c * 16, make_uint4(res[0], res[1], res[2], res[3]));
      }
    }
    if (ct == 0) PROF(5);
    if (ct == 127) PROF(6);
    named_sync(3, 128);
    if (ct == 0) PROF(7);
    for (int it = wc; it < 40; it += 4) {
      const int c = it % 10, rest = it / 10, h = rest & 1, iq = rest >> 1;
      const int tl = 16 * (4 * iq + (r >> 1)) + 15 - (8 * h + 2 * mi + (r & 1));
      uint4 v4;
      ldsm4t(v4.x, v4.y, v4.z, v4.w, U + tl * 160 + c * 16);
      sts128(F + (c * 8 + g) * 256 + h * 128 + (4 * iq + t) * 16, v4);
    }
    fence_async_smem();
    named_sync(3, 128);
    if (ct == 0) {
      tma3d_store(&tmKT, 64 * tau, 0, c0, F);
      bulk_commit();
      bulk_wait0();
      red_publish(cnt(C_PRE + jt));
      PROF(8);
    }
    if (ct >= 32 && ct < 112) {
      const int z = ct - 32;
      sts128(U + (z >> 4) * CH_U + ((z >> 3) & 1) * 2176 + (z & 7) * 16, make_uint4(0, 0, 0, 0));
    }
    named_sync(3, 128);
    {
      const int chb = cta * 5;
      uint4 fv[10]; uint32_t pv[10];
#pragma unroll
      for (int i = 0; i < 10; ++i) {
        const int cl = i >> 1, qq = ct + (i & 1) * 128;
        const uint16_t* src = prm.ssm_k + (size_t)(chb + cl) * SEQ + qq * 8;
        fv[i] = ldg_nc(src);
        pv[i] = qq > 0 ? (uint32_t)__ldg(src - 1) : 0u;
      }
#pragma unroll
      for (int i = 0; i < 10; ++i) {
        const int cl = i >> 1, qq = ct + (i & 1) * 128;
        const uint32_t a = F + cl * CH_F + 32 + qq * 16;
        sts128(a, fv[i]);
        sts128(a + 4160, make_uint4(__byte_perm(pv[i], fv[i].x, 0x5410), __byte_perm(fv[i].x, fv[i].y, 0x5432),
                                    __byte_perm(fv[i].y, fv[i].z, 0x5432), __byte_perm(fv[i].z, fv[i].w, 0x5432)));
      }
      if (ct < 20) sts128(F + (ct >> 2) * CH_F + ((ct >> 1) & 1) * 4160 + (ct & 1) * 16, make_uint4(0, 0, 0, 0));
    }
    if (ct == 0) {
      poll_ge(cnt(C_PRE + jt), 16);
      fence_async();
      mbar_expect(bars + 8 * B_U, 5 * 4096);
      for (int i = 0; i < 10; ++i)
        bulk_load(U + (i >> 1) * CH_U + (i & 1) * 2176 + 128, g_kvT + (size_t)(cta * 5) * SEQ + i * 1024, 2048, bars + 8 * B_U);
      PROF(9);
    }
    named_sync(3, 128);
    mbar_wait(bars + 8 * B_U, 0);
    if (ct == 0) PROF(10);
#pragma unroll 1
    for (int pass = 0; pass < 2; ++pass) {
      const int cl = pass == 0 ? wc : 4;
      const int r0 = pass == 0 ? 0 : 2 * wc, r1 = pass == 0 ? 8 : 2 * wc + 2;
      const uint32_t Ub = U + cl * CH_U, Fb = F + cl * CH_F;
      const uint32_t laneU = Ub + (mi & 1) * 2176 + (8 + 8 * (mi >> 1) + r) * 16;
      const uint32_t laneF = (g & 1) ? Fb + 4160 + 2 * (17 - g + 2 * t) : Fb + 2 * (16 - g + 2 * t);
      float acc[16][4];
#pragma unroll
      for (int i = 0; i < 16; ++i) { acc[i][0] = 0.f; acc[i][1] = 0.f; acc[i][2] = 0.f; acc[i][3] = 0.f; }
#pragma unroll 1
      for (int rho = r0; rho < r1; ++rho) {
        uint32_t uf[16][2];
#pragma unroll
        for (int jj = 0; jj < 8; ++jj)
          ldsm4(uf[2 * jj][0], uf[2 * jj][1], uf[2 * jj + 1][0], uf[2 * jj + 1][1], laneU + jj * 256 - rho * 16);
        const uint32_t fb = laneF + 32 * rho;
#pragma unroll
        for (int mu = 0; mu < 16; ++mu) {
          const uint32_t a0 = lds32(fb + 256 * mu), a1 = lds32(fb + 256 * mu - 16), a2 = lds32(fb + 256 * mu + 16);
#pragma unroll
          for (int i = mu; i < 16; ++i) mma16816(acc[i], a0, a1, a2, a0, uf[i - mu][0], uf[i - mu][1]);
        }
      }
      const uint32_t dv = (uint32_t)__ldg(prm.ssm_D + cta * 5 + cl);
      const uint32_t D2 = dv | (dv << 16);
      if (pass == 0) {
        uint32_t res[8][4];
#pragma unroll
        for (int jj = 0; jj < 8; ++jj) {
          uint32_t u0, u1, u2, u3;
          ldsm4t(u0, u1, u2, u3, laneU + jj * 256);
          res[jj][0] = hadd2(pack_bf16(acc[2 * jj][0], acc[2 * jj][1]), hmul2(u0, D2));
          res[jj][1] = hadd2(pack_bf16(acc[2 * jj][2], acc[2 * jj][3]), hmul2(u1, D2));
          res[jj][2] = hadd2(pack_bf16(acc[2 * jj + 1][0], acc[2 * jj + 1][1]), hmul2(u2, D2));
          res[jj][3] = hadd2(pack_bf16(acc[2 * jj + 1][2], acc[2 * jj + 1][3]), hmul2(u3, D2));
        }
        __syncwarp();
#pragma unroll
        for (int jj = 0; jj < 8; ++jj)
          stsm4t(Ub + ((8 * (2 * jj + (mi >> 1)) + r) * 16 + 8 * (mi & 1)) * 2, res[jj][0], res[jj][1], res[jj][2], res[jj][3]);
        fence_async_smem();
        __syncwarp();
        if (lane == 0) {
          bulk_store(g_yT + (size_t)(cta * 5 + cl) * SEQ, Ub, 4096);
          bulk_commit();
          bulk_wait0();
          red_publish(cnt(C_Y + jt));
        }
        __syncwarp();
      } else {
        const uint32_t rbuf = F + wc * CH_F + lane * 16;
#pragma unroll
        for (int i = 0; i < 16; ++i)
          sts128(rbuf + i * 512, make_uint4(__float_as_uint(acc[i][0]), __float_as_uint(acc[i][1]),
                                            __float_as_uint(acc[i][2]), __float_as_uint(acc[i][3])));
        named_sync(3, 128);
        uint32_t res[2][4];
#pragma unroll
        for (int jj = 0; jj < 2; ++jj) {
          float sum[2][4];
#pragma unroll
          for (int hh = 0; hh < 2; ++hh) {
            const int tile = 4 * wc + 2 * jj + hh;
            sum[hh][0] = 0.f; sum[hh][1] = 0.f; sum[hh][2] = 0.f; sum[hh][3] = 0.f;
#pragma unroll
            for (int w = 0; w < 4; ++w) {
              const uint4 x = lds128(F + w * CH_F + lane * 16 + tile * 512);
              sum[hh][0] += __uint_as_float(x.x); sum[hh][1] += __uint_as_float(x.y);
              sum[hh][2] += __uint_as_float(x.z); sum[hh][3] += __uint_as_float(x.w);
            }
          }
          uint32_t u0, u1, u2, u3;
          ldsm4t(u0, u1, u2, u3, laneU + (2 * wc + jj) * 256);
          res[jj][0] = hadd2(pack_bf16(sum[0][0], sum[0][1]), hmul2(u0, D2));
          res[jj][1] = hadd2(pack_bf16(sum[0][2], sum[0][3]), hmul2(u1, D2));
          res[jj][2] = hadd2(pack_bf16(sum[1][0], sum[1][1]), hmul2(u2, D2));
          res[jj][3] = hadd2(pack_bf16(sum[1][2], sum[1][3]), hmul2(u3, D2));
        }
#pragma unroll
        for (int jj = 0; jj < 2; ++jj)
          stsm4t(U + ((8 * (2 * (2 * wc + jj) + (mi >> 1)) + r) * 16 + 8 * (mi & 1)) * 2, res[jj][0], res[jj][1], res[jj][2], res[jj][3]);
        fence_async_smem();
        named_sync(3, 128);
        if (ct == 0) {
          bulk_store(g_yT + (size_t)(cta * 5 + 4) * SEQ, U, 4096);
          bulk_commit();
          bulk_wait0();
          red_publish(cnt(C_Y + jt));
          PROF(11);
        }
      }
    }
    uint4 qv[10];
#pragma unroll
    for (int i = 0; i < 10; ++i) {
      const int idx = ct + 128 * i, row = idx / 10, c = idx % 10;
      qv[i] = ldg_nc(prm.q + (size_t)(t0 + row) * DM + c0 + c * 8);
    }
    if (ct == 0) { poll_ge(cnt(C_Y + jt), 80); finish_role(); PROF(12); }
    named_sync(3, 128);
    const uint32_t YT = sb + OFF_U, YN = sb + OFF_F + 1024;
#pragma unroll
    for (int i = 0; i < 10; ++i) {
      const int idx = ct + 128 * i, ch = idx >> 4, cq = idx & 15;
      sts128(YT + ch * 272 + cq * 16, ldg_cg(g_yT + (size_t)(c0 + ch) * SEQ + t0 + cq * 8));
    }
    named_sync(3, 128);
    for (int it = wc; it < 40; it += 4) {
      const int c = it % 10, tq = it / 10;
      uint32_t x0, x1, x2, x3;
      ldsm4t(x0, x1, x2, x3, YT + (8 * c + r) * 272 + (4 * tq + mi) * 16);
      const int s = (8 * (4 * tq + mi) + r) ^ 15;
      stsm4(YN + s * 176 + c * 16, x0, x1, x2, x3);
    }
    named_sync(3, 128);
#pragma unroll
    for (int i = 0; i < 10; ++i) {
      const int idx = ct + 128 * i, row = idx / 10, c = idx % 10;
      const uint4 y = lds128(YN + row * 176 + c * 16);
      stg128(prm.out + (size_t)(t0 + row) * (2 * DM) + c0 + c * 8,
             make_uint4(hmul2(qv[i].x, y.x), hmul2(qv[i].y, y.y), hmul2(qv[i].z, y.z), hmul2(qv[i].w, y.w)));
    }
    if (ct == 0) PROF(13);
  } else {
    asm volatile("setmaxnreg.inc.sync.aligned.u32 168;");
    const int wq = warp;
    const int mi = lane >> 3, r = lane & 7;
    {
      float acc1[96], acc2[24];
#pragma unroll 1
      for (int it = 0; it < 10; ++it) {
        const int s = it % NST1;
        mbar_wait(bars + 8 * (B_FULL1 + s), (it / NST1) & 1);
        if (tid == 0) PROF(32 + it);
        const uint32_t st = sb + s * ST1;
        wg_fence();
#pragma unroll
        for (int kk = 0; kk < 4; ++kk) {
          const uint64_t da = make_desc(st + wg * 8192 + kk * 32, 16, 1024, 1);
          const uint64_t db1 = make_desc(st + ST1_B128 + (kk >> 1) * 12288 + (kk & 1) * 2048, 4096, 1024, 1);
          const uint64_t db2 = make_desc(st + ST1_B32 + (kk >> 1) * 3072 + (kk & 1) * 512, 1024, 256, 3);
          wgmma_n192(acc1, da, db1, (it | kk) != 0);
          wgmma_n48(acc2, da, db2, (it | kk) != 0);
        }
        wg_commit();
        wg_wait<0>();
        if (it + NST1 < 10 && lane < 2) mbar_arrive_cta(bars + 8 * (B_EMPTY1 + s), lane);
      }
      if (tid == 0) PROF(17);
      named_sync(1, 256);
      if (tid == 0) mbar_arrive(bars + 8 * B_RINGFREE);
      {
        const uint32_t rq = sb + OFF_STG + (16 * wq + 8 * (mi & 1) + r) * 160 + (mi >> 1) * 16;
#pragma unroll
        for (int tp = 0; tp < 4; ++tp)
          stsm4(rq + tp * 32, pack_bf16(acc1[8 * tp], acc1[8 * tp + 1]), pack_bf16(acc1[8 * tp + 2], acc1[8 * tp + 3]),
                pack_bf16(acc1[8 * tp + 4], acc1[8 * tp + 5]), pack_bf16(acc1[8 * tp + 6], acc1[8 * tp + 7]));
        stsm4(rq + 128, pack_bf16(acc2[0], acc2[1]), pack_bf16(acc2[2], acc2[3]), pack_bf16(acc2[4], acc2[5]), pack_bf16(acc2[6], acc2[7]));
      }
      const uint32_t rowa = sb + (256 + 16 * wq + 8 * (mi & 1) + r) * 80;
#pragma unroll
      for (int kv = 0; kv < 2; ++kv) {
#pragma unroll
        for (int tp = 0; tp < 5; ++tp) {
          uint32_t w[4];
#pragma unroll
          for (int hh = 0; hh < 2; ++hh) {
            const int tile = 2 * tp + hh;
            if (tile < 8) {
              const int o = 32 * (kv + 1) + 4 * tile;
              w[2 * hh] = pack_bf16(acc1[o], acc1[o + 1]); w[2 * hh + 1] = pack_bf16(acc1[o + 2], acc1[o + 3]);
            } else {
              const int o = 8 * (kv + 1) + 4 * (tile - 8);
              w[2 * hh] = pack_bf16(acc2[o], acc2[o + 1]); w[2 * hh + 1] = pack_bf16(acc2[o + 2], acc2[o + 3]);
            }
          }
          const int tA = 2 * tp, tB = 2 * tp + 1;
          const uint32_t offA = ((tA / 5) * 2 + kv) * KVWIN + (tA % 5) * 16;
          const uint32_t offB = ((tB / 5) * 2 + kv) * KVWIN + (tB % 5) * 16;
          stsm4(rowa + ((mi >> 1) ? offB : offA), w[0], w[1], w[2], w[3]);
        }
      }
    }
    if (rb < 2) {
      const int nz = (2 - rb) * 128 * 5;
#pragma unroll 1
      for (int i = tid; i < 4 * nz; i += 256) {
        const int w = i / nz;
        sts128(sb + w * KVWIN + (i - w * nz) * 16, make_uint4(0, 0, 0, 0));
      }
    }
    fence_async_smem();
    __syncwarp();
    if (lane == 0) mbar_arrive(bars + 8 * B_KVST);
    named_sync(2, 256);
    if (tid == 0) PROF(18);
    const uint32_t stg = sb + OFF_STG;
    if (rb >= 2) attn_all<true>(sb, stg, bars, wq, lane, 0);
    else attn_all<false>(sb, stg, bars, wq, lane, max(0, 16 - 8 * rb - wq));
    if (tid == 0) PROF(19);
    fence_async_smem();
    __syncwarp();
    if (lane < 2 * NST2) mbar_arrive_cta(bars + 8 * (B_EMPTY2 + (lane >> 1)), lane & 1);
    if (lane == 0) {
      tma2d_store(&tmOst, g8 * 80, rb * 128 + 16 * wq, stg + wq * 2560);
      bulk_commit();
      bulk_wait0();
      red_publish(cnt(C_O + rb));
    }
    __syncwarp();
    if (tid == 0) PROF(20);
    float acc[40];
#pragma unroll 1
    for (int it = 0; it < 10; ++it) {
      const int s = it % NST2;
      mbar_wait(bars + 8 * (B_FULL2 + s), (it / NST2) & 1);
      if (it == 0 && tid == 0) PROF(21);
      const uint32_t st = sb + s * ST2;
      wg_fence();
#pragma unroll
      for (int kk = 0; kk < 4; ++kk)
        wgmma_n80(acc, make_desc(st + wg * 8192 + kk * 32, 16, 1024, 1), make_desc(st + 16384 + kk * 512, 2048, 256, 3), (it | kk) != 0);
      wg_commit();
      wg_wait<0>();
      if (it + NST2 < 10 && lane < 2) mbar_arrive_cta(bars + 8 * (B_EMPTY2 + s), lane);
    }
    if (tid == 0) PROF(22);
    {
      const uint32_t rowa = stg + (16 * wq + 8 * (mi & 1) + r) * 160 + (mi >> 1) * 16;
#pragma unroll
      for (int tp = 0; tp < 5; ++tp)
        stsm4(rowa + tp * 32, pack_bf16(acc[8 * tp], acc[8 * tp + 1]), pack_bf16(acc[8 * tp + 2], acc[8 * tp + 3]),
              pack_bf16(acc[8 * tp + 4], acc[8 * tp + 5]), pack_bf16(acc[8 * tp + 6], acc[8 * tp + 7]));
      fence_async_smem();
      __syncwarp();
      if (lane == 0) {
        tma2d_store(&tmOut, DM + c2 * 80, rb2 * 128 + 16 * wq, stg + wq * 2560);
        bulk_commit();
        bulk_wait0_read();
      }
    }
    if (tid == 0) PROF(23);
  }
}

typedef CUresult (*EncodeFn)(CUtensorMap*, CUtensorMapDataType, cuuint32_t, void*, const cuuint64_t*, const cuuint64_t*,
                             const cuuint32_t*, const cuuint32_t*, CUtensorMapInterleave, CUtensorMapSwizzle,
                             CUtensorMapL2promotion, CUtensorMapFloatOOBfill);

CUtensorMap make_map(EncodeFn enc, const void* p, int rank, const cuuint64_t* dims, const cuuint64_t* strides,
                     const cuuint32_t* box, CUtensorMapSwizzle sw) {
  CUtensorMap m;
  const cuuint32_t es[3] = {1, 1, 1};
  enc(&m, CU_TENSOR_MAP_DATA_TYPE_BFLOAT16, rank, const_cast<void*>(p), dims, strides, box, es,
      CU_TENSOR_MAP_INTERLEAVE_NONE, sw, CU_TENSOR_MAP_L2_PROMOTION_L2_128B, CU_TENSOR_MAP_FLOAT_OOB_FILL_NONE);
  return m;
}

}

extern "C" void kernel_launch(void* const* d_in, const int* in_sizes, int n_in, void* d_out, int out_size) {
  (void)in_sizes; (void)n_in; (void)out_size;
  static EncodeFn enc = nullptr;
  static void* o_ptr = nullptr;
  static void* kt_ptr = nullptr;
  if (!enc) {
    void* fn = nullptr;
    cudaDriverEntryPointQueryResult qr;
    cudaGetDriverEntryPoint("cuTensorMapEncodeTiled", &fn, cudaEnableDefault, &qr);
    enc = (EncodeFn)fn;
    cudaGetSymbolAddress(&o_ptr, g_o);
    cudaGetSymbolAddress(&kt_ptr, g_kvT);
    cudaFuncSetAttribute(h3_swa_fused_kernel, cudaFuncAttributeMaxDynamicSharedMemorySize, SMEM_BYTES);
  }
  const void* x = d_in[6];
  const void* wqkv = d_in[7];
  const void* wo = d_in[8];
  CUtensorMap tmX, tmW128, tmW32, tmO, tmWo, tmOst, tmOut, tmKT;
  { cuuint64_t d[2] = {640, 2048}, s[1] = {1280}; cuuint32_t b[2] = {64, 128};
    tmX = make_map(enc, x, 2, d, s, b, CU_TENSOR_MAP_SWIZZLE_128B); }
  { cuuint64_t d[3] = {640, 640, 3}, s[2] = {3840, 1280}; cuuint32_t b[3] = {64, 32, 3};
    tmW128 = make_map(enc, wqkv, 3, d, s, b, CU_TENSOR_MAP_SWIZZLE_128B); }
  { cuuint64_t d[3] = {640, 640, 3}, s[2] = {3840, 1280}; cuuint32_t b[3] = {16, 32, 3};
    tmW32 = make_map(enc, wqkv, 3, d, s, b, CU_TENSOR_MAP_SWIZZLE_32B); }
  { cuuint64_t d[2] = {640, 2048}, s[1] = {1280}; cuuint32_t b[2] = {64, 64};
    tmO = make_map(enc, o_ptr, 2, d, s, b, CU_TENSOR_MAP_SWIZZLE_128B); }
  { cuuint64_t d[3] = {16, 640, 40}, s[2] = {1280, 32}; cuuint32_t b[3] = {16, 64, 5};
    tmWo = make_map(enc, wo, 3, d, s, b, CU_TENSOR_MAP_SWIZZLE_32B); }
  { cuuint64_t d[2] = {640, 2048}, s[1] = {1280}; cuuint32_t b[2] = {80, 16};
    tmOst = make_map(enc, o_ptr, 2, d, s, b, CU_TENSOR_MAP_SWIZZLE_NONE); }
  { cuuint64_t d[2] = {1280, 2048}, s[1] = {2560}; cuuint32_t b[2] = {80, 16};
    tmOut = make_map(enc, d_out, 2, d, s, b, CU_TENSOR_MAP_SWIZZLE_NONE); }
  { cuuint64_t d[3] = {1024, 2, 640}, s[2] = {2048, 4096}; cuuint32_t b[3] = {64, 2, 80};
    tmKT = make_map(enc, kt_ptr, 3, d, s, b, CU_TENSOR_MAP_SWIZZLE_NONE); }
  Params prm;
  prm.q = (const uint16_t*)d_in[0]; prm.k = (const uint16_t*)d_in[1]; prm.v = (const uint16_t*)d_in[2];
  prm.shift_k = (const uint16_t*)d_in[3]; prm.ssm_k = (const uint16_t*)d_in[4]; prm.ssm_D = (const uint16_t*)d_in[5];
  prm.out = (uint16_t*)d_out;
  h3_swa_fused_kernel<<<128, 512, SMEM_BYTES>>>(tmX, tmW128, tmW32, tmO, tmWo, tmOst, tmOut, tmKT, prm);
}
```

```cpp
#include <cuda_runtime.h>
#include <cuda.h>
#include <cuda_bf16.h>
#include <stdint.h>

#define DEVINL __device__ __forceinline__

namespace {

constexpr int SEQ = 2048;
constexpr int DM = 640;

constexpr int ST1 = 47104;
constexpr int ST1_B128 = 16384;
constexpr int ST1_B32 = 40960;
constexpr int NST1 = 3;
constexpr int ST2 = 26624;
constexpr int NST2 = 5;
constexpr int OFF_CONV = NST1 * ST1;
constexpr int CH_U = 4352;
constexpr int CH_F = 8320;
constexpr int OFF_U = OFF_CONV;
constexpr int OFF_F = OFF_CONV + 5 * CH_U;
constexpr int OFF_STG = OFF_F + 5 * CH_F;
constexpr int OFF_BAR = OFF_STG + 20480;
constexpr int SMEM_BYTES = OFF_BAR + 256 + 1024;

constexpr int B_FULL1 = 0, B_EMPTY1 = 3, B_RINGFREE = 6, B_HALO = 7, B_FULL2 = 9, B_EMPTY2 = 14, B_U = 19;

__device__ __align__(1024) uint16_t g_kv[8 * 16 * 22 * 1024];
__device__ __align__(1024) uint16_t g_o[SEQ * DM];
__device__ __align__(1024) uint16_t g_kvT[DM * SEQ];
__device__ __align__(1024) uint16_t g_yT[DM * SEQ];
constexpr int CS = 32;
constexpr int C_KV = 0, C_O = 128, C_PRE = 144, C_Y = 152, C_DONE = 160, C_NUM = 161;
__device__ unsigned g_cnt[C_NUM * CS];
__device__ unsigned g_err;
#define PROF(slot) do {} while (0)

DEVINL void mbar_init(uint32_t a, uint32_t c) { asm volatile("mbarrier.init.shared::cta.b64 [%0], %1;" ::"r"(a), "r"(c)); }
DEVINL void mbar_expect(uint32_t a, uint32_t b) {
  asm volatile("mbarrier.arrive.expect_tx.shared::cta.b64 _, [%0], %1;" ::"r"(a), "r"(b) : "memory");
}
DEVINL void mbar_arrive(uint32_t a) { asm volatile("mbarrier.arrive.shared::cta.b64 _, [%0];" ::"r"(a) : "memory"); }
DEVINL void mbar_arrive_cta(uint32_t a, uint32_t cta) {
  asm volatile("{\n.reg .b32 ra;\nmapa.shared::cluster.u32 ra, %0, %1;\nmbarrier.arrive.shared::cluster.b64 _, [ra];\n}"
               ::"r"(a), "r"(cta) : "memory");
}
DEVINL bool mbar_try(uint32_t a, uint32_t p) {
  uint32_t ok;
  asm volatile("{\n.reg .pred P;\nmbarrier.try_wait.parity.shared::cta.b64 P, [%1], %2;\nselp.u32 %0, 1, 0, P;\n}"
               : "=r"(ok) : "r"(a), "r"(p) : "memory");
  return ok;
}
DEVINL void mbar_wait(uint32_t a, uint32_t p) {
  if (mbar_try(a, p)) return;
  int n = 0;
  while (!mbar_try(a, p)) {
    if (++n > (1 << 18)) { g_err = 1; break; }
  }
}
DEVINL void poll_ge(const unsigned* p, unsigned target) {
  int n = 0;
  while (true) {
    unsigned v;
    asm volatile("ld.relaxed.gpu.global.u32 %0, [%1];" : "=r"(v) : "l"(p) : "memory");
    if (v >= target) break;
    if (++n > (1 << 20)) { g_err = 2; break; }
  }
}
DEVINL void red_publish(unsigned* p) { asm volatile("red.release.gpu.global.add.u32 [%0], 1;" ::"l"(p) : "memory"); }
DEVINL void warp_publish(unsigned* p, int lane) {
  asm volatile("fence.acq_rel.gpu;" ::: "memory");
  __syncwarp();
  if (lane == 0) asm volatile("red.relaxed.gpu.global.add.u32 [%0], 1;" ::"l"(p) : "memory");
}
DEVINL void fence_async_smem() { asm volatile("fence.proxy.async.shared::cta;" ::: "memory"); }
DEVINL void named_sync(int id, int n) { asm volatile("bar.sync %0, %1;" ::"r"(id), "r"(n) : "memory"); }
DEVINL void named_arrive(int id, int n) { asm volatile("bar.arrive %0, %1;" ::"r"(id), "r"(n) : "memory"); }

DEVINL void tma2d(uint32_t dst, const CUtensorMap* m, int c0, int c1, uint32_t bar) {
  asm volatile("cp.async.bulk.tensor.2d.shared::cluster.global.mbarrier::complete_tx::bytes [%0], [%1, {%3, %4}], [%2];"
               ::"r"(dst), "l"(m), "r"(bar), "r"(c0), "r"(c1) : "memory");
}
DEVINL void tma2d_mc(uint32_t dst, const CUtensorMap* m, int c0, int c1, uint32_t bar) {
  asm volatile("cp.async.bulk.tensor.2d.shared::cluster.global.mbarrier::complete_tx::bytes.multicast::cluster [%0], [%1, {%3, %4}], [%2], %5;"
               ::"r"(dst), "l"(m), "r"(bar), "r"(c0), "r"(c1), "h"((uint16_t)3) : "memory");
}
DEVINL void tma3d(uint32_t dst, const CUtensorMap* m, int c0, int c1, int c2, uint32_t bar) {
  asm volatile("cp.async.bulk.tensor.3d.shared::cluster.global.mbarrier::complete_tx::bytes [%0], [%1, {%3, %4, %5}], [%2];"
               ::"r"(dst), "l"(m), "r"(bar), "r"(c0), "r"(c1), "r"(c2) : "memory");
}
DEVINL void tma3d_mc(uint32_t dst, const CUtensorMap* m, int c0, int c1, int c2, uint32_t bar) {
  asm volatile("cp.async.bulk.tensor.3d.shared::cluster.global.mbarrier::complete_tx::bytes.multicast::cluster [%0], [%1, {%3, %4, %5}], [%2], %6;"
               ::"r"(dst), "l"(m), "r"(bar), "r"(c0), "r"(c1), "r"(c2), "h"((uint16_t)3) : "memory");
}
DEVINL void tma2d_store(const CUtensorMap* m, int c0, int c1, uint32_t src) {
  asm volatile("cp.async.bulk.tensor.2d.global.shared::cta.bulk_group [%0, {%2, %3}], [%1];"
               ::"l"(m), "r"(src), "r"(c0), "r"(c1) : "memory");
}
DEVINL void tma3d_store(const CUtensorMap* m, int c0, int c1, int c2, uint32_t src) {
  asm volatile("cp.async.bulk.tensor.3d.global.shared::cta.bulk_group [%0, {%2, %3, %4}], [%1];"
               ::"l"(m), "r"(src), "r"(c0), "r"(c1), "r"(c2) : "memory");
}
DEVINL void bulk_load(uint32_t dst, const void* src, uint32_t bytes, uint32_t bar) {
  asm volatile("cp.async.bulk.shared::cluster.global.mbarrier::complete_tx::bytes [%0], [%1], %2, [%3];"
               ::"r"(dst), "l"(src), "r"(bytes), "r"(bar) : "memory");
}
DEVINL void bulk_store(void* dst, uint32_t src, uint32_t bytes) {
  asm volatile("cp.async.bulk.global.shared::cta.bulk_group [%0], [%1], %2;" ::"l"(dst), "r"(src), "r"(bytes) : "memory");
}
DEVINL void bulk_commit() { asm volatile("cp.async.bulk.commit_group;" ::: "memory"); }
DEVINL void bulk_wait0() { asm volatile("cp.async.bulk.wait_group 0;" ::: "memory"); }
DEVINL void bulk_wait0_read() { asm volatile("cp.async.bulk.wait_group.read 0;" ::: "memory"); }
DEVINL void prefetch_tmap(const CUtensorMap* m) { asm volatile("prefetch.tensormap [%0];" ::"l"(m) : "memory"); }

DEVINL uint64_t make_desc(uint32_t addr, uint32_t lbo, uint32_t sbo, uint32_t swz) {
  return (uint64_t)((addr & 0x3FFFF) >> 4) | ((uint64_t)(lbo >> 4) << 16) | ((uint64_t)(sbo >> 4) << 32) | ((uint64_t)swz << 62);
}
DEVINL void wg_fence() { asm volatile("wgmma.fence.sync.aligned;" ::: "memory"); }
DEVINL void wg_commit() { asm volatile("wgmma.commit_group.sync.aligned;" ::: "memory"); }
template <int N> DEVINL void wg_wait() { asm volatile("wgmma.wait_group.sync.aligned %0;" ::"n"(N) : "memory"); }

DEVINL void mma16816(float (&d)[4], uint32_t a0, uint32_t a1, uint32_t a2, uint32_t a3, uint32_t b0, uint32_t b1) {
  asm volatile("mma.sync.aligned.m16n8k16.row.col.f32.bf16.bf16.f32 {%0,%1,%2,%3},{%4,%5,%6,%7},{%8,%9},{%0,%1,%2,%3};"
               : "+f"(d[0]), "+f"(d[1]), "+f"(d[2]), "+f"(d[3]) : "r"(a0), "r"(a1), "r"(a2), "r"(a3), "r"(b0), "r"(b1));
}
DEVINL void mma16816_z(float (&d)[4], uint32_t a0, uint32_t a1, uint32_t a2, uint32_t a3, uint32_t b0, uint32_t b1) {
  asm volatile("mma.sync.aligned.m16n8k16.row.col.f32.bf16.bf16.f32 {%0,%1,%2,%3},{%4,%5,%6,%7},{%8,%9},{%10,%10,%10,%10};"
               : "=f"(d[0]), "=f"(d[1]), "=f"(d[2]), "=f"(d[3]) : "r"(a0), "r"(a1), "r"(a2), "r"(a3), "r"(b0), "r"(b1), "f"(0.f));
}
DEVINL void mma1688(float (&d)[4], uint32_t a0, uint32_t a1, uint32_t b0) {
  asm volatile("mma.sync.aligned.m16n8k8.row.col.f32.bf16.bf16.f32 {%0,%1,%2,%3},{%4,%5},{%6},{%0,%1,%2,%3};"
               : "+f"(d[0]), "+f"(d[1]), "+f"(d[2]), "+f"(d[3]) : "r"(a0), "r"(a1), "r"(b0));
}
DEVINL void ldsm4(uint32_t& r0, uint32_t& r1, uint32_t& r2, uint32_t& r3, uint32_t a) {
  asm volatile("ldmatrix.sync.aligned.m8n8.x4.shared.b16 {%0,%1,%2,%3}, [%4];" : "=r"(r0), "=r"(r1), "=r"(r2), "=r"(r3) : "r"(a));
}
DEVINL void ldsm2(uint32_t& r0, uint32_t& r1, uint32_t a) {
  asm volatile("ldmatrix.sync.aligned.m8n8.x2.shared.b16 {%0,%1}, [%2];" : "=r"(r0), "=r"(r1) : "r"(a));
}
DEVINL void ldsm4t(uint32_t& r0, uint32_t& r1, uint32_t& r2, uint32_t& r3, uint32_t a) {
  asm volatile("ldmatrix.sync.aligned.m8n8.x4.trans.shared.b16 {%0,%1,%2,%3}, [%4];" : "=r"(r0), "=r"(r1), "=r"(r2), "=r"(r3) : "r"(a));
}
DEVINL void ldsm2t(uint32_t& r0, uint32_t& r1, uint32_t a) {
  asm volatile("ldmatrix.sync.aligned.m8n8.x2.trans.shared.b16 {%0,%1}, [%2];" : "=r"(r0), "=r"(r1) : "r"(a));
}
DEVINL void stsm4(uint32_t a, uint32_t r0, uint32_t r1, uint32_t r2, uint32_t r3) {
  asm volatile("stmatrix.sync.aligned.m8n8.x4.shared.b16 [%0], {%1,%2,%3,%4};" ::"r"(a), "r"(r0), "r"(r1), "r"(r2), "r"(r3) : "memory");
}
DEVINL void stsm2(uint32_t a, uint32_t r0, uint32_t r1) {
  asm volatile("stmatrix.sync.aligned.m8n8.x2.shared.b16 [%0], {%1,%2};" ::"r"(a), "r"(r0), "r"(r1) : "memory");
}
DEVINL void stsm4t(uint32_t a, uint32_t r0, uint32_t r1, uint32_t r2, uint32_t r3) {
  asm volatile("stmatrix.sync.aligned.m8n8.x4.trans.shared.b16 [%0], {%1,%2,%3,%4};" ::"r"(a), "r"(r0), "r"(r1), "r"(r2), "r"(r3) : "memory");
}
DEVINL uint32_t lds32(uint32_t a) { uint32_t v; asm volatile("ld.shared.u32 %0, [%1];" : "=r"(v) : "r"(a)); return v; }
DEVINL uint4 lds128(uint32_t a) {
  uint4 v; asm volatile("ld.shared.v4.u32 {%0,%1,%2,%3}, [%4];" : "=r"(v.x), "=r"(v.y), "=r"(v.z), "=r"(v.w) : "r"(a)); return v;
}
DEVINL void sts32(uint32_t a, uint32_t v) { asm volatile("st.shared.u32 [%0], %1;" ::"r"(a), "r"(v) : "memory"); }
DEVINL void sts128(uint32_t a, uint4 v) {
  asm volatile("st.shared.v4.u32 [%0], {%1,%2,%3,%4};" ::"r"(a), "r"(v.x), "r"(v.y), "r"(v.z), "r"(v.w) : "memory");
}
DEVINL uint4 ldg_nc(const void* p) {
  uint4 v; asm volatile("ld.global.nc.L1::no_allocate.v4.u32 {%0,%1,%2,%3}, [%4];" : "=r"(v.x), "=r"(v.y), "=r"(v.z), "=r"(v.w) : "l"(p)); return v;
}
DEVINL uint4 ldg_cg(const void* p) {
  uint4 v; asm volatile("ld.global.cg.v4.u32 {%0,%1,%2,%3}, [%4];" : "=r"(v.x), "=r"(v.y), "=r"(v.z), "=r"(v.w) : "l"(p) : "memory"); return v;
}
DEVINL void stg128(void* p, uint4 v) {
  asm volatile("st.global.v4.u32 [%0], {%1,%2,%3,%4};" ::"l"(p), "r"(v.x), "r"(v.y), "r"(v.z), "r"(v.w) : "memory");
}
DEVINL uint32_t pack_bf16(float lo, float hi) {
  uint32_t r; asm("cvt.rn.bf16x2.f32 %0, %1, %2;" : "=r"(r) : "f"(hi), "f"(lo)); return r;
}
DEVINL uint32_t hmul2(uint32_t a, uint32_t b) { uint32_t r; asm("mul.rn.bf16x2 %0, %1, %2;" : "=r"(r) : "r"(a), "r"(b)); return r; }
DEVINL uint32_t hadd2(uint32_t a, uint32_t b) { uint32_t r; asm("add.rn.bf16x2 %0, %1, %2;" : "=r"(r) : "r"(a), "r"(b)); return r; }
DEVINL float ex2(float x) { float r; asm("ex2.approx.ftz.f32 %0, %1;" : "=f"(r) : "f"(x)); return r; }

DEVINL void wgmma_n192(float (&d)[96], uint64_t da, uint64_t db, int scale_d) {
  asm volatile("{\n.reg .pred p;\nsetp.ne.b32 p, %98, 0;\n"
    "wgmma.mma_async.sync.aligned.m64n192k16.f32.bf16.bf16 "
    "{%0,%1,%2,%3,%4,%5,%6,%7,%8,%9,%10,%11,%12,%13,%14,%15,"
    "%16,%17,%18,%19,%20,%21,%22,%23,%24,%25,%26,%27,%28,%29,%30,%31,"
    "%32,%33,%34,%35,%36,%37,%38,%39,%40,%41,%42,%43,%44,%45,%46,%47,"
    "%48,%49,%50,%51,%52,%53,%54,%55,%56,%57,%58,%59,%60,%61,%62,%63,"
    "%64,%65,%66,%67,%68,%69,%70,%71,%72,%73,%74,%75,%76,%77,%78,%79,"
    "%80,%81,%82,%83,%84,%85,%86,%87,%88,%89,%90,%91,%92,%93,%94,%95}, "
    "%96, %97, p, 1, 1, 0, 1;\n}\n"
    : "+f"(d[0]), "+f"(d[1]), "+f"(d[2]), "+f"(d[3]), "+f"(d[4]), "+f"(d[5]), "+f"(d[6]), "+f"(d[7]),
      "+f"(d[8]), "+f"(d[9]), "+f"(d[10]), "+f"(d[11]), "+f"(d[12]), "+f"(d[13]), "+f"(d[14]), "+f"(d[15]),
      "+f"(d[16]), "+f"(d[17]), "+f"(d[18]), "+f"(d[19]), "+f"(d[20]), "+f"(d[21]), "+f"(d[22]), "+f"(d[23]),
      "+f"(d[24]), "+f"(d[25]), "+f"(d[26]), "+f"(d[27]), "+f"(d[28]), "+f"(d[29]), "+f"(d[30]), "+f"(d[31]),
      "+f"(d[32]), "+f"(d[33]), "+f"(d[34]), "+f"(d[35]), "+f"(d[36]), "+f"(d[37]), "+f"(d[38]), "+f"(d[39]),
      "+f"(d[40]), "+f"(d[41]), "+f"(d[42]), "+f"(d[43]), "+f"(d[44]), "+f"(d[45]), "+f"(d[46]), "+f"(d[47]),
      "+f"(d[48]), "+f"(d[49]), "+f"(d[50]), "+f"(d[51]), "+f"(d[52]), "+f"(d[53]), "+f"(d[54]), "+f"(d[55]),
      "+f"(d[56]), "+f"(d[57]), "+f"(d[58]), "+f"(d[59]), "+f"(d[60]), "+f"(d[61]), "+f"(d[62]), "+f"(d[63]),
      "+f"(d[64]), "+f"(d[65]), "+f"(d[66]), "+f"(d[67]), "+f"(d[68]), "+f"(d[69]), "+f"(d[70]), "+f"(d[71]),
      "+f"(d[72]), "+f"(d[73]), "+f"(d[74]), "+f"(d[75]), "+f"(d[76]), "+f"(d[77]), "+f"(d[78]), "+f"(d[79]),
      "+f"(d[80]), "+f"(d[81]), "+f"(d[82]), "+f"(d[83]), "+f"(d[84]), "+f"(d[85]), "+f"(d[86]), "+f"(d[87]),
      "+f"(d[88]), "+f"(d[89]), "+f"(d[90]), "+f"(d[91]), "+f"(d[92]), "+f"(d[93]), "+f"(d[94]), "+f"(d[95])
    : "l"(da), "l"(db), "r"(scale_d));
}

DEVINL void wgmma_n48(float (&d)[24], uint64_t da, uint64_t db, int scale_d) {
  asm volatile("{\n.reg .pred p;\nsetp.ne.b32 p, %26, 0;\n"
    "wgmma.mma_async.sync.aligned.m64n48k16.f32.bf16.bf16 "
    "{%0,%1,%2,%3,%4,%5,%6,%7,%8,%9,%10,%11,%12,%13,%14,%15,"
    "%16,%17,%18,%19,%20,%21,%22,%23}, "
    "%24, %25, p, 1, 1, 0, 1;\n}\n"
    : "+f"(d[0]), "+f"(d[1]), "+f"(d[2]), "+f"(d[3]), "+f"(d[4]), "+f"(d[5]), "+f"(d[6]), "+f"(d[7]),
      "+f"(d[8]), "+f"(d[9]), "+f"(d[10]), "+f"(d[11]), "+f"(d[12]), "+f"(d[13]), "+f"(d[14]), "+f"(d[15]),
      "+f"(d[16]), "+f"(d[17]), "+f"(d[18]), "+f"(d[19]), "+f"(d[20]), "+f"(d[21]), "+f"(d[22]), "+f"(d[23])
    : "l"(da), "l"(db), "r"(scale_d));
}

DEVINL void wgmma_n80(float (&d)[40], uint64_t da, uint64_t db, int scale_d) {
  asm volatile("{\n.reg .pred p;\nsetp.ne.b32 p, %42, 0;\n"
    "wgmma.mma_async.sync.aligned.m64n80k16.f32.bf16.bf16 "
    "{%0,%1,%2,%3,%4,%5,%6,%7,%8,%9,%10,%11,%12,%13,%14,%15,"
    "%16,%17,%18,%19,%20,%21,%22,%23,%24,%25,%26,%27,%28,%29,%30,%31,"
    "%32,%33,%34,%35,%36,%37,%38,%39}, "
    "%40, %41, p, 1, 1, 0, 1;\n}\n"
    : "+f"(d[0]), "+f"(d[1]), "+f"(d[2]), "+f"(d[3]), "+f"(d[4]), "+f"(d[5]), "+f"(d[6]), "+f"(d[7]),
      "+f"(d[8]), "+f"(d[9]), "+f"(d[10]), "+f"(d[11]), "+f"(d[12]), "+f"(d[13]), "+f"(d[14]), "+f"(d[15]),
      "+f"(d[16]), "+f"(d[17]), "+f"(d[18]), "+f"(d[19]), "+f"(d[20]), "+f"(d[21]), "+f"(d[22]), "+f"(d[23]),
      "+f"(d[24]), "+f"(d[25]), "+f"(d[26]), "+f"(d[27]), "+f"(d[28]), "+f"(d[29]), "+f"(d[30]), "+f"(d[31]),
      "+f"(d[32]), "+f"(d[33]), "+f"(d[34]), "+f"(d[35]), "+f"(d[36]), "+f"(d[37]), "+f"(d[38]), "+f"(d[39])
    : "l"(da), "l"(db), "r"(scale_d));
}

DEVINL void wgmma_qk_n64(float (&d)[32], uint32_t a0, uint32_t a1, uint32_t a2, uint32_t a3, uint64_t db, int scale_d) {
  asm volatile("{\n.reg .pred p;\nsetp.ne.b32 p, %37, 0;\n"
    "wgmma.mma_async.sync.aligned.m64n64k16.f32.bf16.bf16 "
    "{%0,%1,%2,%3,%4,%5,%6,%7,%8,%9,%10,%11,%12,%13,%14,%15,"
    "%16,%17,%18,%19,%20,%21,%22,%23,%24,%25,%26,%27,%28,%29,%30,%31}, "
    "{%32,%33,%34,%35}, %36, p, 1, 1, 0;\n}\n"
    : "+f"(d[0]), "+f"(d[1]), "+f"(d[2]), "+f"(d[3]), "+f"(d[4]), "+f"(d[5]), "+f"(d[6]), "+f"(d[7]),
      "+f"(d[8]), "+f"(d[9]), "+f"(d[10]), "+f"(d[11]), "+f"(d[12]), "+f"(d[13]), "+f"(d[14]), "+f"(d[15]),
      "+f"(d[16]), "+f"(d[17]), "+f"(d[18]), "+f"(d[19]), "+f"(d[20]), "+f"(d[21]), "+f"(d[22]), "+f"(d[23]),
      "+f"(d[24]), "+f"(d[25]), "+f"(d[26]), "+f"(d[27]), "+f"(d[28]), "+f"(d[29]), "+f"(d[30]), "+f"(d[31])
    : "r"(a0), "r"(a1), "r"(a2), "r"(a3), "l"(db), "r"(scale_d));
}

DEVINL void wgmma_pv_n24(float (&d)[12], uint32_t a0, uint32_t a1, uint32_t a2, uint32_t a3, uint64_t db, int scale_d) {
  asm volatile("{\n.reg .pred p;\nsetp.ne.b32 p, %17, 0;\n"
    "wgmma.mma_async.sync.aligned.m64n24k16.f32.bf16.bf16 "
    "{%0,%1,%2,%3,%4,%5,%6,%7,%8,%9,%10,%11}, "
    "{%12,%13,%14,%15}, %16, p, 1, 1, 1;\n}\n"
    : "+f"(d[0]), "+f"(d[1]), "+f"(d[2]), "+f"(d[3]), "+f"(d[4]), "+f"(d[5]), "+f"(d[6]), "+f"(d[7]),
      "+f"(d[8]), "+f"(d[9]), "+f"(d[10]), "+f"(d[11])
    : "r"(a0), "r"(a1), "r"(a2), "r"(a3), "l"(db), "r"(scale_d));
}

DEVINL void wgmma_qk_n64_z(float (&d)[32], uint32_t a0, uint32_t a1, uint32_t a2, uint32_t a3, uint64_t db) {
  asm volatile("{\n.reg .pred p;\nsetp.ne.b32 p, 0, 0;\n"
    "wgmma.mma_async.sync.aligned.m64n64k16.f32.bf16.bf16 "
    "{%0,%1,%2,%3,%4,%5,%6,%7,%8,%9,%10,%11,%12,%13,%14,%15,"
    "%16,%17,%18,%19,%20,%21,%22,%23,%24,%25,%26,%27,%28,%29,%30,%31}, "
    "{%32,%33,%34,%35}, %36, p, 1, 1, 0;\n}\n"
    : "=f"(d[0]), "=f"(d[1]), "=f"(d[2]), "=f"(d[3]), "=f"(d[4]), "=f"(d[5]), "=f"(d[6]), "=f"(d[7]),
      "=f"(d[8]), "=f"(d[9]), "=f"(d[10]), "=f"(d[11]), "=f"(d[12]), "=f"(d[13]), "=f"(d[14]), "=f"(d[15]),
      "=f"(d[16]), "=f"(d[17]), "=f"(d[18]), "=f"(d[19]), "=f"(d[20]), "=f"(d[21]), "=f"(d[22]), "=f"(d[23]),
      "=f"(d[24]), "=f"(d[25]), "=f"(d[26]), "=f"(d[27]), "=f"(d[28]), "=f"(d[29]), "=f"(d[30]), "=f"(d[31])
    : "r"(a0), "r"(a1), "r"(a2), "r"(a3), "l"(db));
}

DEVINL void wgmma_pv_n24_z(float (&d)[12], uint32_t a0, uint32_t a1, uint32_t a2, uint32_t a3, uint64_t db) {
  asm volatile("{\n.reg .pred p;\nsetp.ne.b32 p, 0, 0;\n"
    "wgmma.mma_async.sync.aligned.m64n24k16.f32.bf16.bf16 "
    "{%0,%1,%2,%3,%4,%5,%6,%7,%8,%9,%10,%11}, "
    "{%12,%13,%14,%15}, %16, p, 1, 1, 1;\n}\n"
    : "=f"(d[0]), "=f"(d[1]), "=f"(d[2]), "=f"(d[3]), "=f"(d[4]), "=f"(d[5]), "=f"(d[6]), "=f"(d[7]),
      "=f"(d[8]), "=f"(d[9]), "=f"(d[10]), "=f"(d[11])
    : "r"(a0), "r"(a1), "r"(a2), "r"(a3), "l"(db));
}

#define ATT_T(i) do {} while (0)
constexpr float SM_C = 0.22360679774997896f * 1.4426950408889634f;
constexpr float NEG_INF = -INFINITY;
constexpr int PLANE = 2048;
constexpr int PAIR = 11 * PLANE;
constexpr int SEG = 2 * PAIR;

template <int N> DEVINL void reg_fence(float (&d)[N]) {
#pragma unroll
  for (int i = 0; i < N; ++i) asm volatile("" : "+f"(d[i])::"memory");
}
DEVINL float ex2v(float x) { float r; asm volatile("ex2.approx.ftz.f32 %0, %1;" : "=f"(r) : "f"(x)); return r; }
DEVINL uint32_t bsel(uint32_t a, uint32_t b, uint32_t m) { return (a & m) | (b & ~m); }
DEVINL float fsel(float a, float b, uint32_t m) { return __uint_as_float(bsel(__float_as_uint(a), __float_as_uint(b), m)); }
DEVINL uint64_t kdesc(uint32_t lo) { return (uint64_t)lo | ((uint64_t)(128 >> 4) << 32); }
DEVINL uint64_t vdesc(uint32_t lo) { return (uint64_t)lo | ((uint64_t)(PLANE >> 4) << 32); }

DEVINL void mma_qk(float (&s)[32], const uint32_t (&a)[4], const uint32_t (&a8)[2], uint32_t kmain, uint32_t ktail) {
  wgmma_qk_n64_z(s, a[0], a[1], a[2], a[3], kdesc(kmain));
  wgmma_qk_n64(s, a8[0], a8[1], 0u, 0u, kdesc(ktail), 1);
}
template <bool FIRST>
DEVINL void mma_pv(float (&o)[12], const uint32_t (&p)[16], uint32_t v) {
  if (FIRST) wgmma_pv_n24_z(o, p[0], p[1], p[2], p[3], vdesc(v));
  else wgmma_pv_n24(o, p[0], p[1], p[2], p[3], vdesc(v), 1);
#pragma unroll
  for (int b = 1; b < 4; ++b) wgmma_pv_n24(o, p[4 * b], p[4 * b + 1], p[4 * b + 2], p[4 * b + 3], vdesc(v + b * 16), 1);
}
DEVINL void row_max(const float (&s)[32], float& x0o, float& x1o) {
  float x0 = fmaxf(s[0], s[1]), x1 = fmaxf(s[2], s[3]), y0 = fmaxf(s[4], s[5]), y1 = fmaxf(s[6], s[7]);
#pragma unroll
  for (int i = 2; i < 8; i += 2) {
    x0 = fmaxf(x0, fmaxf(s[4 * i], s[4 * i + 1]));
    x1 = fmaxf(x1, fmaxf(s[4 * i + 2], s[4 * i + 3]));
    y0 = fmaxf(y0, fmaxf(s[4 * i + 4], s[4 * i + 5]));
    y1 = fmaxf(y1, fmaxf(s[4 * i + 6], s[4 * i + 7]));
  }
  x0 = fmaxf(x0, y0); x1 = fmaxf(x1, y1);
  x0 = fmaxf(x0, __shfl_xor_sync(0xffffffffu, x0, 1));
  x1 = fmaxf(x1, __shfl_xor_sync(0xffffffffu, x1, 1));
  x0o = fmaxf(x0, __shfl_xor_sync(0xffffffffu, x0, 2));
  x1o = fmaxf(x1, __shfl_xor_sync(0xffffffffu, x1, 2));
}
template <int I0, int I1>
DEVINL void sm_exp(const float (&s)[32], uint32_t (&p)[16], float n0, float n1) {
#pragma unroll
  for (int i = I0; i < I1; ++i) {
    const float e0 = ex2v(fmaf(s[4 * i], SM_C, n0)), e1 = ex2v(fmaf(s[4 * i + 1], SM_C, n0));
    const float e2 = ex2v(fmaf(s[4 * i + 2], SM_C, n1)), e3 = ex2v(fmaf(s[4 * i + 3], SM_C, n1));
    p[2 * i] = pack_bf16(e0, e1);
    p[2 * i + 1] = pack_bf16(e2, e3);
  }
}
DEVINL void rescale(float (&o)[12], float al0, float al1) {
#pragma unroll
  for (int n = 0; n < 3; ++n) { o[4 * n] *= al0; o[4 * n + 1] *= al0; o[4 * n + 2] *= al1; o[4 * n + 3] *= al1; }
}
struct SoftmaxState { float m0, m1, n0, n1, al0, al1; };
DEVINL void next_max(SoftmaxState& st, float x0, float x1, bool valid) {
  x0 = fmaxf(valid ? x0 : NEG_INF, st.m0); x1 = fmaxf(valid ? x1 : NEG_INF, st.m1);
  const float c0 = -x0 * SM_C, c1 = -x1 * SM_C;
  st.al0 = ex2(fmaf(st.m0, SM_C, c0)); st.al1 = ex2(fmaf(st.m1, SM_C, c1));
  st.m0 = x0; st.m1 = x1;
  st.n0 = valid ? c0 : NEG_INF; st.n1 = valid ? c1 : NEG_INF;
}
template <bool RESC>
DEVINL void step(const float (&cur)[32], float (&nxt)[32], float (&o)[12], uint32_t (&p)[16], SoftmaxState& st, bool valid_nxt) {
  const float n0 = st.n0, n1 = st.n1;
  sm_exp<0, 3>(cur, p, n0, n1);
  wg_wait<0>();
  reg_fence(nxt);
  if (RESC) { reg_fence(o); rescale(o, st.al0, st.al1); }
  float x0, x1;
  row_max(nxt, x0, x1);
  sm_exp<3, 8>(cur, p, n0, n1);
  next_max(st, x0, x1, valid_nxt);
}

DEVINL void attn_all(uint32_t ring, uint32_t stg, uint32_t bars, int wq, int lane, int cmin) {
  const int wg = wq >> 2, w = wq & 3;
  const int g = lane >> 2, t = lane & 3, mi = lane >> 3, r = lane & 7;
  const uint32_t T0 = (2 * t > g) ? 0xFFFFFFFFu : 0u, T1 = (2 * t + 1 > g) ? 0xFFFFFFFFu : 0u;
  const uint32_t tri = (T0 & 0xFFFFu) | (T1 & 0xFFFF0000u);
  const uint32_t rowQ = stg + (16 * wq + r + 8 * (mi & 1)) * 160 + (mi >> 1) * 16;
  const uint32_t rowQ8 = stg + (16 * wq + (lane & 15)) * 160 + 32;
  constexpr uint32_t S16 = SEG >> 4, P16 = PLANE >> 4;
  const uint32_t aE = ((ring + wg * 1024) & 0x3FFFF) >> 4, aO = ((ring + wg * SEG + (wg ^ 1) * 1024) & 0x3FFFF) >> 4;
  const uint32_t kE = aE | (P16 << 16), kO = aO | (P16 << 16);
  const uint32_t vE = aE | ((128 >> 4) << 16), vO = aO | ((128 >> 4) << 16);
  uint32_t a[4], a8[2];
  float sX[32], sY[32], o[12];
  uint32_t pA[16], pB[16];
  mbar_wait(bars + 8 * B_HALO, 0);
  ldsm4(a[0], a[1], a[2], a[3], rowQ);
  ldsm2(a8[0], a8[1], rowQ8);
  if (t >= 2) { a8[0] = 0u; a8[1] = 0u; }
  wg_fence();
  mma_qk(sX, a, a8, kE, kE + 2 * P16);
  mma_qk(sY, a, a8, kE + 2 * S16, kE + 2 * S16 + 2 * P16);
  wg_commit();
#pragma unroll 1
  for (int h = 0; h < 4; ++h) {
    const int p = h >> 1, odd = h & 1;
    const uint32_t km = (p * 11 + odd * 3) * P16, kt = (p * 11 + 2) * P16, vp = (p * 11 + 5 + odd * 3) * P16;
    SoftmaxState st;
    ATT_T(0);
    wg_wait<0>();
    reg_fence(sX); reg_fence(sY);
    ATT_T(1);
    if (cmin > 0) {
#pragma unroll
      for (int i = 0; i < 32; ++i) sX[i] = NEG_INF;
    }
#pragma unroll
    for (int b = 0; b < 4; ++b) {
      const uint32_t gt = b > w ? 0xFFFFFFFFu : 0u, ge = b >= w ? 0xFFFFFFFFu : 0u, eq = ge & ~gt;
      const uint32_t e0 = gt | (eq & T0), e1 = gt | (eq & T1);
      sX[8 * b + 0] = fsel(sX[8 * b + 0], sY[8 * b + 0], e0);
      sX[8 * b + 1] = fsel(sX[8 * b + 1], sY[8 * b + 1], e1);
      sX[8 * b + 2] = fsel(sX[8 * b + 2], sY[8 * b + 2], gt);
      sX[8 * b + 3] = fsel(sX[8 * b + 3], sY[8 * b + 3], gt);
      sX[8 * b + 4] = fsel(sX[8 * b + 4], sY[8 * b + 4], ge);
      sX[8 * b + 5] = fsel(sX[8 * b + 5], sY[8 * b + 5], ge);
      sX[8 * b + 6] = fsel(sX[8 * b + 6], sY[8 * b + 6], e0);
      sX[8 * b + 7] = fsel(sX[8 * b + 7], sY[8 * b + 7], e1);
    }
    wg_fence();
    mma_qk(sY, a, a8, kO + km, kO + kt);
    wg_commit();
    ATT_T(2);
    row_max(sX, st.m0, st.m1);
    st.n0 = -st.m0 * SM_C; st.n1 = -st.m1 * SM_C;
    ATT_T(3);
    step<false>(sX, sY, o, pA, st, wg + 1 >= cmin);
    ATT_T(4);
#pragma unroll
    for (int b = 0; b < 4; ++b) {
      const uint32_t gt = b > w ? 0xFFFFFFFFu : 0u, ge = b >= w ? 0xFFFFFFFFu : 0u, eq = ge & ~gt;
      const uint32_t mt = gt | (eq & tri);
      pB[4 * b + 0] = pA[4 * b + 0] & ~mt; pA[4 * b + 0] &= mt;
      pB[4 * b + 1] = pA[4 * b + 1] & ~gt; pA[4 * b + 1] &= gt;
      pB[4 * b + 2] = pA[4 * b + 2] & ~ge; pA[4 * b + 2] &= ge;
      pB[4 * b + 3] = pA[4 * b + 3] & ~mt; pA[4 * b + 3] &= mt;
    }
    wg_fence();
    mma_qk(sX, a, a8, kE + S16 + km, kE + S16 + kt);
    mma_pv<true>(o, pA, vE + vp);
    mma_pv<false>(o, pB, vE + 2 * S16 + vp);
    wg_commit();
    ATT_T(5);
    step<true>(sY, sX, o, pB, st, wg + 2 >= cmin);
    ATT_T(6);
    wg_fence();
    mma_qk(sY, a, a8, kO + S16 + km, kO + S16 + kt);
    mma_pv<false>(o, pB, vO + vp);
    wg_commit();
    ATT_T(7);
    step<true>(sX, sY, o, pA, st, wg + 3 >= cmin);
    ATT_T(8);
    const int hn = h < 3 ? h + 1 : h, pn = hn >> 1, on = hn & 1;
    const uint32_t kmn = (pn * 11 + on * 3) * P16, ktn = (pn * 11 + 2) * P16;
    if (h == 1) mbar_wait(bars + 8 * (B_HALO + 1), 0);
    ldsm4(a[0], a[1], a[2], a[3], rowQ + pn * 80 + on * 48);
    ldsm2(a8[0], a8[1], rowQ8 + pn * 80);
    if ((t >= 2) != (on != 0)) { a8[0] = 0u; a8[1] = 0u; }
    wg_fence();
    mma_pv<false>(o, pA, vE + S16 + vp);
    mma_qk(sX, a, a8, kE + kmn, kE + ktn);
    wg_commit();
    ATT_T(9);
    sm_exp<0, 8>(sY, pB, st.n0, st.n1);
    ATT_T(10);
    wg_wait<0>();
    reg_fence(o); reg_fence(sX);
    rescale(o, st.al0, st.al1);
    wg_fence();
    mma_pv<false>(o, pB, vO + S16 + vp);
    wg_commit();
    wg_fence();
    mma_qk(sY, a, a8, kE + 2 * S16 + kmn, kE + 2 * S16 + ktn);
    wg_commit();
    ATT_T(11);
    wg_wait<1>();
    reg_fence(o);
    const int src = (lane & ~3) | (odd ? 0 : 2);
    const float i0 = __fdividef(1.f, __shfl_sync(0xffffffffu, o[8], src)), i1 = __fdividef(1.f, __shfl_sync(0xffffffffu, o[10], src));
    const uint32_t ob = stg + (16 * wq + g) * 160 + p * 80 + t * 4;
    const uint32_t om = ob + odd * 48;
    sts32(om, pack_bf16(o[0] * i0, o[1] * i0)); sts32(om + 1280, pack_bf16(o[2] * i1, o[3] * i1));
    sts32(om + 16, pack_bf16(o[4] * i0, o[5] * i0)); sts32(om + 16 + 1280, pack_bf16(o[6] * i1, o[7] * i1));
    if ((t >= 2) == (odd != 0)) { sts32(ob + 32, pack_bf16(o[8] * i0, o[9] * i0)); sts32(ob + 32 + 1280, pack_bf16(o[10] * i1, o[11] * i1)); }
    ATT_T(12);
  }
  wg_wait<0>();
  reg_fence(sX); reg_fence(sY);
  __syncwarp();
}

#define PRE_WAIT 0

struct Params {
  const uint16_t* q; const uint16_t* k; const uint16_t* v; const uint16_t* shift_k; const uint16_t* ssm_k;
  const uint16_t* ssm_D; uint16_t* out;
};

DEVINL unsigned* cnt(int i) { return &g_cnt[i * CS]; }

DEVINL void finish_role() {
  unsigned old = atomicAdd(cnt(C_DONE), 1u);
  if (old == 255u) {
    __threadfence();
    for (int i = 0; i < C_NUM; ++i) *cnt(i) = 0u;
    __threadfence();
  }
}

__global__ void __cluster_dims__(2, 1, 1) __launch_bounds__(512, 1)
h3_swa_fused_kernel(const __grid_constant__ CUtensorMap tmX, const __grid_constant__ CUtensorMap tmW128,
                    const __grid_constant__ CUtensorMap tmW32, const __grid_constant__ CUtensorMap tmO,
                    const __grid_constant__ CUtensorMap tmWo,
                    const __grid_constant__ CUtensorMap tmOut, const __grid_constant__ CUtensorMap tmKT,
                    const Params prm) {
  extern __shared__ uint8_t smem_raw[];
  const uint32_t sb = ((uint32_t)__cvta_generic_to_shared(smem_raw) + 1023u) & ~1023u;
  const uint32_t bars = sb + OFF_BAR;
  const int tid = threadIdx.x, warp = tid >> 5, lane = tid & 31, wg = tid >> 7;
  const int cta = blockIdx.x;
  const uint32_t rank = cta & 1;
  const int g8 = (cta >> 1) & 7, rp = cta >> 4;
  const int rb = 2 * rp + rank;
  const int rb2 = 2 * rp + (g8 & 1);
  const int c2 = 2 * (g8 >> 1) + rank;

  if (tid == 384) {
    prefetch_tmap(&tmX); prefetch_tmap(&tmW128); prefetch_tmap(&tmW32);
  }
  if (tid == 0) {
    PROF(0);
    for (int i = 0; i < NST1; ++i) { mbar_init(bars + 8 * (B_FULL1 + i), 1); mbar_init(bars + 8 * (B_EMPTY1 + i), 16); }
    mbar_init(bars + 8 * B_RINGFREE, 1);
    mbar_init(bars + 8 * B_HALO, 1); mbar_init(bars + 8 * (B_HALO + 1), 1);
    for (int i = 0; i < NST2; ++i) { mbar_init(bars + 8 * (B_FULL2 + i), 1); mbar_init(bars + 8 * (B_EMPTY2 + i), 16); }
    mbar_init(bars + 8 * B_U, 1);
    asm volatile("fence.mbarrier_init.release.cluster;" ::: "memory");
  }
  __syncthreads();
  asm volatile("barrier.cluster.arrive.relaxed.aligned;\nbarrier.cluster.wait.aligned;" ::: "memory");

  if (wg == 3) {
    asm volatile("setmaxnreg.dec.sync.aligned.u32 40;");
    if (warp == 12 && lane == 0) {
      PROF(15);
      for (int it = 0; it < 10; ++it) {
        const int s = it % NST1;
        if (it >= NST1) mbar_wait(bars + 8 * (B_EMPTY1 + s), ((it / NST1) - 1) & 1);
        PROF(44 + it);
        const uint32_t st = sb + s * ST1, fb = bars + 8 * (B_FULL1 + s);
        mbar_expect(fb, ST1);
        tma2d(st, &tmX, it * 64, rb * 128, fb);
        tma3d_mc(st + ST1_B128 + rank * 12288, &tmW128, g8 * 80, it * 64 + rank * 32, 0, fb);
        tma3d_mc(st + ST1_B32 + rank * 3072, &tmW32, g8 * 80 + 64, it * 64 + rank * 32, 0, fb);
      }
      PROF(1);
      mbar_wait(bars + 8 * B_RINGFREE, 0);
      if (rb >= 1) poll_ge(cnt(C_KV + g8 * 16 + rb - 1), 8);
      if (rb >= 2) poll_ge(cnt(C_KV + g8 * 16 + rb - 2), 8);
      PROF(2);
      for (int p = 0; p < 2; ++p) {
        const uint32_t hb = bars + 8 * (B_HALO + p);
        if (rb == 0) { mbar_arrive(hb); continue; }
        mbar_expect(hb, (rb >= 2 ? 2 : 1) * PAIR);
        bulk_load(sb + SEG + p * PAIR, g_kv + (size_t)(g8 * 16 + rb - 1) * (SEG / 2) + p * (PAIR / 2), PAIR, hb);
        if (rb >= 2) bulk_load(sb + p * PAIR, g_kv + (size_t)(g8 * 16 + rb - 2) * (SEG / 2) + p * (PAIR / 2), PAIR, hb);
      }
      for (int s = 0; s < NST2; ++s) {
        mbar_wait(bars + 8 * (B_EMPTY2 + s), 0);
        const uint32_t fb = bars + 8 * (B_FULL2 + s);
        mbar_expect(fb, ST2);
        tma3d(sb + s * ST2 + 16384, &tmWo, 0, s * 64, c2 * 5, fb);
      }
      PROF(3);
      poll_ge(cnt(C_O + rb2), 64);
      PROF(4);
      for (int s = 0; s < NST2; ++s)
        tma2d_mc(sb + s * ST2 + rank * 8192, &tmO, s * 64, rb2 * 128 + rank * 64, bars + 8 * (B_FULL2 + s));
      for (int it = NST2; it < 10; ++it) {
        const int s = it - NST2;
        mbar_wait(bars + 8 * (B_EMPTY2 + s), 1);
        const uint32_t fb = bars + 8 * (B_FULL2 + s);
        mbar_expect(fb, ST2);
        tma3d(sb + s * ST2 + 16384, &tmWo, 0, it * 64, c2 * 5, fb);
        tma2d_mc(sb + s * ST2 + rank * 8192, &tmO, it * 64, rb2 * 128 + rank * 64, fb);
      }
      finish_role();
    } else if (warp == 13 && lane == 0) {
      prefetch_tmap(&tmO); prefetch_tmap(&tmWo); prefetch_tmap(&tmOut);
    }
  } else if (wg == 2) {
    asm volatile("setmaxnreg.inc.sync.aligned.u32 136;");
    const int ct = tid - 256, wc = warp - 8;
    const int tau = cta & 15, jt = cta >> 4;
    const int t0 = tau * 128, c0 = jt * 80;
    const int mi = lane >> 3, r = lane & 7, g = lane >> 2, t = lane & 3;
    const uint32_t U = sb + OFF_U, F = sb + OFF_F;
    if (ct == 0) PROF(14);
    mbar_wait(bars + 8 * (B_FULL1 + PRE_WAIT), 0);
    for (int item = ct; item < 160; item += 128) {
      const int c = item % 10, seg = item / 10;
      const int ts = t0 + seg * 8, ch = c0 + c * 8;
      uint4 kk[11], vv[8], wv[4];
#pragma unroll
      for (int i = 0; i < 11; ++i) {
        const int row = ts - 3 + i;
        kk[i] = row >= 0 ? ldg_nc(prm.k + (size_t)row * DM + ch) : make_uint4(0, 0, 0, 0);
      }
#pragma unroll
      for (int i = 0; i < 8; ++i) vv[i] = ldg_nc(prm.v + (size_t)(ts + i) * DM + ch);
#pragma unroll
      for (int u = 0; u < 4; ++u) wv[u] = ldg_nc(prm.shift_k + (size_t)(ch + 2 * u) * 4);
      uint32_t W[4][4];
#pragma unroll
      for (int u = 0; u < 4; ++u) {
        W[0][u] = __byte_perm(wv[u].x, wv[u].z, 0x5410);
        W[1][u] = __byte_perm(wv[u].x, wv[u].z, 0x7632);
        W[2][u] = __byte_perm(wv[u].y, wv[u].w, 0x5410);
        W[3][u] = __byte_perm(wv[u].y, wv[u].w, 0x7632);
      }
#pragma unroll
      for (int i = 0; i < 8; ++i) {
        uint32_t res[4];
#pragma unroll
        for (int u = 0; u < 4; ++u) {
          const uint32_t k0 = (&kk[i].x)[u], k1 = (&kk[i + 1].x)[u], k2 = (&kk[i + 2].x)[u], k3 = (&kk[i + 3].x)[u];
          uint32_t acc = hadd2(hmul2(k0, W[3][u]), hmul2(k1, W[2][u]));
          acc = hadd2(acc, hmul2(k2, W[1][u]));
          acc = hadd2(acc, hmul2(k3, W[0][u]));
          res[u] = hmul2(acc, (&vv[i].x)[u]);
        }
        sts128(U + (seg * 8 + i) * 160 + c * 16, make_uint4(res[0], res[1], res[2], res[3]));
      }
    }
    if (ct == 0) PROF(5);
    if (ct == 127) PROF(6);
    named_sync(3, 128);
    if (ct == 0) PROF(7);
    for (int it = wc; it < 40; it += 4) {
      const int c = it % 10, rest = it / 10, h = rest & 1, iq = rest >> 1;
      const int tl = 16 * (4 * iq + (r >> 1)) + 15 - (8 * h + 2 * mi + (r & 1));
      uint4 v4;
      ldsm4t(v4.x, v4.y, v4.z, v4.w, U + tl * 160 + c * 16);
      sts128(F + (c * 8 + g) * 256 + h * 128 + (4 * iq + t) * 16, v4);
    }
    fence_async_smem();
    named_sync(3, 128);
    if (ct == 0) {
      tma3d_store(&tmKT, 64 * tau, 0, c0, F);
      bulk_commit();
      bulk_wait0();
      red_publish(cnt(C_PRE + jt));
      PROF(8);
    }
    if (ct >= 32 && ct < 112) {
      const int z = ct - 32;
      sts128(U + (z >> 4) * CH_U + ((z >> 3) & 1) * 2176 + (z & 7) * 16, make_uint4(0, 0, 0, 0));
    }
    named_sync(3, 128);
    {
      const int chb = cta * 5;
      uint4 fv[10]; uint32_t pv[10];
#pragma unroll
      for (int i = 0; i < 10; ++i) {
        const int cl = i >> 1, qq = ct + (i & 1) * 128;
        const uint16_t* src = prm.ssm_k + (size_t)(chb + cl) * SEQ + qq * 8;
        fv[i] = ldg_nc(src);
        pv[i] = qq > 0 ? (uint32_t)__ldg(src - 1) : 0u;
      }
#pragma unroll
      for (int i = 0; i < 10; ++i) {
        const int cl = i >> 1, qq = ct + (i & 1) * 128;
        const uint32_t a = F + cl * CH_F + 32 + qq * 16;
        sts128(a, fv[i]);
        sts128(a + 4160, make_uint4(__byte_perm(pv[i], fv[i].x, 0x5410), __byte_perm(fv[i].x, fv[i].y, 0x5432),
                                    __byte_perm(fv[i].y, fv[i].z, 0x5432), __byte_perm(fv[i].z, fv[i].w, 0x5432)));
      }
      if (ct < 20) sts128(F + (ct >> 2) * CH_F + ((ct >> 1) & 1) * 4160 + (ct & 1) * 16, make_uint4(0, 0, 0, 0));
    }
    if (ct == 0) {
      poll_ge(cnt(C_PRE + jt), 16);
      mbar_expect(bars + 8 * B_U, 5 * 4096);
      for (int i = 0; i < 10; ++i)
        bulk_load(U + (i >> 1) * CH_U + (i & 1) * 2176 + 128, g_kvT + (size_t)(cta * 5) * SEQ + i * 1024, 2048, bars + 8 * B_U);
      PROF(9);
    }
    named_sync(3, 128);
    mbar_wait(bars + 8 * B_U, 0);
    if (ct == 0) PROF(10);
#pragma unroll 1
    for (int pass = 0; pass < 2; ++pass) {
      const int cl = pass == 0 ? wc : 4;
      const int r0 = pass == 0 ? 0 : 2 * wc, r1 = pass == 0 ? 8 : 2 * wc + 2;
      const uint32_t Ub = U + cl * CH_U, Fb = F + cl * CH_F;
      const uint32_t laneU = Ub + (mi & 1) * 2176 + (8 + 8 * (mi >> 1) + r) * 16;
      const uint32_t laneF = (g & 1) ? Fb + 4160 + 2 * (17 - g + 2 * t) : Fb + 2 * (16 - g + 2 * t);
      float acc[16][4];
#pragma unroll
      for (int i = 0; i < 16; ++i) { acc[i][0] = 0.f; acc[i][1] = 0.f; acc[i][2] = 0.f; acc[i][3] = 0.f; }
#pragma unroll 1
      for (int rho = r0; rho < r1; ++rho) {
        uint32_t uf[16][2];
#pragma unroll
        for (int jj = 0; jj < 8; ++jj)
          ldsm4(uf[2 * jj][0], uf[2 * jj][1], uf[2 * jj + 1][0], uf[2 * jj + 1][1], laneU + jj * 256 - rho * 16);
        const uint32_t fb = laneF + 32 * rho;
#pragma unroll
        for (int mu = 0; mu < 16; ++mu) {
          const uint32_t a0 = lds32(fb + 256 * mu), a1 = lds32(fb + 256 * mu - 16), a2 = lds32(fb + 256 * mu + 16);
#pragma unroll
          for (int i = mu; i < 16; ++i) mma16816(acc[i], a0, a1, a2, a0, uf[i - mu][0], uf[i - mu][1]);
        }
      }
      const uint32_t dv = (uint32_t)__ldg(prm.ssm_D + cta * 5 + cl);
      const uint32_t D2 = dv | (dv << 16);
      if (pass == 0) {
        uint32_t res[8][4];
#pragma unroll
        for (int jj = 0; jj < 8; ++jj) {
          uint32_t u0, u1, u2, u3;
          ldsm4t(u0, u1, u2, u3, laneU + jj * 256);
          res[jj][0] = hadd2(pack_bf16(acc[2 * jj][0], acc[2 * jj][1]), hmul2(u0, D2));
          res[jj][1] = hadd2(pack_bf16(acc[2 * jj][2], acc[2 * jj][3]), hmul2(u1, D2));
          res[jj][2] = hadd2(pack_bf16(acc[2 * jj + 1][0], acc[2 * jj + 1][1]), hmul2(u2, D2));
          res[jj][3] = hadd2(pack_bf16(acc[2 * jj + 1][2], acc[2 * jj + 1][3]), hmul2(u3, D2));
        }
        __syncwarp();
#pragma unroll
        for (int jj = 0; jj < 8; ++jj)
          stsm4t(Ub + ((8 * (2 * jj + (mi >> 1)) + r) * 16 + 8 * (mi & 1)) * 2, res[jj][0], res[jj][1], res[jj][2], res[jj][3]);
        fence_async_smem();
        __syncwarp();
        if (lane == 0) {
          bulk_store(g_yT + (size_t)(cta * 5 + cl) * SEQ, Ub, 4096);
          bulk_commit();
          bulk_wait0();
          red_publish(cnt(C_Y + jt));
        }
        __syncwarp();
      } else {
        const uint32_t rbuf = F + wc * CH_F + lane * 16;
#pragma unroll
        for (int i = 0; i < 16; ++i)
          sts128(rbuf + i * 512, make_uint4(__float_as_uint(acc[i][0]), __float_as_uint(acc[i][1]),
                                            __float_as_uint(acc[i][2]), __float_as_uint(acc[i][3])));
        named_sync(3, 128);
        uint32_t res[2][4];
#pragma unroll
        for (int jj = 0; jj < 2; ++jj) {
          float sum[2][4];
#pragma unroll
          for (int hh = 0; hh < 2; ++hh) {
            const int tile = 4 * wc + 2 * jj + hh;
            sum[hh][0] = 0.f; sum[hh][1] = 0.f; sum[hh][2] = 0.f; sum[hh][3] = 0.f;
#pragma unroll
            for (int w = 0; w < 4; ++w) {
              const uint4 x = lds128(F + w * CH_F + lane * 16 + tile * 512);
              sum[hh][0] += __uint_as_float(x.x); sum[hh][1] += __uint_as_float(x.y);
              sum[hh][2] += __uint_as_float(x.z); sum[hh][3] += __uint_as_float(x.w);
            }
          }
          uint32_t u0, u1, u2, u3;
          ldsm4t(u0, u1, u2, u3, laneU + (2 * wc + jj) * 256);
          res[jj][0] = hadd2(pack_bf16(sum[0][0], sum[0][1]), hmul2(u0, D2));
          res[jj][1] = hadd2(pack_bf16(sum[0][2], sum[0][3]), hmul2(u1, D2));
          res[jj][2] = hadd2(pack_bf16(sum[1][0], sum[1][1]), hmul2(u2, D2));
          res[jj][3] = hadd2(pack_bf16(sum[1][2], sum[1][3]), hmul2(u3, D2));
        }
#pragma unroll
        for (int jj = 0; jj < 2; ++jj)
          stsm4t(U + ((8 * (2 * (2 * wc + jj) + (mi >> 1)) + r) * 16 + 8 * (mi & 1)) * 2, res[jj][0], res[jj][1], res[jj][2], res[jj][3]);
        fence_async_smem();
        named_sync(3, 128);
        if (ct == 0) {
          bulk_store(g_yT + (size_t)(cta * 5 + 4) * SEQ, U, 4096);
          bulk_commit();
          bulk_wait0();
          red_publish(cnt(C_Y + jt));
          PROF(11);
        }
      }
    }
    uint4 qv[10];
#pragma unroll
    for (int i = 0; i < 10; ++i) {
      const int idx = ct + 128 * i, row = idx / 10, c = idx % 10;
      qv[i] = ldg_nc(prm.q + (size_t)(t0 + row) * DM + c0 + c * 8);
    }
    if (ct == 0) { poll_ge(cnt(C_Y + jt), 80); finish_role(); PROF(12); }
    named_sync(3, 128);
    const uint32_t YT = sb + OFF_U, YN = sb + OFF_F + 1024;
#pragma unroll
    for (int i = 0; i < 10; ++i) {
      const int idx = ct + 128 * i, ch = idx >> 4, cq = idx & 15;
      sts128(YT + ch * 272 + cq * 16, ldg_cg(g_yT + (size_t)(c0 + ch) * SEQ + t0 + cq * 8));
    }
    named_sync(3, 128);
    for (int it = wc; it < 40; it += 4) {
      const int c = it % 10, tq = it / 10;
      uint32_t x0, x1, x2, x3;
      ldsm4t(x0, x1, x2, x3, YT + (8 * c + r) * 272 + (4 * tq + mi) * 16);
      const int s = (8 * (4 * tq + mi) + r) ^ 15;
      stsm4(YN + s * 176 + c * 16, x0, x1, x2, x3);
    }
    named_sync(3, 128);
#pragma unroll
    for (int i = 0; i < 10; ++i) {
      const int idx = ct + 128 * i, row = idx / 10, c = idx % 10;
      const uint4 y = lds128(YN + row * 176 + c * 16);
      stg128(prm.out + (size_t)(t0 + row) * (2 * DM) + c0 + c * 8,
             make_uint4(hmul2(qv[i].x, y.x), hmul2(qv[i].y, y.y), hmul2(qv[i].z, y.z), hmul2(qv[i].w, y.w)));
    }
    if (ct == 0) PROF(13);
  } else {
    asm volatile("setmaxnreg.inc.sync.aligned.u32 168;");
    const int wq = __shfl_sync(0xffffffffu, warp, 0);
    const int mi = lane >> 3, r = lane & 7;
    {
      float acc1[96], acc2[24];
#pragma unroll 1
      for (int it = 0; it < 10; ++it) {
        const int s = it % NST1;
        mbar_wait(bars + 8 * (B_FULL1 + s), (it / NST1) & 1);
        if (tid == 0) PROF(32 + it);
        const uint32_t st = sb + s * ST1;
        wg_fence();
#pragma unroll
        for (int kk = 0; kk < 4; ++kk) {
          const uint64_t da = make_desc(st + wg * 8192 + kk * 32, 16, 1024, 1);
          const uint64_t db1 = make_desc(st + ST1_B128 + (kk >> 1) * 12288 + (kk & 1) * 2048, 4096, 1024, 1);
          const uint64_t db2 = make_desc(st + ST1_B32 + (kk >> 1) * 3072 + (kk & 1) * 512, 1024, 256, 3);
          wgmma_n192(acc1, da, db1, (it | kk) != 0);
          wgmma_n48(acc2, da, db2, (it | kk) != 0);
        }
        wg_commit();
        wg_wait<0>();
        if (it + NST1 < 10 && lane < 2) mbar_arrive_cta(bars + 8 * (B_EMPTY1 + s), lane);
      }
      if (tid == 0) PROF(17);
      named_sync(1, 256);
      if (tid == 0) mbar_arrive(bars + 8 * B_RINGFREE);
      {
        const uint32_t rq = sb + OFF_STG + (16 * wq + 8 * (mi & 1) + r) * 160 + (mi >> 1) * 16;
#pragma unroll
        for (int tp = 0; tp < 4; ++tp)
          stsm4(rq + tp * 32, pack_bf16(acc1[8 * tp], acc1[8 * tp + 1]), pack_bf16(acc1[8 * tp + 2], acc1[8 * tp + 3]),
                pack_bf16(acc1[8 * tp + 4], acc1[8 * tp + 5]), pack_bf16(acc1[8 * tp + 6], acc1[8 * tp + 7]));
        stsm4(rq + 128, pack_bf16(acc2[0], acc2[1]), pack_bf16(acc2[2], acc2[3]), pack_bf16(acc2[4], acc2[5]), pack_bf16(acc2[6], acc2[7]));
      }
      const uint32_t rowa = sb + 2 * SEG + (16 * wq + 8 * (mi & 1) + r) * 16;
      const int t4 = lane & 3;
#pragma unroll
      for (int kv = 0; kv < 2; ++kv) {
#pragma unroll
        for (int tp = 0; tp < 5; ++tp) {
          uint32_t w[4];
#pragma unroll
          for (int hh = 0; hh < 2; ++hh) {
            const int tile = 2 * tp + hh;
            if (tile < 8) {
              const int o = 32 * (kv + 1) + 4 * tile;
              w[2 * hh] = pack_bf16(acc1[o], acc1[o + 1]); w[2 * hh + 1] = pack_bf16(acc1[o + 2], acc1[o + 3]);
            } else {
              const int o = 8 * (kv + 1) + 4 * (tile - 8);
              w[2 * hh] = pack_bf16(acc2[o], acc2[o + 1]); w[2 * hh + 1] = pack_bf16(acc2[o + 2], acc2[o + 3]);
            }
          }
          const int tA = 2 * tp, tB = 2 * tp + 1;
          const int plA = (tA / 5) * 11 + (kv ? 5 : 0) + tA % 5, plB = (tB / 5) * 11 + (kv ? 5 : 0) + tB % 5;
          if (kv == 1) {
            if (tA % 5 == 2 || tB % 5 == 2) {
              const int hh = (tA % 5 == 2) ? 0 : 1, pr = (hh ? tB : tA) / 5;
              const uint32_t x0 = w[2 * hh], x1 = w[2 * hh + 1];
              const uint32_t oneE = t4 == 2 ? 0x00003F80u : 0u, oneO = t4 == 0 ? 0x00003F80u : 0u;
              stsm2(sb + 2 * SEG + (pr * 11 + 10) * PLANE + (16 * wq + (lane & 15)) * 16, t4 >= 2 ? x0 : oneO, t4 >= 2 ? x1 : oneO);
              w[2 * hh] = t4 < 2 ? x0 : oneE; w[2 * hh + 1] = t4 < 2 ? x1 : oneE;
            }
          }
          stsm4(rowa + ((mi >> 1) ? plB : plA) * PLANE, w[0], w[1], w[2], w[3]);
        }
      }
    }
    __syncwarp();
    {
      uint16_t* dst = g_kv + (size_t)(g8 * 16 + rb) * (SEG / 2) + (16 * wq + (lane & 15)) * 8;
      const uint32_t src = sb + 2 * SEG + (16 * wq + (lane & 15)) * 16;
#pragma unroll
      for (int i = 0; i < 11; ++i) {
        const int pl = 2 * i + (lane >> 4);
        stg128(dst + pl * (PLANE / 2), lds128(src + pl * PLANE));
      }
      warp_publish(cnt(C_KV + g8 * 16 + rb), lane);
    }
    if (rb < 2) {
      const int nz = (2 - rb) * (SEG / 16);
#pragma unroll 1
      for (int i = tid; i < nz; i += 256) sts128(sb + i * 16, make_uint4(0, 0, 0, 0));
    }
    fence_async_smem();
    named_sync(2, 256);
    if (tid == 0) PROF(18);
    const uint32_t stg = sb + OFF_STG;
    attn_all(sb, stg, bars, wq, lane, rb >= 2 ? 0 : 4 - 2 * rb);
    if (tid == 0) PROF(19);
    if (lane < 2 * NST2) mbar_arrive_cta(bars + 8 * (B_EMPTY2 + (lane >> 1)), lane & 1);
    {
#pragma unroll
      for (int i = 0; i < 5; ++i) {
        const int idx = lane + 32 * i, row = idx / 10, c = idx % 10;
        stg128(g_o + (size_t)(rb * 128 + 16 * wq + row) * DM + g8 * 80 + c * 8, lds128(stg + (16 * wq + row) * 160 + c * 16));
      }
      warp_publish(cnt(C_O + rb), lane);
    }
    if (tid == 0) PROF(20);
    float acc[40];
#pragma unroll 1
    for (int it = 0; it < 10; ++it) {
      const int s = it % NST2;
      mbar_wait(bars + 8 * (B_FULL2 + s), (it / NST2) & 1);
      if (it == 0 && tid == 0) PROF(21);
      const uint32_t st = sb + s * ST2;
      wg_fence();
#pragma unroll
      for (int kk = 0; kk < 4; ++kk)
        wgmma_n80(acc, make_desc(st + wg * 8192 + kk * 32, 16, 1024, 1), make_desc(st + 16384 + kk * 512, 2048, 256, 3), (it | kk) != 0);
      wg_commit();
      wg_wait<0>();
      if (it + NST2 < 10 && lane < 2) mbar_arrive_cta(bars + 8 * (B_EMPTY2 + s), lane);
    }
    if (tid == 0) PROF(22);
    {
      const uint32_t rowa = stg + (16 * wq + 8 * (mi & 1) + r) * 160 + (mi >> 1) * 16;
#pragma unroll
      for (int tp = 0; tp < 5; ++tp)
        stsm4(rowa + tp * 32, pack_bf16(acc[8 * tp], acc[8 * tp + 1]), pack_bf16(acc[8 * tp + 2], acc[8 * tp + 3]),
              pack_bf16(acc[8 * tp + 4], acc[8 * tp + 5]), pack_bf16(acc[8 * tp + 6], acc[8 * tp + 7]));
      fence_async_smem();
      __syncwarp();
      if (lane == 0) {
        tma2d_store(&tmOut, DM + c2 * 80, rb2 * 128 + 16 * wq, stg + wq * 2560);
        bulk_commit();
        bulk_wait0_read();
      }
    }
    if (tid == 0) PROF(23);
  }
}

typedef CUresult (*EncodeFn)(CUtensorMap*, CUtensorMapDataType, cuuint32_t, void*, const cuuint64_t*, const cuuint64_t*,
                             const cuuint32_t*, const cuuint32_t*, CUtensorMapInterleave, CUtensorMapSwizzle,
                             CUtensorMapL2promotion, CUtensorMapFloatOOBfill);

CUtensorMap make_map(EncodeFn enc, const void* p, int rank, const cuuint64_t* dims, const cuuint64_t* strides,
                     const cuuint32_t* box, CUtensorMapSwizzle sw) {
  CUtensorMap m;
  const cuuint32_t es[3] = {1, 1, 1};
  enc(&m, CU_TENSOR_MAP_DATA_TYPE_BFLOAT16, rank, const_cast<void*>(p), dims, strides, box, es,
      CU_TENSOR_MAP_INTERLEAVE_NONE, sw, CU_TENSOR_MAP_L2_PROMOTION_L2_128B, CU_TENSOR_MAP_FLOAT_OOB_FILL_NONE);
  return m;
}

}

extern "C" void kernel_launch(void* const* d_in, const int* in_sizes, int n_in, void* d_out, int out_size) {
  (void)in_sizes; (void)n_in; (void)out_size;
  static EncodeFn enc = nullptr;
  static void* o_ptr = nullptr;
  static void* kt_ptr = nullptr;
  if (!enc) {
    void* fn = nullptr;
    cudaDriverEntryPointQueryResult qr;
    cudaGetDriverEntryPoint("cuTensorMapEncodeTiled", &fn, cudaEnableDefault, &qr);
    enc = (EncodeFn)fn;
    cudaGetSymbolAddress(&o_ptr, g_o);
    cudaGetSymbolAddress(&kt_ptr, g_kvT);
    cudaFuncSetAttribute(h3_swa_fused_kernel, cudaFuncAttributeMaxDynamicSharedMemorySize, SMEM_BYTES);
  }
  const void* x = d_in[6];
  const void* wqkv = d_in[7];
  const void* wo = d_in[8];
  CUtensorMap tmX, tmW128, tmW32, tmO, tmWo, tmOut, tmKT;
  { cuuint64_t d[2] = {640, 2048}, s[1] = {1280}; cuuint32_t b[2] = {64, 128};
    tmX = make_map(enc, x, 2, d, s, b, CU_TENSOR_MAP_SWIZZLE_128B); }
  { cuuint64_t d[3] = {640, 640, 3}, s[2] = {3840, 1280}; cuuint32_t b[3] = {64, 32, 3};
    tmW128 = make_map(enc, wqkv, 3, d, s, b, CU_TENSOR_MAP_SWIZZLE_128B); }
  { cuuint64_t d[3] = {640, 640, 3}, s[2] = {3840, 1280}; cuuint32_t b[3] = {16, 32, 3};
    tmW32 = make_map(enc, wqkv, 3, d, s, b, CU_TENSOR_MAP_SWIZZLE_32B); }
  { cuuint64_t d[2] = {640, 2048}, s[1] = {1280}; cuuint32_t b[2] = {64, 64};
    tmO = make_map(enc, o_ptr, 2, d, s, b, CU_TENSOR_MAP_SWIZZLE_128B); }
  { cuuint64_t d[3] = {16, 640, 40}, s[2] = {1280, 32}; cuuint32_t b[3] = {16, 64, 5};
    tmWo = make_map(enc, wo, 3, d, s, b, CU_TENSOR_MAP_SWIZZLE_32B); }
  { cuuint64_t d[2] = {1280, 2048}, s[1] = {2560}; cuuint32_t b[2] = {80, 16};
    tmOut = make_map(enc, d_out, 2, d, s, b, CU_TENSOR_MAP_SWIZZLE_NONE); }
  { cuuint64_t d[3] = {1024, 2, 640}, s[2] = {2048, 4096}; cuuint32_t b[3] = {64, 2, 80};
    tmKT = make_map(enc, kt_ptr, 3, d, s, b, CU_TENSOR_MAP_SWIZZLE_NONE); }
  Params prm;
  prm.q = (const uint16_t*)d_in[0]; prm.k = (const uint16_t*)d_in[1]; prm.v = (const uint16_t*)d_in[2];
  prm.shift_k = (const uint16_t*)d_in[3]; prm.ssm_k = (const uint16_t*)d_in[4]; prm.ssm_D = (const uint16_t*)d_in[5];
  prm.out = (uint16_t*)d_out;
  h3_swa_fused_kernel<<<128, 512, SMEM_BYTES>>>(tmX, tmW128, tmW32, tmO, tmWo, tmOut, tmKT, prm);
}
```

```cpp
#include <cuda_runtime.h>
#include <cuda.h>
#include <cuda_bf16.h>
#include <stdint.h>

#define DEVINL __device__ __forceinline__

namespace {

constexpr int SEQ = 2048;
constexpr int DM = 640;

constexpr int ST1 = 47104;
constexpr int ST1_B128 = 16384;
constexpr int ST1_B32 = 40960;
constexpr int NST1 = 3;
constexpr int ST2 = 33280;
constexpr int NST2 = 4;
constexpr int OFF_CONV = NST1 * ST1;
constexpr int CH_U = 4352;
constexpr int CH_F = 8320;
constexpr int OFF_U = OFF_CONV;
constexpr int OFF_F = OFF_CONV + 5 * CH_U;
constexpr int OFF_STG = OFF_F + 5 * CH_F;
constexpr int OFF_BAR = OFF_STG + 20480;
constexpr int SMEM_BYTES = OFF_BAR + 256 + 1024;

constexpr int B_FULL1 = 0, B_EMPTY1 = 3, B_RINGFREE = 6, B_HALO = 7, B_FULL2 = 9, B_EMPTY2 = 13, B_U = 17, B_KVST = 18,
              B_OST = 19, B_PRE = 21, B_KTST = 22, B_YST = 23, B_STGFREE = 25;

__device__ __align__(1024) uint16_t g_kv[8 * 16 * 22 * 1024];
__device__ __align__(1024) uint16_t g_o[SEQ * DM];
__device__ __align__(1024) uint16_t g_kvT[DM * SEQ];
__device__ __align__(1024) uint16_t g_yT[DM * SEQ];
constexpr int CS = 32;
constexpr int C_KV = 0, C_O = 256, C_PRE = 288, C_Y = 296, C_DONE = 304, C_NUM = 305;
__device__ unsigned g_cnt[C_NUM * CS];
__device__ unsigned g_err;
#define PROF(slot) do {} while (0)

DEVINL void mbar_init(uint32_t a, uint32_t c) { asm volatile("mbarrier.init.shared::cta.b64 [%0], %1;" ::"r"(a), "r"(c)); }
DEVINL void mbar_expect(uint32_t a, uint32_t b) {
  asm volatile("mbarrier.arrive.expect_tx.shared::cta.b64 _, [%0], %1;" ::"r"(a), "r"(b) : "memory");
}
DEVINL void mbar_arrive(uint32_t a) { asm volatile("mbarrier.arrive.shared::cta.b64 _, [%0];" ::"r"(a) : "memory"); }
DEVINL void mbar_arrive_cta(uint32_t a, uint32_t cta) {
  asm volatile("{\n.reg .b32 ra;\nmapa.shared::cluster.u32 ra, %0, %1;\nmbarrier.arrive.shared::cluster.b64 _, [ra];\n}"
               ::"r"(a), "r"(cta) : "memory");
}
DEVINL bool mbar_try(uint32_t a, uint32_t p) {
  uint32_t ok;
  asm volatile("{\n.reg .pred P;\nmbarrier.try_wait.parity.shared::cta.b64 P, [%1], %2;\nselp.u32 %0, 1, 0, P;\n}"
               : "=r"(ok) : "r"(a), "r"(p) : "memory");
  return ok;
}
DEVINL void mbar_wait(uint32_t a, uint32_t p) {
  if (mbar_try(a, p)) return;
  int n = 0;
  while (!mbar_try(a, p)) {
    if (++n > (1 << 18)) { g_err = 1; break; }
  }
}
DEVINL void poll_ge(const unsigned* p, unsigned target) {
  int n = 0;
  while (true) {
    unsigned v;
    asm volatile("ld.relaxed.gpu.global.u32 %0, [%1];" : "=r"(v) : "l"(p) : "memory");
    if (v >= target) break;
    if (++n > (1 << 20)) { g_err = 2; break; }
  }
}
DEVINL void red_publish(unsigned* p, unsigned n = 1) { asm volatile("red.release.gpu.global.add.u32 [%0], %1;" ::"l"(p), "r"(n) : "memory"); }
DEVINL void fence_async_smem() { asm volatile("fence.proxy.async.shared::cta;" ::: "memory"); }
DEVINL void named_sync(int id, int n) { asm volatile("bar.sync %0, %1;" ::"r"(id), "r"(n) : "memory"); }
DEVINL void named_arrive(int id, int n) { asm volatile("bar.arrive %0, %1;" ::"r"(id), "r"(n) : "memory"); }

DEVINL void tma2d(uint32_t dst, const CUtensorMap* m, int c0, int c1, uint32_t bar) {
  asm volatile("cp.async.bulk.tensor.2d.shared::cluster.global.mbarrier::complete_tx::bytes [%0], [%1, {%3, %4}], [%2];"
               ::"r"(dst), "l"(m), "r"(bar), "r"(c0), "r"(c1) : "memory");
}
DEVINL void tma2d_mc(uint32_t dst, const CUtensorMap* m, int c0, int c1, uint32_t bar) {
  asm volatile("cp.async.bulk.tensor.2d.shared::cluster.global.mbarrier::complete_tx::bytes.multicast::cluster [%0], [%1, {%3, %4}], [%2], %5;"
               ::"r"(dst), "l"(m), "r"(bar), "r"(c0), "r"(c1), "h"((uint16_t)3) : "memory");
}
DEVINL void tma3d(uint32_t dst, const CUtensorMap* m, int c0, int c1, int c2, uint32_t bar) {
  asm volatile("cp.async.bulk.tensor.3d.shared::cluster.global.mbarrier::complete_tx::bytes [%0], [%1, {%3, %4, %5}], [%2];"
               ::"r"(dst), "l"(m), "r"(bar), "r"(c0), "r"(c1), "r"(c2) : "memory");
}
DEVINL void tma3d_mc(uint32_t dst, const CUtensorMap* m, int c0, int c1, int c2, uint32_t bar) {
  asm volatile("cp.async.bulk.tensor.3d.shared::cluster.global.mbarrier::complete_tx::bytes.multicast::cluster [%0], [%1, {%3, %4, %5}], [%2], %6;"
               ::"r"(dst), "l"(m), "r"(bar), "r"(c0), "r"(c1), "r"(c2), "h"((uint16_t)3) : "memory");
}
DEVINL void tma2d_store(const CUtensorMap* m, int c0, int c1, uint32_t src) {
  asm volatile("cp.async.bulk.tensor.2d.global.shared::cta.bulk_group [%0, {%2, %3}], [%1];"
               ::"l"(m), "r"(src), "r"(c0), "r"(c1) : "memory");
}
DEVINL void tma3d_store(const CUtensorMap* m, int c0, int c1, int c2, uint32_t src) {
  asm volatile("cp.async.bulk.tensor.3d.global.shared::cta.bulk_group [%0, {%2, %3, %4}], [%1];"
               ::"l"(m), "r"(src), "r"(c0), "r"(c1), "r"(c2) : "memory");
}
DEVINL void bulk_load(uint32_t dst, const void* src, uint32_t bytes, uint32_t bar) {
  asm volatile("cp.async.bulk.shared::cluster.global.mbarrier::complete_tx::bytes [%0], [%1], %2, [%3];"
               ::"r"(dst), "l"(src), "r"(bytes), "r"(bar) : "memory");
}
DEVINL void bulk_load_mc(uint32_t dst, const void* src, uint32_t bytes, uint32_t bar) {
  asm volatile("cp.async.bulk.shared::cluster.global.mbarrier::complete_tx::bytes.multicast::cluster [%0], [%1], %2, [%3], %4;"
               ::"r"(dst), "l"(src), "r"(bytes), "r"(bar), "h"((uint16_t)3) : "memory");
}
DEVINL void tma5d(uint32_t dst, const CUtensorMap* m, int c0, int c1, int c2, int c3, int c4, uint32_t bar) {
  asm volatile("cp.async.bulk.tensor.5d.shared::cluster.global.mbarrier::complete_tx::bytes [%0], [%1, {%3, %4, %5, %6, %7}], [%2];"
               ::"r"(dst), "l"(m), "r"(bar), "r"(c0), "r"(c1), "r"(c2), "r"(c3), "r"(c4) : "memory");
}
DEVINL void prefetch_l2(const void* p, uint32_t bytes) {
  asm volatile("cp.async.bulk.prefetch.L2.global [%0], %1;" ::"l"(p), "r"(bytes) : "memory");
}
template <int N> DEVINL void bulk_wait() { asm volatile("cp.async.bulk.wait_group %0;" ::"n"(N) : "memory"); }
DEVINL void bulk_store(void* dst, uint32_t src, uint32_t bytes) {
  asm volatile("cp.async.bulk.global.shared::cta.bulk_group [%0], [%1], %2;" ::"l"(dst), "r"(src), "r"(bytes) : "memory");
}
DEVINL void bulk_commit() { asm volatile("cp.async.bulk.commit_group;" ::: "memory"); }
DEVINL void bulk_wait0() { asm volatile("cp.async.bulk.wait_group 0;" ::: "memory"); }
DEVINL void bulk_wait0_read() { asm volatile("cp.async.bulk.wait_group.read 0;" ::: "memory"); }
DEVINL void prefetch_tmap(const CUtensorMap* m) { asm volatile("prefetch.tensormap [%0];" ::"l"(m) : "memory"); }

DEVINL uint64_t make_desc(uint32_t addr, uint32_t lbo, uint32_t sbo, uint32_t swz) {
  return (uint64_t)((addr & 0x3FFFF) >> 4) | ((uint64_t)(lbo >> 4) << 16) | ((uint64_t)(sbo >> 4) << 32) | ((uint64_t)swz << 62);
}
DEVINL void wg_fence() { asm volatile("wgmma.fence.sync.aligned;" ::: "memory"); }
DEVINL void wg_commit() { asm volatile("wgmma.commit_group.sync.aligned;" ::: "memory"); }
template <int N> DEVINL void wg_wait() { asm volatile("wgmma.wait_group.sync.aligned %0;" ::"n"(N) : "memory"); }

DEVINL void mma16816(float (&d)[4], uint32_t a0, uint32_t a1, uint32_t a2, uint32_t a3, uint32_t b0, uint32_t b1) {
  asm volatile("mma.sync.aligned.m16n8k16.row.col.f32.bf16.bf16.f32 {%0,%1,%2,%3},{%4,%5,%6,%7},{%8,%9},{%0,%1,%2,%3};"
               : "+f"(d[0]), "+f"(d[1]), "+f"(d[2]), "+f"(d[3]) : "r"(a0), "r"(a1), "r"(a2), "r"(a3), "r"(b0), "r"(b1));
}
DEVINL void mma16816_z(float (&d)[4], uint32_t a0, uint32_t a1, uint32_t a2, uint32_t a3, uint32_t b0, uint32_t b1) {
  asm volatile("mma.sync.aligned.m16n8k16.row.col.f32.bf16.bf16.f32 {%0,%1,%2,%3},{%4,%5,%6,%7},{%8,%9},{%10,%10,%10,%10};"
               : "=f"(d[0]), "=f"(d[1]), "=f"(d[2]), "=f"(d[3]) : "r"(a0), "r"(a1), "r"(a2), "r"(a3), "r"(b0), "r"(b1), "f"(0.f));
}
DEVINL void mma1688(float (&d)[4], uint32_t a0, uint32_t a1, uint32_t b0) {
  asm volatile("mma.sync.aligned.m16n8k8.row.col.f32.bf16.bf16.f32 {%0,%1,%2,%3},{%4,%5},{%6},{%0,%1,%2,%3};"
               : "+f"(d[0]), "+f"(d[1]), "+f"(d[2]), "+f"(d[3]) : "r"(a0), "r"(a1), "r"(b0));
}
DEVINL void ldsm4(uint32_t& r0, uint32_t& r1, uint32_t& r2, uint32_t& r3, uint32_t a) {
  asm volatile("ldmatrix.sync.aligned.m8n8.x4.shared.b16 {%0,%1,%2,%3}, [%4];" : "=r"(r0), "=r"(r1), "=r"(r2), "=r"(r3) : "r"(a));
}
DEVINL void ldsm2(uint32_t& r0, uint32_t& r1, uint32_t a) {
  asm volatile("ldmatrix.sync.aligned.m8n8.x2.shared.b16 {%0,%1}, [%2];" : "=r"(r0), "=r"(r1) : "r"(a));
}
DEVINL void ldsm4t(uint32_t& r0, uint32_t& r1, uint32_t& r2, uint32_t& r3, uint32_t a) {
  asm volatile("ldmatrix.sync.aligned.m8n8.x4.trans.shared.b16 {%0,%1,%2,%3}, [%4];" : "=r"(r0), "=r"(r1), "=r"(r2), "=r"(r3) : "r"(a));
}
DEVINL void ldsm2t(uint32_t& r0, uint32_t& r1, uint32_t a) {
  asm volatile("ldmatrix.sync.aligned.m8n8.x2.trans.shared.b16 {%0,%1}, [%2];" : "=r"(r0), "=r"(r1) : "r"(a));
}
DEVINL void stsm4(uint32_t a, uint32_t r0, uint32_t r1, uint32_t r2, uint32_t r3) {
  asm volatile("stmatrix.sync.aligned.m8n8.x4.shared.b16 [%0], {%1,%2,%3,%4};" ::"r"(a), "r"(r0), "r"(r1), "r"(r2), "r"(r3) : "memory");
}
DEVINL void stsm2(uint32_t a, uint32_t r0, uint32_t r1) {
  asm volatile("stmatrix.sync.aligned.m8n8.x2.shared.b16 [%0], {%1,%2};" ::"r"(a), "r"(r0), "r"(r1) : "memory");
}
DEVINL void stsm4t(uint32_t a, uint32_t r0, uint32_t r1, uint32_t r2, uint32_t r3) {
  asm volatile("stmatrix.sync.aligned.m8n8.x4.trans.shared.b16 [%0], {%1,%2,%3,%4};" ::"r"(a), "r"(r0), "r"(r1), "r"(r2), "r"(r3) : "memory");
}
DEVINL uint32_t lds32(uint32_t a) { uint32_t v; asm volatile("ld.shared.u32 %0, [%1];" : "=r"(v) : "r"(a)); return v; }
DEVINL uint4 lds128(uint32_t a) {
  uint4 v; asm volatile("ld.shared.v4.u32 {%0,%1,%2,%3}, [%4];" : "=r"(v.x), "=r"(v.y), "=r"(v.z), "=r"(v.w) : "r"(a)); return v;
}
DEVINL void sts32(uint32_t a, uint32_t v) { asm volatile("st.shared.u32 [%0], %1;" ::"r"(a), "r"(v) : "memory"); }
DEVINL void sts128(uint32_t a, uint4 v) {
  asm volatile("st.shared.v4.u32 [%0], {%1,%2,%3,%4};" ::"r"(a), "r"(v.x), "r"(v.y), "r"(v.z), "r"(v.w) : "memory");
}
DEVINL uint4 ldg_nc(const void* p) {
  uint4 v; asm volatile("ld.global.nc.L1::no_allocate.v4.u32 {%0,%1,%2,%3}, [%4];" : "=r"(v.x), "=r"(v.y), "=r"(v.z), "=r"(v.w) : "l"(p)); return v;
}
DEVINL uint4 ldg_cg(const void* p) {
  uint4 v; asm volatile("ld.global.cg.v4.u32 {%0,%1,%2,%3}, [%4];" : "=r"(v.x), "=r"(v.y), "=r"(v.z), "=r"(v.w) : "l"(p) : "memory"); return v;
}
DEVINL void stg128(void* p, uint4 v) {
  asm volatile("st.global.v4.u32 [%0], {%1,%2,%3,%4};" ::"l"(p), "r"(v.x), "r"(v.y), "r"(v.z), "r"(v.w) : "memory");
}
DEVINL uint32_t pack_bf16(float lo, float hi) {
  uint32_t r; asm("cvt.rn.bf16x2.f32 %0, %1, %2;" : "=r"(r) : "f"(hi), "f"(lo)); return r;
}
DEVINL uint32_t hmul2(uint32_t a, uint32_t b) { uint32_t r; asm("mul.rn.bf16x2 %0, %1, %2;" : "=r"(r) : "r"(a), "r"(b)); return r; }
DEVINL uint32_t hadd2(uint32_t a, uint32_t b) { uint32_t r; asm("add.rn.bf16x2 %0, %1, %2;" : "=r"(r) : "r"(a), "r"(b)); return r; }
DEVINL float ex2(float x) { float r; asm("ex2.approx.ftz.f32 %0, %1;" : "=f"(r) : "f"(x)); return r; }

DEVINL void wgmma_n192(float (&d)[96], uint64_t da, uint64_t db, int scale_d) {
  asm volatile("{\n.reg .pred p;\nsetp.ne.b32 p, %98, 0;\n"
    "wgmma.mma_async.sync.aligned.m64n192k16.f32.bf16.bf16 "
    "{%0,%1,%2,%3,%4,%5,%6,%7,%8,%9,%10,%11,%12,%13,%14,%15,"
    "%16,%17,%18,%19,%20,%21,%22,%23,%24,%25,%26,%27,%28,%29,%30,%31,"
    "%32,%33,%34,%35,%36,%37,%38,%39,%40,%41,%42,%43,%44,%45,%46,%47,"
    "%48,%49,%50,%51,%52,%53,%54,%55,%56,%57,%58,%59,%60,%61,%62,%63,"
    "%64,%65,%66,%67,%68,%69,%70,%71,%72,%73,%74,%75,%76,%77,%78,%79,"
    "%80,%81,%82,%83,%84,%85,%86,%87,%88,%89,%90,%91,%92,%93,%94,%95}, "
    "%96, %97, p, 1, 1, 0, 1;\n}\n"
    : "+f"(d[0]), "+f"(d[1]), "+f"(d[2]), "+f"(d[3]), "+f"(d[4]), "+f"(d[5]), "+f"(d[6]), "+f"(d[7]),
      "+f"(d[8]), "+f"(d[9]), "+f"(d[10]), "+f"(d[11]), "+f"(d[12]), "+f"(d[13]), "+f"(d[14]), "+f"(d[15]),
      "+f"(d[16]), "+f"(d[17]), "+f"(d[18]), "+f"(d[19]), "+f"(d[20]), "+f"(d[21]), "+f"(d[22]), "+f"(d[23]),
      "+f"(d[24]), "+f"(d[25]), "+f"(d[26]), "+f"(d[27]), "+f"(d[28]), "+f"(d[29]), "+f"(d[30]), "+f"(d[31]),
      "+f"(d[32]), "+f"(d[33]), "+f"(d[34]), "+f"(d[35]), "+f"(d[36]), "+f"(d[37]), "+f"(d[38]), "+f"(d[39]),
      "+f"(d[40]), "+f"(d[41]), "+f"(d[42]), "+f"(d[43]), "+f"(d[44]), "+f"(d[45]), "+f"(d[46]), "+f"(d[47]),
      "+f"(d[48]), "+f"(d[49]), "+f"(d[50]), "+f"(d[51]), "+f"(d[52]), "+f"(d[53]), "+f"(d[54]), "+f"(d[55]),
      "+f"(d[56]), "+f"(d[57]), "+f"(d[58]), "+f"(d[59]), "+f"(d[60]), "+f"(d[61]), "+f"(d[62]), "+f"(d[63]),
      "+f"(d[64]), "+f"(d[65]), "+f"(d[66]), "+f"(d[67]), "+f"(d[68]), "+f"(d[69]), "+f"(d[70]), "+f"(d[71]),
      "+f"(d[72]), "+f"(d[73]), "+f"(d[74]), "+f"(d[75]), "+f"(d[76]), "+f"(d[77]), "+f"(d[78]), "+f"(d[79]),
      "+f"(d[80]), "+f"(d[81]), "+f"(d[82]), "+f"(d[83]), "+f"(d[84]), "+f"(d[85]), "+f"(d[86]), "+f"(d[87]),
      "+f"(d[88]), "+f"(d[89]), "+f"(d[90]), "+f"(d[91]), "+f"(d[92]), "+f"(d[93]), "+f"(d[94]), "+f"(d[95])
    : "l"(da), "l"(db), "r"(scale_d));
}

DEVINL void wgmma_n48(float (&d)[24], uint64_t da, uint64_t db, int scale_d) {
  asm volatile("{\n.reg .pred p;\nsetp.ne.b32 p, %26, 0;\n"
    "wgmma.mma_async.sync.aligned.m64n48k16.f32.bf16.bf16 "
    "{%0,%1,%2,%3,%4,%5,%6,%7,%8,%9,%10,%11,%12,%13,%14,%15,"
    "%16,%17,%18,%19,%20,%21,%22,%23}, "
    "%24, %25, p, 1, 1, 0, 1;\n}\n"
    : "+f"(d[0]), "+f"(d[1]), "+f"(d[2]), "+f"(d[3]), "+f"(d[4]), "+f"(d[5]), "+f"(d[6]), "+f"(d[7]),
      "+f"(d[8]), "+f"(d[9]), "+f"(d[10]), "+f"(d[11]), "+f"(d[12]), "+f"(d[13]), "+f"(d[14]), "+f"(d[15]),
      "+f"(d[16]), "+f"(d[17]), "+f"(d[18]), "+f"(d[19]), "+f"(d[20]), "+f"(d[21]), "+f"(d[22]), "+f"(d[23])
    : "l"(da), "l"(db), "r"(scale_d));
}

DEVINL void wgmma_n80(float (&d)[40], uint64_t da, uint64_t db, int scale_d) {
  asm volatile("{\n.reg .pred p;\nsetp.ne.b32 p, %42, 0;\n"
    "wgmma.mma_async.sync.aligned.m64n80k16.f32.bf16.bf16 "
    "{%0,%1,%2,%3,%4,%5,%6,%7,%8,%9,%10,%11,%12,%13,%14,%15,"
    "%16,%17,%18,%19,%20,%21,%22,%23,%24,%25,%26,%27,%28,%29,%30,%31,"
    "%32,%33,%34,%35,%36,%37,%38,%39}, "
    "%40, %41, p, 1, 1, 0, 1;\n}\n"
    : "+f"(d[0]), "+f"(d[1]), "+f"(d[2]), "+f"(d[3]), "+f"(d[4]), "+f"(d[5]), "+f"(d[6]), "+f"(d[7]),
      "+f"(d[8]), "+f"(d[9]), "+f"(d[10]), "+f"(d[11]), "+f"(d[12]), "+f"(d[13]), "+f"(d[14]), "+f"(d[15]),
      "+f"(d[16]), "+f"(d[17]), "+f"(d[18]), "+f"(d[19]), "+f"(d[20]), "+f"(d[21]), "+f"(d[22]), "+f"(d[23]),
      "+f"(d[24]), "+f"(d[25]), "+f"(d[26]), "+f"(d[27]), "+f"(d[28]), "+f"(d[29]), "+f"(d[30]), "+f"(d[31]),
      "+f"(d[32]), "+f"(d[33]), "+f"(d[34]), "+f"(d[35]), "+f"(d[36]), "+f"(d[37]), "+f"(d[38]), "+f"(d[39])
    : "l"(da), "l"(db), "r"(scale_d));
}

DEVINL void wgmma_qk_n64(float (&d)[32], uint32_t a0, uint32_t a1, uint32_t a2, uint32_t a3, uint64_t db, int scale_d) {
  asm volatile("{\n.reg .pred p;\nsetp.ne.b32 p, %37, 0;\n"
    "wgmma.mma_async.sync.aligned.m64n64k16.f32.bf16.bf16 "
    "{%0,%1,%2,%3,%4,%5,%6,%7,%8,%9,%10,%11,%12,%13,%14,%15,"
    "%16,%17,%18,%19,%20,%21,%22,%23,%24,%25,%26,%27,%28,%29,%30,%31}, "
    "{%32,%33,%34,%35}, %36, p, 1, 1, 0;\n}\n"
    : "+f"(d[0]), "+f"(d[1]), "+f"(d[2]), "+f"(d[3]), "+f"(d[4]), "+f"(d[5]), "+f"(d[6]), "+f"(d[7]),
      "+f"(d[8]), "+f"(d[9]), "+f"(d[10]), "+f"(d[11]), "+f"(d[12]), "+f"(d[13]), "+f"(d[14]), "+f"(d[15]),
      "+f"(d[16]), "+f"(d[17]), "+f"(d[18]), "+f"(d[19]), "+f"(d[20]), "+f"(d[21]), "+f"(d[22]), "+f"(d[23]),
      "+f"(d[24]), "+f"(d[25]), "+f"(d[26]), "+f"(d[27]), "+f"(d[28]), "+f"(d[29]), "+f"(d[30]), "+f"(d[31])
    : "r"(a0), "r"(a1), "r"(a2), "r"(a3), "l"(db), "r"(scale_d));
}

DEVINL void wgmma_pv_n24(float (&d)[12], uint32_t a0, uint32_t a1, uint32_t a2, uint32_t a3, uint64_t db, int scale_d) {
  asm volatile("{\n.reg .pred p;\nsetp.ne.b32 p, %17, 0;\n"
    "wgmma.mma_async.sync.aligned.m64n24k16.f32.bf16.bf16 "
    "{%0,%1,%2,%3,%4,%5,%6,%7,%8,%9,%10,%11}, "
    "{%12,%13,%14,%15}, %16, p, 1, 1, 1;\n}\n"
    : "+f"(d[0]), "+f"(d[1]), "+f"(d[2]), "+f"(d[3]), "+f"(d[4]), "+f"(d[5]), "+f"(d[6]), "+f"(d[7]),
      "+f"(d[8]), "+f"(d[9]), "+f"(d[10]), "+f"(d[11])
    : "r"(a0), "r"(a1), "r"(a2), "r"(a3), "l"(db), "r"(scale_d));
}

DEVINL void wgmma_qk_n64_z(float (&d)[32], uint32_t a0, uint32_t a1, uint32_t a2, uint32_t a3, uint64_t db) {
  asm volatile("{\n.reg .pred p;\nsetp.ne.b32 p, 0, 0;\n"
    "wgmma.mma_async.sync.aligned.m64n64k16.f32.bf16.bf16 "
    "{%0,%1,%2,%3,%4,%5,%6,%7,%8,%9,%10,%11,%12,%13,%14,%15,"
    "%16,%17,%18,%19,%20,%21,%22,%23,%24,%25,%26,%27,%28,%29,%30,%31}, "
    "{%32,%33,%34,%35}, %36, p, 1, 1, 0;\n}\n"
    : "=f"(d[0]), "=f"(d[1]), "=f"(d[2]), "=f"(d[3]), "=f"(d[4]), "=f"(d[5]), "=f"(d[6]), "=f"(d[7]),
      "=f"(d[8]), "=f"(d[9]), "=f"(d[10]), "=f"(d[11]), "=f"(d[12]), "=f"(d[13]), "=f"(d[14]), "=f"(d[15]),
      "=f"(d[16]), "=f"(d[17]), "=f"(d[18]), "=f"(d[19]), "=f"(d[20]), "=f"(d[21]), "=f"(d[22]), "=f"(d[23]),
      "=f"(d[24]), "=f"(d[25]), "=f"(d[26]), "=f"(d[27]), "=f"(d[28]), "=f"(d[29]), "=f"(d[30]), "=f"(d[31])
    : "r"(a0), "r"(a1), "r"(a2), "r"(a3), "l"(db));
}

DEVINL void wgmma_pv_n24_z(float (&d)[12], uint32_t a0, uint32_t a1, uint32_t a2, uint32_t a3, uint64_t db) {
  asm volatile("{\n.reg .pred p;\nsetp.ne.b32 p, 0, 0;\n"
    "wgmma.mma_async.sync.aligned.m64n24k16.f32.bf16.bf16 "
    "{%0,%1,%2,%3,%4,%5,%6,%7,%8,%9,%10,%11}, "
    "{%12,%13,%14,%15}, %16, p, 1, 1, 1;\n}\n"
    : "=f"(d[0]), "=f"(d[1]), "=f"(d[2]), "=f"(d[3]), "=f"(d[4]), "=f"(d[5]), "=f"(d[6]), "=f"(d[7]),
      "=f"(d[8]), "=f"(d[9]), "=f"(d[10]), "=f"(d[11])
    : "r"(a0), "r"(a1), "r"(a2), "r"(a3), "l"(db));
}

#define ATT_T(i) do {} while (0)
constexpr float SM_C = 0.22360679774997896f * 1.4426950408889634f;
constexpr float NEG_INF = -INFINITY;
constexpr int PLANE = 2048;
constexpr int PAIR = 11 * PLANE;
constexpr int SEG = 2 * PAIR;

template <int N> DEVINL void reg_fence(float (&d)[N]) {
#pragma unroll
  for (int i = 0; i < N; ++i) asm volatile("" : "+f"(d[i])::"memory");
}
DEVINL float ex2v(float x) { float r; asm volatile("ex2.approx.ftz.f32 %0, %1;" : "=f"(r) : "f"(x)); return r; }
DEVINL uint32_t bsel(uint32_t a, uint32_t b, uint32_t m) { return (a & m) | (b & ~m); }
DEVINL float fsel(float a, float b, uint32_t m) { return __uint_as_float(bsel(__float_as_uint(a), __float_as_uint(b), m)); }
DEVINL uint64_t kdesc(uint32_t lo) { return (uint64_t)lo | ((uint64_t)(128 >> 4) << 32); }
DEVINL uint64_t vdesc(uint32_t lo) { return (uint64_t)lo | ((uint64_t)(PLANE >> 4) << 32); }

DEVINL void mma_qk(float (&s)[32], const uint32_t (&a)[4], const uint32_t (&a8)[2], uint32_t kmain, uint32_t ktail) {
  wgmma_qk_n64_z(s, a[0], a[1], a[2], a[3], kdesc(kmain));
  wgmma_qk_n64(s, a8[0], a8[1], 0u, 0u, kdesc(ktail), 1);
}
template <bool FIRST>
DEVINL void mma_pv(float (&o)[12], const uint32_t (&p)[16], uint32_t v) {
  if (FIRST) wgmma_pv_n24_z(o, p[0], p[1], p[2], p[3], vdesc(v));
  else wgmma_pv_n24(o, p[0], p[1], p[2], p[3], vdesc(v), 1);
#pragma unroll
  for (int b = 1; b < 4; ++b) wgmma_pv_n24(o, p[4 * b], p[4 * b + 1], p[4 * b + 2], p[4 * b + 3], vdesc(v + b * 16), 1);
}
DEVINL void row_max(const float (&s)[32], float& x0o, float& x1o) {
  float x0 = fmaxf(s[0], s[1]), x1 = fmaxf(s[2], s[3]), y0 = fmaxf(s[4], s[5]), y1 = fmaxf(s[6], s[7]);
#pragma unroll
  for (int i = 2; i < 8; i += 2) {
    x0 = fmaxf(x0, fmaxf(s[4 * i], s[4 * i + 1]));
    x1 = fmaxf(x1, fmaxf(s[4 * i + 2], s[4 * i + 3]));
    y0 = fmaxf(y0, fmaxf(s[4 * i + 4], s[4 * i + 5]));
    y1 = fmaxf(y1, fmaxf(s[4 * i + 6], s[4 * i + 7]));
  }
  x0 = fmaxf(x0, y0); x1 = fmaxf(x1, y1);
  x0 = fmaxf(x0, __shfl_xor_sync(0xffffffffu, x0, 1));
  x1 = fmaxf(x1, __shfl_xor_sync(0xffffffffu, x1, 1));
  x0o = fmaxf(x0, __shfl_xor_sync(0xffffffffu, x0, 2));
  x1o = fmaxf(x1, __shfl_xor_sync(0xffffffffu, x1, 2));
}
template <int I0, int I1>
DEVINL void sm_exp(const float (&s)[32], uint32_t (&p)[16], float n0, float n1) {
#pragma unroll
  for (int i = I0; i < I1; ++i) {
    const float e0 = ex2v(fmaf(s[4 * i], SM_C, n0)), e1 = ex2v(fmaf(s[4 * i + 1], SM_C, n0));
    const float e2 = ex2v(fmaf(s[4 * i + 2], SM_C, n1)), e3 = ex2v(fmaf(s[4 * i + 3], SM_C, n1));
    p[2 * i] = pack_bf16(e0, e1);
    p[2 * i + 1] = pack_bf16(e2, e3);
  }
}
DEVINL void rescale(float (&o)[12], float al0, float al1) {
#pragma unroll
  for (int n = 0; n < 3; ++n) { o[4 * n] *= al0; o[4 * n + 1] *= al0; o[4 * n + 2] *= al1; o[4 * n + 3] *= al1; }
}
struct SoftmaxState { float m0, m1, n0, n1, al0, al1; };
DEVINL void next_max(SoftmaxState& st, float x0, float x1, bool valid) {
  x0 = fmaxf(valid ? x0 : NEG_INF, st.m0); x1 = fmaxf(valid ? x1 : NEG_INF, st.m1);
  const float c0 = -x0 * SM_C, c1 = -x1 * SM_C;
  st.al0 = ex2(fmaf(st.m0, SM_C, c0)); st.al1 = ex2(fmaf(st.m1, SM_C, c1));
  st.m0 = x0; st.m1 = x1;
  st.n0 = valid ? c0 : NEG_INF; st.n1 = valid ? c1 : NEG_INF;
}
template <bool RESC>
DEVINL void step(const float (&cur)[32], float (&nxt)[32], float (&o)[12], uint32_t (&p)[16], SoftmaxState& st, bool valid_nxt) {
  const float n0 = st.n0, n1 = st.n1;
  sm_exp<0, 3>(cur, p, n0, n1);
  wg_wait<0>();
  reg_fence(nxt);
  if (RESC) { reg_fence(o); rescale(o, st.al0, st.al1); }
  float x0, x1;
  row_max(nxt, x0, x1);
  sm_exp<3, 8>(cur, p, n0, n1);
  next_max(st, x0, x1, valid_nxt);
}

DEVINL void attn_all(uint32_t ring, uint32_t stg, uint32_t bars, int wq, int lane, int cmin) {
  const int wg = wq >> 2, w = wq & 3;
  const int g = lane >> 2, t = lane & 3, mi = lane >> 3, r = lane & 7;
  const uint32_t T0 = (2 * t > g) ? 0xFFFFFFFFu : 0u, T1 = (2 * t + 1 > g) ? 0xFFFFFFFFu : 0u;
  const uint32_t tri = (T0 & 0xFFFFu) | (T1 & 0xFFFF0000u);
  const uint32_t rowQ = stg + (mi >> 1) * PLANE + (16 * wq + r + 8 * (mi & 1)) * 16;
  const uint32_t rowQ8 = stg + 2 * PLANE + (16 * wq + (lane & 15)) * 16;
  constexpr uint32_t S16 = SEG >> 4, P16 = PLANE >> 4;
  const uint32_t aE = ((ring + wg * 1024) & 0x3FFFF) >> 4, aO = ((ring + wg * SEG + (wg ^ 1) * 1024) & 0x3FFFF) >> 4;
  const uint32_t kE = aE | (P16 << 16), kO = aO | (P16 << 16);
  const uint32_t vE = aE | ((128 >> 4) << 16), vO = aO | ((128 >> 4) << 16);
  uint32_t a[4], a8[2];
  float sX[32], sY[32], o[12];
  uint32_t pA[16], pB[16];
  mbar_wait(bars + 8 * B_HALO, 0);
  ldsm4(a[0], a[1], a[2], a[3], rowQ);
  ldsm2(a8[0], a8[1], rowQ8);
  if (t >= 2) { a8[0] = 0u; a8[1] = 0u; }
  wg_fence();
  mma_qk(sX, a, a8, kE, kE + 2 * P16);
  mma_qk(sY, a, a8, kE + 2 * S16, kE + 2 * S16 + 2 * P16);
  wg_commit();
#pragma unroll 1
  for (int h = 0; h < 4; ++h) {
    const int p = h >> 1, odd = h & 1;
    const uint32_t km = (p * 11 + odd * 3) * P16, kt = (p * 11 + 2) * P16, vp = (p * 11 + 5 + odd * 3) * P16;
    SoftmaxState st;
    ATT_T(0);
    wg_wait<0>();
    reg_fence(sX); reg_fence(sY);
    ATT_T(1);
    if (cmin > 0) {
#pragma unroll
      for (int i = 0; i < 32; ++i) sX[i] = NEG_INF;
    }
#pragma unroll
    for (int b = 0; b < 4; ++b) {
      const uint32_t gt = b > w ? 0xFFFFFFFFu : 0u, ge = b >= w ? 0xFFFFFFFFu : 0u, eq = ge & ~gt;
      const uint32_t e0 = gt | (eq & T0), e1 = gt | (eq & T1);
      sX[8 * b + 0] = fsel(sX[8 * b + 0], sY[8 * b + 0], e0);
      sX[8 * b + 1] = fsel(sX[8 * b + 1], sY[8 * b + 1], e1);
      sX[8 * b + 2] = fsel(sX[8 * b + 2], sY[8 * b + 2], gt);
      sX[8 * b + 3] = fsel(sX[8 * b + 3], sY[8 * b + 3], gt);
      sX[8 * b + 4] = fsel(sX[8 * b + 4], sY[8 * b + 4], ge);
      sX[8 * b + 5] = fsel(sX[8 * b + 5], sY[8 * b + 5], ge);
      sX[8 * b + 6] = fsel(sX[8 * b + 6], sY[8 * b + 6], e0);
      sX[8 * b + 7] = fsel(sX[8 * b + 7], sY[8 * b + 7], e1);
    }
    wg_fence();
    mma_qk(sY, a, a8, kO + km, kO + kt);
    wg_commit();
    ATT_T(2);
    row_max(sX, st.m0, st.m1);
    st.n0 = -st.m0 * SM_C; st.n1 = -st.m1 * SM_C;
    ATT_T(3);
    step<false>(sX, sY, o, pA, st, wg + 1 >= cmin);
    ATT_T(4);
#pragma unroll
    for (int b = 0; b < 4; ++b) {
      const uint32_t gt = b > w ? 0xFFFFFFFFu : 0u, ge = b >= w ? 0xFFFFFFFFu : 0u, eq = ge & ~gt;
      const uint32_t mt = gt | (eq & tri);
      pB[4 * b + 0] = pA[4 * b + 0] & ~mt; pA[4 * b + 0] &= mt;
      pB[4 * b + 1] = pA[4 * b + 1] & ~gt; pA[4 * b + 1] &= gt;
      pB[4 * b + 2] = pA[4 * b + 2] & ~ge; pA[4 * b + 2] &= ge;
      pB[4 * b + 3] = pA[4 * b + 3] & ~mt; pA[4 * b + 3] &= mt;
    }
    wg_fence();
    mma_qk(sX, a, a8, kE + S16 + km, kE + S16 + kt);
    mma_pv<true>(o, pA, vE + vp);
    mma_pv<false>(o, pB, vE + 2 * S16 + vp);
    wg_commit();
    ATT_T(5);
    step<true>(sY, sX, o, pB, st, wg + 2 >= cmin);
    ATT_T(6);
    wg_fence();
    mma_qk(sY, a, a8, kO + S16 + km, kO + S16 + kt);
    mma_pv<false>(o, pB, vO + vp);
    wg_commit();
    ATT_T(7);
    step<true>(sX, sY, o, pA, st, wg + 3 >= cmin);
    ATT_T(8);
    const int hn = h < 3 ? h + 1 : h, pn = hn >> 1, on = hn & 1;
    const uint32_t kmn = (pn * 11 + on * 3) * P16, ktn = (pn * 11 + 2) * P16;
    if (h == 1) mbar_wait(bars + 8 * (B_HALO + 1), 0);
    ldsm4(a[0], a[1], a[2], a[3], rowQ + (pn * 5 + on * 3) * PLANE);
    ldsm2(a8[0], a8[1], rowQ8 + pn * 5 * PLANE);
    if ((t >= 2) != (on != 0)) { a8[0] = 0u; a8[1] = 0u; }
    wg_fence();
    mma_pv<false>(o, pA, vE + S16 + vp);
    mma_qk(sX, a, a8, kE + kmn, kE + ktn);
    wg_commit();
    ATT_T(9);
    sm_exp<0, 8>(sY, pB, st.n0, st.n1);
    ATT_T(10);
    wg_wait<0>();
    reg_fence(o); reg_fence(sX);
    rescale(o, st.al0, st.al1);
    wg_fence();
    mma_pv<false>(o, pB, vO + S16 + vp);
    wg_commit();
    wg_fence();
    mma_qk(sY, a, a8, kE + 2 * S16 + kmn, kE + 2 * S16 + ktn);
    wg_commit();
    ATT_T(11);
    wg_wait<1>();
    reg_fence(o);
    const int src = (lane & ~3) | (odd ? 0 : 2);
    const float i0 = __fdividef(1.f, __shfl_sync(0xffffffffu, o[8], src)), i1 = __fdividef(1.f, __shfl_sync(0xffffffffu, o[10], src));
    const uint32_t ob = stg + p * 5 * PLANE + (16 * wq + g) * 16 + t * 4;
    const uint32_t om = ob + odd * 3 * PLANE;
    sts32(om, pack_bf16(o[0] * i0, o[1] * i0)); sts32(om + 128, pack_bf16(o[2] * i1, o[3] * i1));
    sts32(om + PLANE, pack_bf16(o[4] * i0, o[5] * i0)); sts32(om + PLANE + 128, pack_bf16(o[6] * i1, o[7] * i1));
    if ((t >= 2) == (odd != 0)) { sts32(ob + 2 * PLANE, pack_bf16(o[8] * i0, o[9] * i0)); sts32(ob + 2 * PLANE + 128, pack_bf16(o[10] * i1, o[11] * i1)); }
    if (odd) {
      fence_async_smem();
      __syncwarp();
      if (lane == 0) mbar_arrive(bars + 8 * (B_OST + p));
    }
    ATT_T(12);
  }
  wg_wait<0>();
  reg_fence(sX); reg_fence(sY);
  __syncwarp();
}

struct Params {
  const uint16_t* q; const uint16_t* shift_k; const uint16_t* ssm_k; const uint16_t* ssm_D; uint16_t* out;
};

DEVINL unsigned* cnt(int i) { return &g_cnt[i * CS]; }

DEVINL void finish_role() {
  unsigned old = atomicAdd(cnt(C_DONE), 1u);
  if (old == 255u) {
    __threadfence();
    for (int i = 0; i < C_NUM; ++i) *cnt(i) = 0u;
    __threadfence();
  }
}

__global__ void __cluster_dims__(2, 1, 1) __launch_bounds__(512, 1)
h3_swa_fused_kernel(const __grid_constant__ CUtensorMap tmX, const __grid_constant__ CUtensorMap tmW128,
                    const __grid_constant__ CUtensorMap tmW32, const __grid_constant__ CUtensorMap tmWo,
                    const __grid_constant__ CUtensorMap tmOut, const __grid_constant__ CUtensorMap tmKT,
                    const __grid_constant__ CUtensorMap tmKin, const __grid_constant__ CUtensorMap tmVin,
                    const Params prm) {
  extern __shared__ uint8_t smem_raw[];
  const uint32_t sb = ((uint32_t)__cvta_generic_to_shared(smem_raw) + 1023u) & ~1023u;
  const uint32_t bars = sb + OFF_BAR;
  const int tid = threadIdx.x, warp = tid >> 5, lane = tid & 31, wg = tid >> 7;
  const int cta = blockIdx.x;
  const uint32_t rank = cta & 1;
  const int g8 = (cta >> 1) & 7, rp = cta >> 4;
  const int rb = 2 * rp + rank;
  const int rb2 = 2 * rp + (g8 & 1);
  const int c2 = 2 * (g8 >> 1) + rank;
  const int tau = cta & 15, jt = cta >> 4;

  if (tid == 384) { prefetch_tmap(&tmX); prefetch_tmap(&tmW128); prefetch_tmap(&tmW32); }
  if (tid == 256) { prefetch_tmap(&tmKin); prefetch_tmap(&tmVin); }
  if (tid == 0) {
    PROF(0);
    for (int i = 0; i < NST1; ++i) { mbar_init(bars + 8 * (B_FULL1 + i), 1); mbar_init(bars + 8 * (B_EMPTY1 + i), 16); }
    mbar_init(bars + 8 * B_RINGFREE, 1);
    mbar_init(bars + 8 * B_HALO, 1); mbar_init(bars + 8 * (B_HALO + 1), 1);
    for (int i = 0; i < NST2; ++i) { mbar_init(bars + 8 * (B_FULL2 + i), 1); mbar_init(bars + 8 * (B_EMPTY2 + i), 16); }
    mbar_init(bars + 8 * B_U, 1);
    mbar_init(bars + 8 * B_KVST, 8);
    mbar_init(bars + 8 * B_OST, 8); mbar_init(bars + 8 * (B_OST + 1), 8);
    mbar_init(bars + 8 * B_PRE, 1);
    mbar_init(bars + 8 * B_KTST, 4);
    mbar_init(bars + 8 * B_YST, 4); mbar_init(bars + 8 * (B_YST + 1), 4);
    mbar_init(bars + 8 * B_STGFREE, 1);
    asm volatile("fence.mbarrier_init.release.cluster;" ::: "memory");
  }
  __syncthreads();
  asm volatile("barrier.cluster.arrive.relaxed.aligned;\nbarrier.cluster.wait.aligned;" ::: "memory");

  if (wg == 3) {
    asm volatile("setmaxnreg.dec.sync.aligned.u32 40;");
    if (warp == 12 && lane == 0) {
      PROF(15);
      for (int it = 0; it < 10; ++it) {
        const int s = it % NST1;
        if (it >= NST1) mbar_wait(bars + 8 * (B_EMPTY1 + s), ((it / NST1) - 1) & 1);
        PROF(44 + it);
        const uint32_t st = sb + s * ST1, fb = bars + 8 * (B_FULL1 + s);
        mbar_expect(fb, ST1);
        tma2d(st, &tmX, it * 64, rb * 128, fb);
        tma3d_mc(st + ST1_B128 + rank * 12288, &tmW128, g8 * 80, it * 64 + rank * 32, 0, fb);
        tma3d_mc(st + ST1_B32 + rank * 3072, &tmW32, g8 * 80 + 64, it * 64 + rank * 32, 0, fb);
      }
      PROF(1);
      mbar_wait(bars + 8 * B_RINGFREE, 0);
      for (int p = 0; p < 2; ++p) {
        const uint32_t hb = bars + 8 * (B_HALO + p);
        if (rb == 0) { mbar_arrive(hb); continue; }
        poll_ge(cnt(C_KV + (g8 * 16 + rb - 1) * 2 + p), 1);
        if (rb >= 2) poll_ge(cnt(C_KV + (g8 * 16 + rb - 2) * 2 + p), 1);
        if (p == 0) PROF(2);
        mbar_expect(hb, (rb >= 2 ? 2 : 1) * PAIR);
        bulk_load(sb + SEG + p * PAIR, g_kv + (size_t)(g8 * 16 + rb - 1) * (SEG / 2) + p * (PAIR / 2), PAIR, hb);
        if (rb >= 2) bulk_load(sb + p * PAIR, g_kv + (size_t)(g8 * 16 + rb - 2) * (SEG / 2) + p * (PAIR / 2), PAIR, hb);
      }
      for (int it = 0; it < 8; ++it) {
        const int s = it & 3, p = it >> 2;
        mbar_wait(bars + 8 * (B_EMPTY2 + s), p);
        const uint32_t fb = bars + 8 * (B_FULL2 + s);
        mbar_expect(fb, ST2);
        tma5d(sb + s * ST2 + 20480, &tmWo, 0, 0, p, 2 * s, c2 * 5, fb);
        if (s == 0) { if (p == 0) PROF(3); poll_ge(cnt(C_O + rb2 * 2 + p), 8); if (p == 1) PROF(4); }
        bulk_load_mc(sb + s * ST2 + rank * 10240, g_o + (size_t)(rb2 * 80 + p * 40 + (2 * s + rank) * 5) * 1024, 10240, fb);
      }
      finish_role();
    } else if (warp == 13 && lane == 0) {
      prefetch_tmap(&tmWo); prefetch_tmap(&tmOut);
      mbar_wait(bars + 8 * B_KVST, 0);
      uint16_t* kd = g_kv + (size_t)(g8 * 16 + rb) * (SEG / 2);
      bulk_store(kd, sb + 2 * SEG, PAIR); bulk_commit();
      bulk_store(kd + PAIR / 2, sb + 2 * SEG + PAIR, PAIR); bulk_commit();
      bulk_wait<1>(); red_publish(cnt(C_KV + (g8 * 16 + rb) * 2));
      bulk_wait<0>(); red_publish(cnt(C_KV + (g8 * 16 + rb) * 2 + 1));
      PROF(24);
      for (int p = 0; p < 2; ++p) {
        mbar_wait(bars + 8 * (B_OST + p), 0);
        bulk_store(g_o + (size_t)(rb * 80 + p * 40 + g8 * 5) * 1024, sb + OFF_STG + p * 10240, 10240);
        bulk_commit(); bulk_wait<0>();
        red_publish(cnt(C_O + rb * 2 + p));
      }
      PROF(20);
    } else if (warp == 14 && lane == 0) {
      mbar_expect(bars + 8 * B_PRE, 131 * 160 + 128 * 160);
      tma2d(sb + OFF_F, &tmKin, jt * 80, tau * 128 - 3, bars + 8 * B_PRE);
      tma2d(sb + OFF_F + 21120, &tmVin, jt * 80, tau * 128, bars + 8 * B_PRE);
      prefetch_l2(prm.ssm_k + (size_t)cta * 5 * SEQ, 5 * SEQ * 2);
      prefetch_tmap(&tmKT);
      mbar_wait(bars + 8 * B_KTST, 0);
      tma3d_store(&tmKT, 64 * tau, 0, jt * 80, sb + OFF_STG);
      bulk_commit(); bulk_wait<0>();
      mbar_arrive(bars + 8 * B_STGFREE);
      red_publish(cnt(C_PRE + jt));
      PROF(8);
      poll_ge(cnt(C_PRE + jt), 16);
      mbar_expect(bars + 8 * B_U, 5 * 4096);
      for (int i = 0; i < 10; ++i)
        bulk_load(sb + OFF_U + (i >> 1) * CH_U + (i & 1) * 2176 + 128, g_kvT + (size_t)(cta * 5) * SEQ + i * 1024, 2048, bars + 8 * B_U);
      PROF(9);
      mbar_wait(bars + 8 * B_YST, 0);
      for (int i = 0; i < 4; ++i) bulk_store(g_yT + (size_t)(cta * 5 + i) * SEQ, sb + OFF_U + i * CH_U, 4096);
      bulk_commit(); bulk_wait<0>();
      red_publish(cnt(C_Y + jt), 4);
      mbar_wait(bars + 8 * (B_YST + 1), 0);
      bulk_store(g_yT + (size_t)(cta * 5 + 4) * SEQ, sb + OFF_F + 4 * CH_F, 4096);
      bulk_commit(); bulk_wait<0>();
      red_publish(cnt(C_Y + jt), 1);
      PROF(11);
    }
  } else if (wg == 2) {
    asm volatile("setmaxnreg.inc.sync.aligned.u32 136;");
    const int ct = tid - 256, wc = warp - 8;
    const int t0 = tau * 128, c0 = jt * 80;
    const int mi = lane >> 3, r = lane & 7, g = lane >> 2, t = lane & 3;
    const uint32_t U = sb + OFF_U, F = sb + OFF_F;
    if (ct == 0) PROF(14);
    {
      const uint32_t KT = F, VT = F + 21120;
      mbar_wait(bars + 8 * B_PRE, 0);
      if (ct == 0) PROF(5);
#pragma unroll 1
      for (int item = ct; item < 160; item += 128) {
        const int c = item % 10, seg = item / 10;
        uint32_t W[4][4];
#pragma unroll
        for (int u = 0; u < 4; ++u) {
          const uint4 wv = ldg_nc(prm.shift_k + (size_t)(c0 + c * 8 + 2 * u) * 4);
          W[0][u] = __byte_perm(wv.x, wv.z, 0x5410); W[1][u] = __byte_perm(wv.x, wv.z, 0x7632);
          W[2][u] = __byte_perm(wv.y, wv.w, 0x5410); W[3][u] = __byte_perm(wv.y, wv.w, 0x7632);
        }
        const uint32_t ka = KT + seg * 8 * 160 + c * 16, va = VT + seg * 8 * 160 + c * 16;
        uint4 k0 = lds128(ka), k1 = lds128(ka + 160), k2 = lds128(ka + 320);
#pragma unroll
        for (int i = 0; i < 8; ++i) {
          const uint4 k3 = lds128(ka + (i + 3) * 160), vv = lds128(va + i * 160);
          uint32_t res[4];
#pragma unroll
          for (int u = 0; u < 4; ++u) {
            uint32_t acc = hadd2(hmul2((&k0.x)[u], W[3][u]), hmul2((&k1.x)[u], W[2][u]));
            acc = hadd2(acc, hmul2((&k2.x)[u], W[1][u]));
            acc = hadd2(acc, hmul2((&k3.x)[u], W[0][u]));
            res[u] = hmul2(acc, (&vv.x)[u]);
          }
          sts128(U + (seg * 8 + i) * 160 + c * 16, make_uint4(res[0], res[1], res[2], res[3]));
          k0 = k1; k1 = k2; k2 = k3;
        }
      }
    }
    named_sync(3, 128);
#pragma unroll 1
    for (int it = wc; it < 40; it += 4) {
      const int c = it % 10, rest = it / 10, h = rest & 1, iq = rest >> 1;
      const int tl = 16 * (4 * iq + (r >> 1)) + 15 - (8 * h + 2 * mi + (r & 1));
      uint4 v4;
      ldsm4t(v4.x, v4.y, v4.z, v4.w, U + tl * 160 + c * 16);
      sts128(sb + OFF_STG + (c * 8 + g) * 256 + h * 128 + (4 * iq + t) * 16, v4);
    }
    fence_async_smem();
    __syncwarp();
    if (lane == 0) mbar_arrive(bars + 8 * B_KTST);
    if (ct == 0) PROF(7);
    named_sync(3, 128);
    if (ct < 80) sts128(U + (ct >> 4) * CH_U + ((ct >> 3) & 1) * 2176 + (ct & 7) * 16, make_uint4(0, 0, 0, 0));
    {
      const int chb = cta * 5;
      uint4 fv[10]; uint32_t pv[10];
#pragma unroll
      for (int i = 0; i < 10; ++i) {
        const int cl = i >> 1, qq = ct + (i & 1) * 128;
        const uint16_t* src = prm.ssm_k + (size_t)(chb + cl) * SEQ + qq * 8;
        fv[i] = ldg_nc(src);
        pv[i] = qq > 0 ? (uint32_t)__ldg(src - 1) : 0u;
      }
#pragma unroll
      for (int i = 0; i < 10; ++i) {
        const int cl = i >> 1, qq = ct + (i & 1) * 128;
        const uint32_t a = F + cl * CH_F + 32 + qq * 16;
        sts128(a, fv[i]);
        sts128(a + 4160, make_uint4(__byte_perm(pv[i], fv[i].x, 0x5410), __byte_perm(fv[i].x, fv[i].y, 0x5432),
                                    __byte_perm(fv[i].y, fv[i].z, 0x5432), __byte_perm(fv[i].z, fv[i].w, 0x5432)));
      }
      if (ct < 20) sts128(F + (ct >> 2) * CH_F + ((ct >> 1) & 1) * 4160 + (ct & 1) * 16, make_uint4(0, 0, 0, 0));
    }
    named_sync(3, 128);
    mbar_wait(bars + 8 * B_U, 0);
    if (ct == 0) PROF(10);
#pragma unroll 1
    for (int pass = 0; pass < 2; ++pass) {
      const int cl = pass == 0 ? wc : 4;
      const int r0 = pass == 0 ? 0 : 2 * wc, r1 = pass == 0 ? 8 : 2 * wc + 2;
      const uint32_t Ub = U + cl * CH_U, Fb = F + cl * CH_F;
      const uint32_t laneU = Ub + (mi & 1) * 2176 + (8 + 8 * (mi >> 1) + r) * 16;
      const uint32_t laneF = (g & 1) ? Fb + 4160 + 2 * (17 - g + 2 * t) : Fb + 2 * (16 - g + 2 * t);
      float acc[16][4];
#pragma unroll
      for (int i = 0; i < 16; ++i) { acc[i][0] = 0.f; acc[i][1] = 0.f; acc[i][2] = 0.f; acc[i][3] = 0.f; }
#pragma unroll 1
      for (int rho = r0; rho < r1; ++rho) {
        uint32_t uf[16][2];
#pragma unroll
        for (int jj = 0; jj < 8; ++jj)
          ldsm4(uf[2 * jj][0], uf[2 * jj][1], uf[2 * jj + 1][0], uf[2 * jj + 1][1], laneU + jj * 256 - rho * 16);
        const uint32_t fb = laneF + 32 * rho;
#pragma unroll
        for (int mu = 0; mu < 16; ++mu) {
          const uint32_t a0 = lds32(fb + 256 * mu), a1 = lds32(fb + 256 * mu - 16), a2 = lds32(fb + 256 * mu + 16);
#pragma unroll
          for (int i = mu; i < 16; ++i) mma16816(acc[i], a0, a1, a2, a0, uf[i - mu][0], uf[i - mu][1]);
        }
      }
      const uint32_t dv = (uint32_t)__ldg(prm.ssm_D + cta * 5 + cl);
      const uint32_t D2 = dv | (dv << 16);
      if (pass == 0) {
        uint32_t res[8][4];
#pragma unroll
        for (int jj = 0; jj < 8; ++jj) {
          uint32_t u0, u1, u2, u3;
          ldsm4t(u0, u1, u2, u3, laneU + jj * 256);
          res[jj][0] = hadd2(pack_bf16(acc[2 * jj][0], acc[2 * jj][1]), hmul2(u0, D2));
          res[jj][1] = hadd2(pack_bf16(acc[2 * jj][2], acc[2 * jj][3]), hmul2(u1, D2));
          res[jj][2] = hadd2(pack_bf16(acc[2 * jj + 1][0], acc[2 * jj + 1][1]), hmul2(u2, D2));
          res[jj][3] = hadd2(pack_bf16(acc[2 * jj + 1][2], acc[2 * jj + 1][3]), hmul2(u3, D2));
        }
        __syncwarp();
#pragma unroll
        for (int jj = 0; jj < 8; ++jj)
          stsm4t(Ub + ((8 * (2 * jj + (mi >> 1)) + r) * 16 + 8 * (mi & 1)) * 2, res[jj][0], res[jj][1], res[jj][2], res[jj][3]);
        fence_async_smem();
        __syncwarp();
        if (lane == 0) mbar_arrive(bars + 8 * B_YST);
      } else {
        const uint32_t rbuf = F + wc * CH_F + lane * 16;
#pragma unroll
        for (int i = 0; i < 16; ++i)
          sts128(rbuf + i * 512, make_uint4(__float_as_uint(acc[i][0]), __float_as_uint(acc[i][1]),
                                            __float_as_uint(acc[i][2]), __float_as_uint(acc[i][3])));
        named_sync(3, 128);
        uint32_t res[2][4];
#pragma unroll
        for (int jj = 0; jj < 2; ++jj) {
          float sum[2][4];
#pragma unroll
          for (int hh = 0; hh < 2; ++hh) {
            const int tile = 4 * wc + 2 * jj + hh;
            sum[hh][0] = 0.f; sum[hh][1] = 0.f; sum[hh][2] = 0.f; sum[hh][3] = 0.f;
#pragma unroll
            for (int w = 0; w < 4; ++w) {
              const uint4 x = lds128(F + w * CH_F + lane * 16 + tile * 512);
              sum[hh][0] += __uint_as_float(x.x); sum[hh][1] += __uint_as_float(x.y);
              sum[hh][2] += __uint_as_float(x.z); sum[hh][3] += __uint_as_float(x.w);
            }
          }
          uint32_t u0, u1, u2, u3;
          ldsm4t(u0, u1, u2, u3, laneU + (2 * wc + jj) * 256);
          res[jj][0] = hadd2(pack_bf16(sum[0][0], sum[0][1]), hmul2(u0, D2));
          res[jj][1] = hadd2(pack_bf16(sum[0][2], sum[0][3]), hmul2(u1, D2));
          res[jj][2] = hadd2(pack_bf16(sum[1][0], sum[1][1]), hmul2(u2, D2));
          res[jj][3] = hadd2(pack_bf16(sum[1][2], sum[1][3]), hmul2(u3, D2));
        }
#pragma unroll
        for (int jj = 0; jj < 2; ++jj)
          stsm4t(F + 4 * CH_F + ((8 * (2 * (2 * wc + jj) + (mi >> 1)) + r) * 16 + 8 * (mi & 1)) * 2, res[jj][0], res[jj][1], res[jj][2], res[jj][3]);
        fence_async_smem();
        __syncwarp();
        if (lane == 0) mbar_arrive(bars + 8 * (B_YST + 1));
      }
    }
    uint4 qv[10];
#pragma unroll
    for (int i = 0; i < 10; ++i) {
      const int idx = ct + 128 * i, row = idx / 10, c = idx % 10;
      qv[i] = ldg_nc(prm.q + (size_t)(t0 + row) * DM + c0 + c * 8);
    }
    if (ct == 0) { poll_ge(cnt(C_Y + jt), 80); finish_role(); PROF(12); }
    named_sync(3, 128);
    const uint32_t YT = sb + OFF_U, YN = sb + OFF_F + 1024;
#pragma unroll
    for (int i = 0; i < 10; ++i) {
      const int idx = ct + 128 * i, ch = idx >> 4, cq = idx & 15;
      sts128(YT + ch * 272 + cq * 16, ldg_cg(g_yT + (size_t)(c0 + ch) * SEQ + t0 + cq * 8));
    }
    named_sync(3, 128);
#pragma unroll 1
    for (int it = wc; it < 40; it += 4) {
      const int c = it % 10, tq = it / 10;
      uint32_t x0, x1, x2, x3;
      ldsm4t(x0, x1, x2, x3, YT + (8 * c + r) * 272 + (4 * tq + mi) * 16);
      const int s = (8 * (4 * tq + mi) + r) ^ 15;
      stsm4(YN + s * 176 + c * 16, x0, x1, x2, x3);
    }
    named_sync(3, 128);
#pragma unroll
    for (int i = 0; i < 10; ++i) {
      const int idx = ct + 128 * i, row = idx / 10, c = idx % 10;
      const uint4 y = lds128(YN + row * 176 + c * 16);
      stg128(prm.out + (size_t)(t0 + row) * (2 * DM) + c0 + c * 8,
             make_uint4(hmul2(qv[i].x, y.x), hmul2(qv[i].y, y.y), hmul2(qv[i].z, y.z), hmul2(qv[i].w, y.w)));
    }
    if (ct == 0) PROF(13);
  } else {
    asm volatile("setmaxnreg.inc.sync.aligned.u32 168;");
    const int wq = __shfl_sync(0xffffffffu, warp, 0);
    const int mi = lane >> 3, r = lane & 7;
    const uint32_t stg = sb + OFF_STG;
    {
      float acc1[96], acc2[24];
#pragma unroll 1
      for (int it = 0; it < 10; ++it) {
        const int s = it % NST1;
        mbar_wait(bars + 8 * (B_FULL1 + s), (it / NST1) & 1);
        if (tid == 0) PROF(32 + it);
        const uint32_t st = sb + s * ST1;
        wg_fence();
#pragma unroll
        for (int kk = 0; kk < 4; ++kk) {
          const uint64_t da = make_desc(st + wg * 8192 + kk * 32, 16, 1024, 1);
          const uint64_t db1 = make_desc(st + ST1_B128 + (kk >> 1) * 12288 + (kk & 1) * 2048, 4096, 1024, 1);
          const uint64_t db2 = make_desc(st + ST1_B32 + (kk >> 1) * 3072 + (kk & 1) * 512, 1024, 256, 3);
          wgmma_n192(acc1, da, db1, (it | kk) != 0);
          wgmma_n48(acc2, da, db2, (it | kk) != 0);
        }
        wg_commit();
        wg_wait<0>();
        if (it + NST1 < 10 && lane < 2) mbar_arrive_cta(bars + 8 * (B_EMPTY1 + s), lane);
      }
      reg_fence(acc1); reg_fence(acc2);
      if (tid == 0) PROF(17);
      named_sync(1, 256);
      if (tid == 0) mbar_arrive(bars + 8 * B_RINGFREE);
      const uint32_t rowo = (16 * wq + 8 * (mi & 1) + r) * 16;
      const int t4 = lane & 3;
#pragma unroll
      for (int kv = 0; kv < 2; ++kv) {
#pragma unroll
        for (int tp = 0; tp < 5; ++tp) {
          uint32_t w[4];
#pragma unroll
          for (int hh = 0; hh < 2; ++hh) {
            const int tile = 2 * tp + hh;
            if (tile < 8) {
              const int o = 32 * (kv + 1) + 4 * tile;
              w[2 * hh] = pack_bf16(acc1[o], acc1[o + 1]); w[2 * hh + 1] = pack_bf16(acc1[o + 2], acc1[o + 3]);
            } else {
              const int o = 8 * (kv + 1) + 4 * (tile - 8);
              w[2 * hh] = pack_bf16(acc2[o], acc2[o + 1]); w[2 * hh + 1] = pack_bf16(acc2[o + 2], acc2[o + 3]);
            }
          }
          const int tA = 2 * tp, tB = 2 * tp + 1;
          const int plA = (tA / 5) * 11 + (kv ? 5 : 0) + tA % 5, plB = (tB / 5) * 11 + (kv ? 5 : 0) + tB % 5;
          if (kv == 1 && (tA % 5 == 2 || tB % 5 == 2)) {
            const int hh = (tA % 5 == 2) ? 0 : 1, pr = (hh ? tB : tA) / 5;
            const uint32_t x0 = w[2 * hh], x1 = w[2 * hh + 1];
            const uint32_t oneE = t4 == 2 ? 0x00003F80u : 0u, oneO = t4 == 0 ? 0x00003F80u : 0u;
            stsm2(sb + 2 * SEG + (pr * 11 + 10) * PLANE + (16 * wq + (lane & 15)) * 16, t4 >= 2 ? x0 : oneO, t4 >= 2 ? x1 : oneO);
            w[2 * hh] = t4 < 2 ? x0 : oneE; w[2 * hh + 1] = t4 < 2 ? x1 : oneE;
          }
          stsm4(sb + 2 * SEG + rowo + ((mi >> 1) ? plB : plA) * PLANE, w[0], w[1], w[2], w[3]);
        }
      }
      fence_async_smem();
      __syncwarp();
      if (lane == 0) mbar_arrive(bars + 8 * B_KVST);
      mbar_wait(bars + 8 * B_STGFREE, 0);
      const uint32_t rq = stg + rowo + (mi >> 1) * PLANE;
#pragma unroll
      for (int tp = 0; tp < 4; ++tp)
        stsm4(rq + tp * 2 * PLANE, pack_bf16(acc1[8 * tp], acc1[8 * tp + 1]), pack_bf16(acc1[8 * tp + 2], acc1[8 * tp + 3]),
              pack_bf16(acc1[8 * tp + 4], acc1[8 * tp + 5]), pack_bf16(acc1[8 * tp + 6], acc1[8 * tp + 7]));
      stsm4(rq + 8 * PLANE, pack_bf16(acc2[0], acc2[1]), pack_bf16(acc2[2], acc2[3]), pack_bf16(acc2[4], acc2[5]), pack_bf16(acc2[6], acc2[7]));
    }
    if (rb < 2) {
      const int nz = (2 - rb) * (SEG / 16);
#pragma unroll 1
      for (int i = tid; i < nz; i += 256) sts128(sb + i * 16, make_uint4(0, 0, 0, 0));
      fence_async_smem();
    }
    named_sync(2, 256);
    if (tid == 0) PROF(18);
    attn_all(sb, stg, bars, wq, lane, rb >= 2 ? 0 : 4 - 2 * rb);
    if (tid == 0) PROF(19);
    if (lane < 2 * NST2) mbar_arrive_cta(bars + 8 * (B_EMPTY2 + (lane >> 1)), lane & 1);
    float acc[40];
#pragma unroll 1
    for (int it = 0; it < 8; ++it) {
      const int s = it & 3;
      mbar_wait(bars + 8 * (B_FULL2 + s), it >> 2);
      if (it == 0 && tid == 0) PROF(21);
      if (it == 4 && tid == 0) PROF(25);
      const uint32_t st = sb + s * ST2;
      wg_fence();
#pragma unroll
      for (int kk = 0; kk < 5; ++kk)
        wgmma_n80(acc, make_desc(st + wg * 1024 + kk * 2 * PLANE, PLANE, 128, 0), make_desc(st + 20480 + kk * 512, 2560, 256, 3), (it | kk) != 0);
      wg_commit();
      wg_wait<0>();
      if (it < 4 && lane < 2) mbar_arrive_cta(bars + 8 * (B_EMPTY2 + s), lane);
    }
    reg_fence(acc);
    if (tid == 0) PROF(22);
    named_sync(1, 256);
    {
      const uint32_t rowa = sb + (16 * wq + 8 * (mi & 1) + r) * 160 + (mi >> 1) * 16;
#pragma unroll
      for (int tp = 0; tp < 5; ++tp)
        stsm4(rowa + tp * 32, pack_bf16(acc[8 * tp], acc[8 * tp + 1]), pack_bf16(acc[8 * tp + 2], acc[8 * tp + 3]),
              pack_bf16(acc[8 * tp + 4], acc[8 * tp + 5]), pack_bf16(acc[8 * tp + 6], acc[8 * tp + 7]));
      fence_async_smem();
      __syncwarp();
      if (lane == 0) {
        tma2d_store(&tmOut, DM + c2 * 80, rb2 * 128 + 16 * wq, sb + wq * 2560);
        bulk_commit();
        bulk_wait0_read();
      }
    }
    if (tid == 0) PROF(23);
  }
}

typedef CUresult (*EncodeFn)(CUtensorMap*, CUtensorMapDataType, cuuint32_t, void*, const cuuint64_t*, const cuuint64_t*,
                             const cuuint32_t*, const cuuint32_t*, CUtensorMapInterleave, CUtensorMapSwizzle,
                             CUtensorMapL2promotion, CUtensorMapFloatOOBfill);

CUtensorMap make_map(EncodeFn enc, const void* p, int rank, const cuuint64_t* dims, const cuuint64_t* strides,
                     const cuuint32_t* box, CUtensorMapSwizzle sw) {
  CUtensorMap m;
  const cuuint32_t es[5] = {1, 1, 1, 1, 1};
  enc(&m, CU_TENSOR_MAP_DATA_TYPE_BFLOAT16, rank, const_cast<void*>(p), dims, strides, box, es,
      CU_TENSOR_MAP_INTERLEAVE_NONE, sw, CU_TENSOR_MAP_L2_PROMOTION_L2_128B, CU_TENSOR_MAP_FLOAT_OOB_FILL_NONE);
  return m;
}

}

extern "C" void kernel_launch(void* const* d_in, const int* in_sizes, int n_in, void* d_out, int out_size) {
  (void)in_sizes; (void)n_in; (void)out_size;
  static EncodeFn enc = nullptr;
  static void* kt_ptr = nullptr;
  if (!enc) {
    void* fn = nullptr;
    cudaDriverEntryPointQueryResult qr;
    cudaGetDriverEntryPoint("cuTensorMapEncodeTiled", &fn, cudaEnableDefault, &qr);
    enc = (EncodeFn)fn;
    cudaGetSymbolAddress(&kt_ptr, g_kvT);
    cudaFuncSetAttribute(h3_swa_fused_kernel, cudaFuncAttributeMaxDynamicSharedMemorySize, SMEM_BYTES);
  }
  const void* x = d_in[6];
  const void* wqkv = d_in[7];
  const void* wo = d_in[8];
  CUtensorMap tmX, tmW128, tmW32, tmWo, tmOut, tmKT, tmKin, tmVin;
  { cuuint64_t d[2] = {640, 2048}, s[1] = {1280}; cuuint32_t b[2] = {64, 128};
    tmX = make_map(enc, x, 2, d, s, b, CU_TENSOR_MAP_SWIZZLE_128B); }
  { cuuint64_t d[3] = {640, 640, 3}, s[2] = {3840, 1280}; cuuint32_t b[3] = {64, 32, 3};
    tmW128 = make_map(enc, wqkv, 3, d, s, b, CU_TENSOR_MAP_SWIZZLE_128B); }
  { cuuint64_t d[3] = {640, 640, 3}, s[2] = {3840, 1280}; cuuint32_t b[3] = {16, 32, 3};
    tmW32 = make_map(enc, wqkv, 3, d, s, b, CU_TENSOR_MAP_SWIZZLE_32B); }
  {
    cuuint64_t d[5] = {16, 40, 2, 8, 40}, s[4] = {1280, 51200, 102400, 32}; cuuint32_t b[5] = {16, 40, 1, 2, 5};
    tmWo = make_map(enc, wo, 5, d, s, b, CU_TENSOR_MAP_SWIZZLE_32B); }
  { cuuint64_t d[2] = {1280, 2048}, s[1] = {2560}; cuuint32_t b[2] = {80, 16};
    tmOut = make_map(enc, d_out, 2, d, s, b, CU_TENSOR_MAP_SWIZZLE_NONE); }
  { cuuint64_t d[3] = {1024, 2, 640}, s[2] = {2048, 4096}; cuuint32_t b[3] = {64, 2, 80};
    tmKT = make_map(enc, kt_ptr, 3, d, s, b, CU_TENSOR_MAP_SWIZZLE_NONE); }
  { cuuint64_t d[2] = {640, 2048}, s[1] = {1280}; cuuint32_t b[2] = {80, 131};
    tmKin = make_map(enc, d_in[1], 2, d, s, b, CU_TENSOR_MAP_SWIZZLE_NONE); }
  { cuuint64_t d[2] = {640, 2048}, s[1] = {1280}; cuuint32_t b[2] = {80, 128};
    tmVin = make_map(enc, d_in[2], 2, d, s, b, CU_TENSOR_MAP_SWIZZLE_NONE); }
  Params prm;
  prm.q = (const uint16_t*)d_in[0]; prm.shift_k = (const uint16_t*)d_in[3]; prm.ssm_k = (const uint16_t*)d_in[4];
  prm.ssm_D = (const uint16_t*)d_in[5]; prm.out = (uint16_t*)d_out;
  h3_swa_fused_kernel<<<128, 512, SMEM_BYTES>>>(tmX, tmW128, tmW32, tmWo, tmOut, tmKT, tmKin, tmVin, prm);
}
```

```cpp
#include <cuda_runtime.h>
#include <cuda.h>
#include <cuda_bf16.h>
#include <stdint.h>

#define DEVINL __device__ __forceinline__

namespace {

constexpr int SEQ = 2048;
constexpr int DM = 640;

constexpr int ST1 = 47104;
constexpr int ST1_B128 = 16384;
constexpr int ST1_B32 = 40960;
constexpr int NST1 = 3;
constexpr int ST2 = 33280;
constexpr int NST2 = 4;
constexpr int OFF_CONV = NST1 * ST1;
constexpr int CH_U = 4352;
constexpr int CH_F = 8320;
constexpr int OFF_U = OFF_CONV;
constexpr int OFF_F = OFF_CONV + 5 * CH_U;
constexpr int OFF_STG = OFF_F + 5 * CH_F;
constexpr int OFF_BAR = OFF_STG + 20480;
constexpr int SMEM_BYTES = OFF_BAR + 256 + 1024;

constexpr int B_FULL1 = 0, B_EMPTY1 = 3, B_RINGFREE = 6, B_HALO = 7, B_FULL2 = 9, B_EMPTY2 = 13, B_U = 17, B_KVST = 18,
              B_OST = 19, B_PRE = 21, B_KTST = 22, B_YST = 23, B_STGFREE = 25;

__device__ __align__(1024) uint16_t g_kv[8 * 16 * 22 * 1024];
__device__ __align__(1024) uint16_t g_o[SEQ * DM];
__device__ __align__(1024) uint16_t g_kvT[DM * SEQ];
__device__ __align__(1024) uint16_t g_yT[DM * SEQ];
constexpr int CS = 32;
constexpr int C_KV = 0, C_O = 256, C_PRE = 288, C_Y = 296, C_DONE = 304, C_NUM = 305;
__device__ unsigned g_cnt[C_NUM * CS];
__device__ unsigned g_err;
#define PROF(slot) do {} while (0)

DEVINL void mbar_init(uint32_t a, uint32_t c) { asm volatile("mbarrier.init.shared::cta.b64 [%0], %1;" ::"r"(a), "r"(c)); }
DEVINL void mbar_expect(uint32_t a, uint32_t b) {
  asm volatile("mbarrier.arrive.expect_tx.shared::cta.b64 _, [%0], %1;" ::"r"(a), "r"(b) : "memory");
}
DEVINL void mbar_arrive(uint32_t a) { asm volatile("mbarrier.arrive.shared::cta.b64 _, [%0];" ::"r"(a) : "memory"); }
DEVINL void mbar_arrive_cta(uint32_t a, uint32_t cta) {
  asm volatile("{\n.reg .b32 ra;\nmapa.shared::cluster.u32 ra, %0, %1;\nmbarrier.arrive.shared::cluster.b64 _, [ra];\n}"
               ::"r"(a), "r"(cta) : "memory");
}
DEVINL bool mbar_try(uint32_t a, uint32_t p) {
  uint32_t ok;
  asm volatile("{\n.reg .pred P;\nmbarrier.try_wait.parity.shared::cta.b64 P, [%1], %2;\nselp.u32 %0, 1, 0, P;\n}"
               : "=r"(ok) : "r"(a), "r"(p) : "memory");
  return ok;
}
DEVINL void mbar_wait(uint32_t a, uint32_t p) {
  if (mbar_try(a, p)) return;
  int n = 0;
  while (!mbar_try(a, p)) {
    if (++n > (1 << 18)) { g_err = 1; break; }
  }
}
DEVINL void poll_ge(const unsigned* p, unsigned target) {
  int n = 0;
  while (true) {
    unsigned v;
    asm volatile("ld.relaxed.gpu.global.u32 %0, [%1];" : "=r"(v) : "l"(p) : "memory");
    if (v >= target) break;
    if (++n > (1 << 20)) { g_err = 2; break; }
  }
}
DEVINL void red_publish(unsigned* p, unsigned n = 1) { asm volatile("red.release.gpu.global.add.u32 [%0], %1;" ::"l"(p), "r"(n) : "memory"); }
DEVINL void fence_async_smem() { asm volatile("fence.proxy.async.shared::cta;" ::: "memory"); }
DEVINL void named_sync(int id, int n) { asm volatile("bar.sync %0, %1;" ::"r"(id), "r"(n) : "memory"); }
DEVINL void named_arrive(int id, int n) { asm volatile("bar.arrive %0, %1;" ::"r"(id), "r"(n) : "memory"); }

DEVINL void tma2d(uint32_t dst, const CUtensorMap* m, int c0, int c1, uint32_t bar) {
  asm volatile("cp.async.bulk.tensor.2d.shared::cluster.global.mbarrier::complete_tx::bytes [%0], [%1, {%3, %4}], [%2];"
               ::"r"(dst), "l"(m), "r"(bar), "r"(c0), "r"(c1) : "memory");
}
DEVINL void tma2d_mc(uint32_t dst, const CUtensorMap* m, int c0, int c1, uint32_t bar) {
  asm volatile("cp.async.bulk.tensor.2d.shared::cluster.global.mbarrier::complete_tx::bytes.multicast::cluster [%0], [%1, {%3, %4}], [%2], %5;"
               ::"r"(dst), "l"(m), "r"(bar), "r"(c0), "r"(c1), "h"((uint16_t)3) : "memory");
}
DEVINL void tma3d(uint32_t dst, const CUtensorMap* m, int c0, int c1, int c2, uint32_t bar) {
  asm volatile("cp.async.bulk.tensor.3d.shared::cluster.global.mbarrier::complete_tx::bytes [%0], [%1, {%3, %4, %5}], [%2];"
               ::"r"(dst), "l"(m), "r"(bar), "r"(c0), "r"(c1), "r"(c2) : "memory");
}
DEVINL void tma3d_mc(uint32_t dst, const CUtensorMap* m, int c0, int c1, int c2, uint32_t bar) {
  asm volatile("cp.async.bulk.tensor.3d.shared::cluster.global.mbarrier::complete_tx::bytes.multicast::cluster [%0], [%1, {%3, %4, %5}], [%2], %6;"
               ::"r"(dst), "l"(m), "r"(bar), "r"(c0), "r"(c1), "r"(c2), "h"((uint16_t)3) : "memory");
}
DEVINL void tma2d_store(const CUtensorMap* m, int c0, int c1, uint32_t src) {
  asm volatile("cp.async.bulk.tensor.2d.global.shared::cta.bulk_group [%0, {%2, %3}], [%1];"
               ::"l"(m), "r"(src), "r"(c0), "r"(c1) : "memory");
}
DEVINL void tma3d_store(const CUtensorMap* m, int c0, int c1, int c2, uint32_t src) {
  asm volatile("cp.async.bulk.tensor.3d.global.shared::cta.bulk_group [%0, {%2, %3, %4}], [%1];"
               ::"l"(m), "r"(src), "r"(c0), "r"(c1), "r"(c2) : "memory");
}
DEVINL void bulk_load(uint32_t dst, const void* src, uint32_t bytes, uint32_t bar) {
  asm volatile("cp.async.bulk.shared::cluster.global.mbarrier::complete_tx::bytes [%0], [%1], %2, [%3];"
               ::"r"(dst), "l"(src), "r"(bytes), "r"(bar) : "memory");
}
DEVINL void bulk_load_mc(uint32_t dst, const void* src, uint32_t bytes, uint32_t bar) {
  asm volatile("cp.async.bulk.shared::cluster.global.mbarrier::complete_tx::bytes.multicast::cluster [%0], [%1], %2, [%3], %4;"
               ::"r"(dst), "l"(src), "r"(bytes), "r"(bar), "h"((uint16_t)3) : "memory");
}
DEVINL void tma5d(uint32_t dst, const CUtensorMap* m, int c0, int c1, int c2, int c3, int c4, uint32_t bar) {
  asm volatile("cp.async.bulk.tensor.5d.shared::cluster.global.mbarrier::complete_tx::bytes [%0], [%1, {%3, %4, %5, %6, %7}], [%2];"
               ::"r"(dst), "l"(m), "r"(bar), "r"(c0), "r"(c1), "r"(c2), "r"(c3), "r"(c4) : "memory");
}
DEVINL void prefetch_line(const void* p) { asm volatile("prefetch.global.L2 [%0];" ::"l"(p)); }
DEVINL void prefetch_l2(const void* p, uint32_t bytes) {
  asm volatile("cp.async.bulk.prefetch.L2.global [%0], %1;" ::"l"(p), "r"(bytes) : "memory");
}
template <int N> DEVINL void bulk_wait() { asm volatile("cp.async.bulk.wait_group %0;" ::"n"(N) : "memory"); }
DEVINL void bulk_store(void* dst, uint32_t src, uint32_t bytes) {
  asm volatile("cp.async.bulk.global.shared::cta.bulk_group [%0], [%1], %2;" ::"l"(dst), "r"(src), "r"(bytes) : "memory");
}
DEVINL void bulk_commit() { asm volatile("cp.async.bulk.commit_group;" ::: "memory"); }
DEVINL void bulk_wait0() { asm volatile("cp.async.bulk.wait_group 0;" ::: "memory"); }
DEVINL void bulk_wait0_read() { asm volatile("cp.async.bulk.wait_group.read 0;" ::: "memory"); }
DEVINL void prefetch_tmap(const CUtensorMap* m) { asm volatile("prefetch.tensormap [%0];" ::"l"(m) : "memory"); }

DEVINL uint64_t make_desc(uint32_t addr, uint32_t lbo, uint32_t sbo, uint32_t swz) {
  return (uint64_t)((addr & 0x3FFFF) >> 4) | ((uint64_t)(lbo >> 4) << 16) | ((uint64_t)(sbo >> 4) << 32) | ((uint64_t)swz << 62);
}
DEVINL void wg_fence() { asm volatile("wgmma.fence.sync.aligned;" ::: "memory"); }
DEVINL void wg_commit() { asm volatile("wgmma.commit_group.sync.aligned;" ::: "memory"); }
template <int N> DEVINL void wg_wait() { asm volatile("wgmma.wait_group.sync.aligned %0;" ::"n"(N) : "memory"); }

DEVINL void mma16816(float (&d)[4], uint32_t a0, uint32_t a1, uint32_t a2, uint32_t a3, uint32_t b0, uint32_t b1) {
  asm volatile("mma.sync.aligned.m16n8k16.row.col.f32.bf16.bf16.f32 {%0,%1,%2,%3},{%4,%5,%6,%7},{%8,%9},{%0,%1,%2,%3};"
               : "+f"(d[0]), "+f"(d[1]), "+f"(d[2]), "+f"(d[3]) : "r"(a0), "r"(a1), "r"(a2), "r"(a3), "r"(b0), "r"(b1));
}
DEVINL void mma16816_z(float (&d)[4], uint32_t a0, uint32_t a1, uint32_t a2, uint32_t a3, uint32_t b0, uint32_t b1) {
  asm volatile("mma.sync.aligned.m16n8k16.row.col.f32.bf16.bf16.f32 {%0,%1,%2,%3},{%4,%5,%6,%7},{%8,%9},{%10,%10,%10,%10};"
               : "=f"(d[0]), "=f"(d[1]), "=f"(d[2]), "=f"(d[3]) : "r"(a0), "r"(a1), "r"(a2), "r"(a3), "r"(b0), "r"(b1), "f"(0.f));
}
DEVINL void mma1688(float (&d)[4], uint32_t a0, uint32_t a1, uint32_t b0) {
  asm volatile("mma.sync.aligned.m16n8k8.row.col.f32.bf16.bf16.f32 {%0,%1,%2,%3},{%4,%5},{%6},{%0,%1,%2,%3};"
               : "+f"(d[0]), "+f"(d[1]), "+f"(d[2]), "+f"(d[3]) : "r"(a0), "r"(a1), "r"(b0));
}
DEVINL void ldsm4(uint32_t& r0, uint32_t& r1, uint32_t& r2, uint32_t& r3, uint32_t a) {
  asm volatile("ldmatrix.sync.aligned.m8n8.x4.shared.b16 {%0,%1,%2,%3}, [%4];" : "=r"(r0), "=r"(r1), "=r"(r2), "=r"(r3) : "r"(a));
}
DEVINL void ldsm2(uint32_t& r0, uint32_t& r1, uint32_t a) {
  asm volatile("ldmatrix.sync.aligned.m8n8.x2.shared.b16 {%0,%1}, [%2];" : "=r"(r0), "=r"(r1) : "r"(a));
}
DEVINL void ldsm4t(uint32_t& r0, uint32_t& r1, uint32_t& r2, uint32_t& r3, uint32_t a) {
  asm volatile("ldmatrix.sync.aligned.m8n8.x4.trans.shared.b16 {%0,%1,%2,%3}, [%4];" : "=r"(r0), "=r"(r1), "=r"(r2), "=r"(r3) : "r"(a));
}
DEVINL void ldsm2t(uint32_t& r0, uint32_t& r1, uint32_t a) {
  asm volatile("ldmatrix.sync.aligned.m8n8.x2.trans.shared.b16 {%0,%1}, [%2];" : "=r"(r0), "=r"(r1) : "r"(a));
}
DEVINL void stsm4(uint32_t a, uint32_t r0, uint32_t r1, uint32_t r2, uint32_t r3) {
  asm volatile("stmatrix.sync.aligned.m8n8.x4.shared.b16 [%0], {%1,%2,%3,%4};" ::"r"(a), "r"(r0), "r"(r1), "r"(r2), "r"(r3) : "memory");
}
DEVINL void stsm2(uint32_t a, uint32_t r0, uint32_t r1) {
  asm volatile("stmatrix.sync.aligned.m8n8.x2.shared.b16 [%0], {%1,%2};" ::"r"(a), "r"(r0), "r"(r1) : "memory");
}
DEVINL void stsm4t(uint32_t a, uint32_t r0, uint32_t r1, uint32_t r2, uint32_t r3) {
  asm volatile("stmatrix.sync.aligned.m8n8.x4.trans.shared.b16 [%0], {%1,%2,%3,%4};" ::"r"(a), "r"(r0), "r"(r1), "r"(r2), "r"(r3) : "memory");
}
DEVINL uint32_t lds32(uint32_t a) { uint32_t v; asm volatile("ld.shared.u32 %0, [%1];" : "=r"(v) : "r"(a)); return v; }
DEVINL uint4 lds128(uint32_t a) {
  uint4 v; asm volatile("ld.shared.v4.u32 {%0,%1,%2,%3}, [%4];" : "=r"(v.x), "=r"(v.y), "=r"(v.z), "=r"(v.w) : "r"(a)); return v;
}
DEVINL void sts32(uint32_t a, uint32_t v) { asm volatile("st.shared.u32 [%0], %1;" ::"r"(a), "r"(v) : "memory"); }
DEVINL void sts128(uint32_t a, uint4 v) {
  asm volatile("st.shared.v4.u32 [%0], {%1,%2,%3,%4};" ::"r"(a), "r"(v.x), "r"(v.y), "r"(v.z), "r"(v.w) : "memory");
}
DEVINL uint4 ldg_nc(const void* p) {
  uint4 v; asm volatile("ld.global.nc.L1::no_allocate.v4.u32 {%0,%1,%2,%3}, [%4];" : "=r"(v.x), "=r"(v.y), "=r"(v.z), "=r"(v.w) : "l"(p)); return v;
}
DEVINL uint4 ldg_cg(const void* p) {
  uint4 v; asm volatile("ld.global.cg.v4.u32 {%0,%1,%2,%3}, [%4];" : "=r"(v.x), "=r"(v.y), "=r"(v.z), "=r"(v.w) : "l"(p) : "memory"); return v;
}
DEVINL void stg128(void* p, uint4 v) {
  asm volatile("st.global.v4.u32 [%0], {%1,%2,%3,%4};" ::"l"(p), "r"(v.x), "r"(v.y), "r"(v.z), "r"(v.w) : "memory");
}
DEVINL uint32_t pack_bf16(float lo, float hi) {
  uint32_t r; asm("cvt.rn.bf16x2.f32 %0, %1, %2;" : "=r"(r) : "f"(hi), "f"(lo)); return r;
}
DEVINL uint32_t hmul2(uint32_t a, uint32_t b) { uint32_t r; asm("mul.rn.bf16x2 %0, %1, %2;" : "=r"(r) : "r"(a), "r"(b)); return r; }
DEVINL uint32_t hadd2(uint32_t a, uint32_t b) { uint32_t r; asm("add.rn.bf16x2 %0, %1, %2;" : "=r"(r) : "r"(a), "r"(b)); return r; }
DEVINL float ex2(float x) { float r; asm("ex2.approx.ftz.f32 %0, %1;" : "=f"(r) : "f"(x)); return r; }

DEVINL void wgmma_n192(float (&d)[96], uint64_t da, uint64_t db, int scale_d) {
  asm volatile("{\n.reg .pred p;\nsetp.ne.b32 p, %98, 0;\n"
    "wgmma.mma_async.sync.aligned.m64n192k16.f32.bf16.bf16 "
    "{%0,%1,%2,%3,%4,%5,%6,%7,%8,%9,%10,%11,%12,%13,%14,%15,"
    "%16,%17,%18,%19,%20,%21,%22,%23,%24,%25,%26,%27,%28,%29,%30,%31,"
    "%32,%33,%34,%35,%36,%37,%38,%39,%40,%41,%42,%43,%44,%45,%46,%47,"
    "%48,%49,%50,%51,%52,%53,%54,%55,%56,%57,%58,%59,%60,%61,%62,%63,"
    "%64,%65,%66,%67,%68,%69,%70,%71,%72,%73,%74,%75,%76,%77,%78,%79,"
    "%80,%81,%82,%83,%84,%85,%86,%87,%88,%89,%90,%91,%92,%93,%94,%95}, "
    "%96, %97, p, 1, 1, 0, 1;\n}\n"
    : "+f"(d[0]), "+f"(d[1]), "+f"(d[2]), "+f"(d[3]), "+f"(d[4]), "+f"(d[5]), "+f"(d[6]), "+f"(d[7]),
      "+f"(d[8]), "+f"(d[9]), "+f"(d[10]), "+f"(d[11]), "+f"(d[12]), "+f"(d[13]), "+f"(d[14]), "+f"(d[15]),
      "+f"(d[16]), "+f"(d[17]), "+f"(d[18]), "+f"(d[19]), "+f"(d[20]), "+f"(d[21]), "+f"(d[22]), "+f"(d[23]),
      "+f"(d[24]), "+f"(d[25]), "+f"(d[26]), "+f"(d[27]), "+f"(d[28]), "+f"(d[29]), "+f"(d[30]), "+f"(d[31]),
      "+f"(d[32]), "+f"(d[33]), "+f"(d[34]), "+f"(d[35]), "+f"(d[36]), "+f"(d[37]), "+f"(d[38]), "+f"(d[39]),
      "+f"(d[40]), "+f"(d[41]), "+f"(d[42]), "+f"(d[43]), "+f"(d[44]), "+f"(d[45]), "+f"(d[46]), "+f"(d[47]),
      "+f"(d[48]), "+f"(d[49]), "+f"(d[50]), "+f"(d[51]), "+f"(d[52]), "+f"(d[53]), "+f"(d[54]), "+f"(d[55]),
      "+f"(d[56]), "+f"(d[57]), "+f"(d[58]), "+f"(d[59]), "+f"(d[60]), "+f"(d[61]), "+f"(d[62]), "+f"(d[63]),
      "+f"(d[64]), "+f"(d[65]), "+f"(d[66]), "+f"(d[67]), "+f"(d[68]), "+f"(d[69]), "+f"(d[70]), "+f"(d[71]),
      "+f"(d[72]), "+f"(d[73]), "+f"(d[74]), "+f"(d[75]), "+f"(d[76]), "+f"(d[77]), "+f"(d[78]), "+f"(d[79]),
      "+f"(d[80]), "+f"(d[81]), "+f"(d[82]), "+f"(d[83]), "+f"(d[84]), "+f"(d[85]), "+f"(d[86]), "+f"(d[87]),
      "+f"(d[88]), "+f"(d[89]), "+f"(d[90]), "+f"(d[91]), "+f"(d[92]), "+f"(d[93]), "+f"(d[94]), "+f"(d[95])
    : "l"(da), "l"(db), "r"(scale_d));
}

DEVINL void wgmma_n48(float (&d)[24], uint64_t da, uint64_t db, int scale_d) {
  asm volatile("{\n.reg .pred p;\nsetp.ne.b32 p, %26, 0;\n"
    "wgmma.mma_async.sync.aligned.m64n48k16.f32.bf16.bf16 "
    "{%0,%1,%2,%3,%4,%5,%6,%7,%8,%9,%10,%11,%12,%13,%14,%15,"
    "%16,%17,%18,%19,%20,%21,%22,%23}, "
    "%24, %25, p, 1, 1, 0, 1;\n}\n"
    : "+f"(d[0]), "+f"(d[1]), "+f"(d[2]), "+f"(d[3]), "+f"(d[4]), "+f"(d[5]), "+f"(d[6]), "+f"(d[7]),
      "+f"(d[8]), "+f"(d[9]), "+f"(d[10]), "+f"(d[11]), "+f"(d[12]), "+f"(d[13]), "+f"(d[14]), "+f"(d[15]),
      "+f"(d[16]), "+f"(d[17]), "+f"(d[18]), "+f"(d[19]), "+f"(d[20]), "+f"(d[21]), "+f"(d[22]), "+f"(d[23])
    : "l"(da), "l"(db), "r"(scale_d));
}

DEVINL void wgmma_n80(float (&d)[40], uint64_t da, uint64_t db, int scale_d) {
  asm volatile("{\n.reg .pred p;\nsetp.ne.b32 p, %42, 0;\n"
    "wgmma.mma_async.sync.aligned.m64n80k16.f32.bf16.bf16 "
    "{%0,%1,%2,%3,%4,%5,%6,%7,%8,%9,%10,%11,%12,%13,%14,%15,"
    "%16,%17,%18,%19,%20,%21,%22,%23,%24,%25,%26,%27,%28,%29,%30,%31,"
    "%32,%33,%34,%35,%36,%37,%38,%39}, "
    "%40, %41, p, 1, 1, 0, 1;\n}\n"
    : "+f"(d[0]), "+f"(d[1]), "+f"(d[2]), "+f"(d[3]), "+f"(d[4]), "+f"(d[5]), "+f"(d[6]), "+f"(d[7]),
      "+f"(d[8]), "+f"(d[9]), "+f"(d[10]), "+f"(d[11]), "+f"(d[12]), "+f"(d[13]), "+f"(d[14]), "+f"(d[15]),
      "+f"(d[16]), "+f"(d[17]), "+f"(d[18]), "+f"(d[19]), "+f"(d[20]), "+f"(d[21]), "+f"(d[22]), "+f"(d[23]),
      "+f"(d[24]), "+f"(d[25]), "+f"(d[26]), "+f"(d[27]), "+f"(d[28]), "+f"(d[29]), "+f"(d[30]), "+f"(d[31]),
      "+f"(d[32]), "+f"(d[33]), "+f"(d[34]), "+f"(d[35]), "+f"(d[36]), "+f"(d[37]), "+f"(d[38]), "+f"(d[39])
    : "l"(da), "l"(db), "r"(scale_d));
}

DEVINL void wgmma_qk_n64(float (&d)[32], uint32_t a0, uint32_t a1, uint32_t a2, uint32_t a3, uint64_t db, int scale_d) {
  asm volatile("{\n.reg .pred p;\nsetp.ne.b32 p, %37, 0;\n"
    "wgmma.mma_async.sync.aligned.m64n64k16.f32.bf16.bf16 "
    "{%0,%1,%2,%3,%4,%5,%6,%7,%8,%9,%10,%11,%12,%13,%14,%15,"
    "%16,%17,%18,%19,%20,%21,%22,%23,%24,%25,%26,%27,%28,%29,%30,%31}, "
    "{%32,%33,%34,%35}, %36, p, 1, 1, 0;\n}\n"
    : "+f"(d[0]), "+f"(d[1]), "+f"(d[2]), "+f"(d[3]), "+f"(d[4]), "+f"(d[5]), "+f"(d[6]), "+f"(d[7]),
      "+f"(d[8]), "+f"(d[9]), "+f"(d[10]), "+f"(d[11]), "+f"(d[12]), "+f"(d[13]), "+f"(d[14]), "+f"(d[15]),
      "+f"(d[16]), "+f"(d[17]), "+f"(d[18]), "+f"(d[19]), "+f"(d[20]), "+f"(d[21]), "+f"(d[22]), "+f"(d[23]),
      "+f"(d[24]), "+f"(d[25]), "+f"(d[26]), "+f"(d[27]), "+f"(d[28]), "+f"(d[29]), "+f"(d[30]), "+f"(d[31])
    : "r"(a0), "r"(a1), "r"(a2), "r"(a3), "l"(db), "r"(scale_d));
}

DEVINL void wgmma_pv_n24(float (&d)[12], uint32_t a0, uint32_t a1, uint32_t a2, uint32_t a3, uint64_t db, int scale_d) {
  asm volatile("{\n.reg .pred p;\nsetp.ne.b32 p, %17, 0;\n"
    "wgmma.mma_async.sync.aligned.m64n24k16.f32.bf16.bf16 "
    "{%0,%1,%2,%3,%4,%5,%6,%7,%8,%9,%10,%11}, "
    "{%12,%13,%14,%15}, %16, p, 1, 1, 1;\n}\n"
    : "+f"(d[0]), "+f"(d[1]), "+f"(d[2]), "+f"(d[3]), "+f"(d[4]), "+f"(d[5]), "+f"(d[6]), "+f"(d[7]),
      "+f"(d[8]), "+f"(d[9]), "+f"(d[10]), "+f"(d[11])
    : "r"(a0), "r"(a1), "r"(a2), "r"(a3), "l"(db), "r"(scale_d));
}

DEVINL void wgmma_qk_n64_z(float (&d)[32], uint32_t a0, uint32_t a1, uint32_t a2, uint32_t a3, uint64_t db) {
  asm volatile("{\n.reg .pred p;\nsetp.ne.b32 p, 0, 0;\n"
    "wgmma.mma_async.sync.aligned.m64n64k16.f32.bf16.bf16 "
    "{%0,%1,%2,%3,%4,%5,%6,%7,%8,%9,%10,%11,%12,%13,%14,%15,"
    "%16,%17,%18,%19,%20,%21,%22,%23,%24,%25,%26,%27,%28,%29,%30,%31}, "
    "{%32,%33,%34,%35}, %36, p, 1, 1, 0;\n}\n"
    : "=f"(d[0]), "=f"(d[1]), "=f"(d[2]), "=f"(d[3]), "=f"(d[4]), "=f"(d[5]), "=f"(d[6]), "=f"(d[7]),
      "=f"(d[8]), "=f"(d[9]), "=f"(d[10]), "=f"(d[11]), "=f"(d[12]), "=f"(d[13]), "=f"(d[14]), "=f"(d[15]),
      "=f"(d[16]), "=f"(d[17]), "=f"(d[18]), "=f"(d[19]), "=f"(d[20]), "=f"(d[21]), "=f"(d[22]), "=f"(d[23]),
      "=f"(d[24]), "=f"(d[25]), "=f"(d[26]), "=f"(d[27]), "=f"(d[28]), "=f"(d[29]), "=f"(d[30]), "=f"(d[31])
    : "r"(a0), "r"(a1), "r"(a2), "r"(a3), "l"(db));
}

DEVINL void wgmma_pv_n24_z(float (&d)[12], uint32_t a0, uint32_t a1, uint32_t a2, uint32_t a3, uint64_t db) {
  asm volatile("{\n.reg .pred p;\nsetp.ne.b32 p, 0, 0;\n"
    "wgmma.mma_async.sync.aligned.m64n24k16.f32.bf16.bf16 "
    "{%0,%1,%2,%3,%4,%5,%6,%7,%8,%9,%10,%11}, "
    "{%12,%13,%14,%15}, %16, p, 1, 1, 1;\n}\n"
    : "=f"(d[0]), "=f"(d[1]), "=f"(d[2]), "=f"(d[3]), "=f"(d[4]), "=f"(d[5]), "=f"(d[6]), "=f"(d[7]),
      "=f"(d[8]), "=f"(d[9]), "=f"(d[10]), "=f"(d[11])
    : "r"(a0), "r"(a1), "r"(a2), "r"(a3), "l"(db));
}

#define ATT_T(i) do {} while (0)
constexpr float SM_C = 0.22360679774997896f * 1.4426950408889634f;
constexpr float NEG_INF = -INFINITY;
constexpr int PLANE = 2048;
constexpr int PAIR = 11 * PLANE;
constexpr int SEG = 2 * PAIR;

template <int N> DEVINL void reg_fence(float (&d)[N]) {
#pragma unroll
  for (int i = 0; i < N; ++i) asm volatile("" : "+f"(d[i])::"memory");
}
DEVINL float ex2v(float x) { float r; asm volatile("ex2.approx.ftz.f32 %0, %1;" : "=f"(r) : "f"(x)); return r; }
DEVINL uint32_t bsel(uint32_t a, uint32_t b, uint32_t m) { return (a & m) | (b & ~m); }
DEVINL float fsel(float a, float b, uint32_t m) { return __uint_as_float(bsel(__float_as_uint(a), __float_as_uint(b), m)); }
DEVINL uint64_t kdesc(uint32_t lo) { return (uint64_t)lo | ((uint64_t)(128 >> 4) << 32); }
DEVINL uint64_t vdesc(uint32_t lo) { return (uint64_t)lo | ((uint64_t)(PLANE >> 4) << 32); }

DEVINL void mma_qk(float (&s)[32], const uint32_t (&a)[4], const uint32_t (&a8)[2], uint32_t kmain, uint32_t ktail) {
  wgmma_qk_n64_z(s, a[0], a[1], a[2], a[3], kdesc(kmain));
  wgmma_qk_n64(s, a8[0], a8[1], 0u, 0u, kdesc(ktail), 1);
}
template <bool FIRST>
DEVINL void mma_pv(float (&o)[12], const uint32_t (&p)[16], uint32_t v) {
  if (FIRST) wgmma_pv_n24_z(o, p[0], p[1], p[2], p[3], vdesc(v));
  else wgmma_pv_n24(o, p[0], p[1], p[2], p[3], vdesc(v), 1);
#pragma unroll
  for (int b = 1; b < 4; ++b) wgmma_pv_n24(o, p[4 * b], p[4 * b + 1], p[4 * b + 2], p[4 * b + 3], vdesc(v + b * 16), 1);
}
DEVINL void row_max(const float (&s)[32], float& x0o, float& x1o) {
  float x0 = fmaxf(s[0], s[1]), x1 = fmaxf(s[2], s[3]), y0 = fmaxf(s[4], s[5]), y1 = fmaxf(s[6], s[7]);
#pragma unroll
  for (int i = 2; i < 8; i += 2) {
    x0 = fmaxf(x0, fmaxf(s[4 * i], s[4 * i + 1]));
    x1 = fmaxf(x1, fmaxf(s[4 * i + 2], s[4 * i + 3]));
    y0 = fmaxf(y0, fmaxf(s[4 * i + 4], s[4 * i + 5]));
    y1 = fmaxf(y1, fmaxf(s[4 * i + 6], s[4 * i + 7]));
  }
  x0 = fmaxf(x0, y0); x1 = fmaxf(x1, y1);
  x0 = fmaxf(x0, __shfl_xor_sync(0xffffffffu, x0, 1));
  x1 = fmaxf(x1, __shfl_xor_sync(0xffffffffu, x1, 1));
  x0o = fmaxf(x0, __shfl_xor_sync(0xffffffffu, x0, 2));
  x1o = fmaxf(x1, __shfl_xor_sync(0xffffffffu, x1, 2));
}
template <int I0, int I1>
DEVINL void sm_exp(const float (&s)[32], uint32_t (&p)[16], float n0, float n1) {
#pragma unroll
  for (int i = I0; i < I1; ++i) {
    const float e0 = ex2v(fmaf(s[4 * i], SM_C, n0)), e1 = ex2v(fmaf(s[4 * i + 1], SM_C, n0));
    const float e2 = ex2v(fmaf(s[4 * i + 2], SM_C, n1)), e3 = ex2v(fmaf(s[4 * i + 3], SM_C, n1));
    p[2 * i] = pack_bf16(e0, e1);
    p[2 * i + 1] = pack_bf16(e2, e3);
  }
}
DEVINL void rescale(float (&o)[12], float al0, float al1) {
#pragma unroll
  for (int n = 0; n < 3; ++n) { o[4 * n] *= al0; o[4 * n + 1] *= al0; o[4 * n + 2] *= al1; o[4 * n + 3] *= al1; }
}
struct SoftmaxState { float m0, m1, n0, n1, al0, al1; };
DEVINL void next_max(SoftmaxState& st, float x0, float x1, bool valid) {
  x0 = fmaxf(valid ? x0 : NEG_INF, st.m0); x1 = fmaxf(valid ? x1 : NEG_INF, st.m1);
  const float c0 = -x0 * SM_C, c1 = -x1 * SM_C;
  st.al0 = ex2(fmaf(st.m0, SM_C, c0)); st.al1 = ex2(fmaf(st.m1, SM_C, c1));
  st.m0 = x0; st.m1 = x1;
  st.n0 = valid ? c0 : NEG_INF; st.n1 = valid ? c1 : NEG_INF;
}
template <bool RESC>
DEVINL void step(const float (&cur)[32], float (&nxt)[32], float (&o)[12], uint32_t (&p)[16], SoftmaxState& st, bool valid_nxt) {
  const float n0 = st.n0, n1 = st.n1;
  sm_exp<0, 3>(cur, p, n0, n1);
  wg_wait<0>();
  reg_fence(nxt);
  if (RESC) { reg_fence(o); rescale(o, st.al0, st.al1); }
  float x0, x1;
  row_max(nxt, x0, x1);
  sm_exp<3, 8>(cur, p, n0, n1);
  next_max(st, x0, x1, valid_nxt);
}

DEVINL void attn_all(uint32_t ring, uint32_t stg, uint32_t bars, int wq, int lane, int cmin) {
  const int wg = wq >> 2, w = wq & 3;
  const int g = lane >> 2, t = lane & 3, mi = lane >> 3, r = lane & 7;
  const uint32_t T0 = (2 * t > g) ? 0xFFFFFFFFu : 0u, T1 = (2 * t + 1 > g) ? 0xFFFFFFFFu : 0u;
  const uint32_t tri = (T0 & 0xFFFFu) | (T1 & 0xFFFF0000u);
  const uint32_t rowQ = stg + (mi >> 1) * PLANE + (16 * wq + r + 8 * (mi & 1)) * 16;
  const uint32_t rowQ8 = stg + 2 * PLANE + (16 * wq + (lane & 15)) * 16;
  constexpr uint32_t S16 = SEG >> 4, P16 = PLANE >> 4;
  const uint32_t aE = ((ring + wg * 1024) & 0x3FFFF) >> 4, aO = ((ring + wg * SEG + (wg ^ 1) * 1024) & 0x3FFFF) >> 4;
  const uint32_t kE = aE | (P16 << 16), kO = aO | (P16 << 16);
  const uint32_t vE = aE | ((128 >> 4) << 16), vO = aO | ((128 >> 4) << 16);
  uint32_t a[4], a8[2];
  float sX[32], sY[32], o[12];
  uint32_t pA[16], pB[16];
  mbar_wait(bars + 8 * B_HALO, 0);
  ldsm4(a[0], a[1], a[2], a[3], rowQ);
  ldsm2(a8[0], a8[1], rowQ8);
  if (t >= 2) { a8[0] = 0u; a8[1] = 0u; }
  wg_fence();
  mma_qk(sX, a, a8, kE, kE + 2 * P16);
  mma_qk(sY, a, a8, kE + 2 * S16, kE + 2 * S16 + 2 * P16);
  wg_commit();
#pragma unroll 1
  for (int h = 0; h < 4; ++h) {
    const int p = h >> 1, odd = h & 1;
    const uint32_t km = (p * 11 + odd * 3) * P16, kt = (p * 11 + 2) * P16, vp = (p * 11 + 5 + odd * 3) * P16;
    SoftmaxState st;
    ATT_T(0);
    wg_wait<0>();
    reg_fence(sX); reg_fence(sY);
    ATT_T(1);
    if (cmin > 0) {
#pragma unroll
      for (int i = 0; i < 32; ++i) sX[i] = NEG_INF;
    }
#pragma unroll
    for (int b = 0; b < 4; ++b) {
      const uint32_t gt = b > w ? 0xFFFFFFFFu : 0u, ge = b >= w ? 0xFFFFFFFFu : 0u, eq = ge & ~gt;
      const uint32_t e0 = gt | (eq & T0), e1 = gt | (eq & T1);
      sX[8 * b + 0] = fsel(sX[8 * b + 0], sY[8 * b + 0], e0);
      sX[8 * b + 1] = fsel(sX[8 * b + 1], sY[8 * b + 1], e1);
      sX[8 * b + 2] = fsel(sX[8 * b + 2], sY[8 * b + 2], gt);
      sX[8 * b + 3] = fsel(sX[8 * b + 3], sY[8 * b + 3], gt);
      sX[8 * b + 4] = fsel(sX[8 * b + 4], sY[8 * b + 4], ge);
      sX[8 * b + 5] = fsel(sX[8 * b + 5], sY[8 * b + 5], ge);
      sX[8 * b + 6] = fsel(sX[8 * b + 6], sY[8 * b + 6], e0);
      sX[8 * b + 7] = fsel(sX[8 * b + 7], sY[8 * b + 7], e1);
    }
    wg_fence();
    mma_qk(sY, a, a8, kO + km, kO + kt);
    wg_commit();
    ATT_T(2);
    row_max(sX, st.m0, st.m1);
    st.n0 = -st.m0 * SM_C; st.n1 = -st.m1 * SM_C;
    ATT_T(3);
    step<false>(sX, sY, o, pA, st, wg + 1 >= cmin);
    ATT_T(4);
#pragma unroll
    for (int b = 0; b < 4; ++b) {
      const uint32_t gt = b > w ? 0xFFFFFFFFu : 0u, ge = b >= w ? 0xFFFFFFFFu : 0u, eq = ge & ~gt;
      const uint32_t mt = gt | (eq & tri);
      pB[4 * b + 0] = pA[4 * b + 0] & ~mt; pA[4 * b + 0] &= mt;
      pB[4 * b + 1] = pA[4 * b + 1] & ~gt; pA[4 * b + 1] &= gt;
      pB[4 * b + 2] = pA[4 * b + 2] & ~ge; pA[4 * b + 2] &= ge;
      pB[4 * b + 3] = pA[4 * b + 3] & ~mt; pA[4 * b + 3] &= mt;
    }
    wg_fence();
    mma_qk(sX, a, a8, kE + S16 + km, kE + S16 + kt);
    mma_pv<true>(o, pA, vE + vp);
    mma_pv<false>(o, pB, vE + 2 * S16 + vp);
    wg_commit();
    ATT_T(5);
    step<true>(sY, sX, o, pB, st, wg + 2 >= cmin);
    ATT_T(6);
    wg_fence();
    mma_qk(sY, a, a8, kO + S16 + km, kO + S16 + kt);
    mma_pv<false>(o, pB, vO + vp);
    wg_commit();
    ATT_T(7);
    step<true>(sX, sY, o, pA, st, wg + 3 >= cmin);
    ATT_T(8);
    const int hn = h < 3 ? h + 1 : h, pn = hn >> 1, on = hn & 1;
    const uint32_t kmn = (pn * 11 + on * 3) * P16, ktn = (pn * 11 + 2) * P16;
    if (h == 1) mbar_wait(bars + 8 * (B_HALO + 1), 0);
    ldsm4(a[0], a[1], a[2], a[3], rowQ + (pn * 5 + on * 3) * PLANE);
    ldsm2(a8[0], a8[1], rowQ8 + pn * 5 * PLANE);
    if ((t >= 2) != (on != 0)) { a8[0] = 0u; a8[1] = 0u; }
    wg_fence();
    mma_pv<false>(o, pA, vE + S16 + vp);
    mma_qk(sX, a, a8, kE + kmn, kE + ktn);
    wg_commit();
    ATT_T(9);
    sm_exp<0, 8>(sY, pB, st.n0, st.n1);
    ATT_T(10);
    wg_wait<0>();
    reg_fence(o); reg_fence(sX);
    rescale(o, st.al0, st.al1);
    wg_fence();
    mma_pv<false>(o, pB, vO + S16 + vp);
    wg_commit();
    wg_fence();
    mma_qk(sY, a, a8, kE + 2 * S16 + kmn, kE + 2 * S16 + ktn);
    wg_commit();
    ATT_T(11);
    wg_wait<1>();
    reg_fence(o);
    const int src = (lane & ~3) | (odd ? 0 : 2);
    const float i0 = __fdividef(1.f, __shfl_sync(0xffffffffu, o[8], src)), i1 = __fdividef(1.f, __shfl_sync(0xffffffffu, o[10], src));
    const uint32_t ob = stg + p * 5 * PLANE + (16 * wq + g) * 16 + t * 4;
    const uint32_t om = ob + odd * 3 * PLANE;
    sts32(om, pack_bf16(o[0] * i0, o[1] * i0)); sts32(om + 128, pack_bf16(o[2] * i1, o[3] * i1));
    sts32(om + PLANE, pack_bf16(o[4] * i0, o[5] * i0)); sts32(om + PLANE + 128, pack_bf16(o[6] * i1, o[7] * i1));
    if ((t >= 2) == (odd != 0)) { sts32(ob + 2 * PLANE, pack_bf16(o[8] * i0, o[9] * i0)); sts32(ob + 2 * PLANE + 128, pack_bf16(o[10] * i1, o[11] * i1)); }
    if (odd) {
      fence_async_smem();
      __syncwarp();
      if (lane == 0) mbar_arrive(bars + 8 * (B_OST + p));
    }
    ATT_T(12);
  }
  wg_wait<0>();
  reg_fence(sX); reg_fence(sY);
  __syncwarp();
}

#define PRE_AFTER 5
struct Params {
  const uint16_t* q; const uint16_t* k; const uint16_t* v; const uint16_t* shift_k; const uint16_t* ssm_k;
  const uint16_t* ssm_D; const uint16_t* x; const uint16_t* wqkv; const uint16_t* wo; uint16_t* out;
};

DEVINL unsigned* cnt(int i) { return &g_cnt[i * CS]; }

DEVINL void finish_role() {
  unsigned old = atomicAdd(cnt(C_DONE), 1u);
  if (old == 255u) {
    __threadfence();
    for (int i = 0; i < C_NUM; ++i) *cnt(i) = 0u;
    __threadfence();
  }
}

__global__ void __cluster_dims__(2, 1, 1) __launch_bounds__(512, 1)
h3_swa_fused_kernel(const __grid_constant__ CUtensorMap tmX, const __grid_constant__ CUtensorMap tmW128,
                    const __grid_constant__ CUtensorMap tmW32, const __grid_constant__ CUtensorMap tmWo,
                    const __grid_constant__ CUtensorMap tmOut, const __grid_constant__ CUtensorMap tmKT,
                    const __grid_constant__ CUtensorMap tmKin, const __grid_constant__ CUtensorMap tmVin,
                    const Params prm) {
  extern __shared__ uint8_t smem_raw[];
  const uint32_t sb = ((uint32_t)__cvta_generic_to_shared(smem_raw) + 1023u) & ~1023u;
  const uint32_t bars = sb + OFF_BAR;
  const int tid = threadIdx.x, warp = tid >> 5, lane = tid & 31, wg = tid >> 7;
  const int cta = blockIdx.x;
  const uint32_t rank = cta & 1;
  const int g8 = (cta >> 1) & 7, rp = cta >> 4;
  const int rb = 2 * rp + rank;
  const int rb2 = 2 * rp + (g8 & 1);
  const int c2 = 2 * (g8 >> 1) + rank;
  const int tau = cta & 15, jt = cta >> 4;

  if (tid < 160) prefetch_line(prm.x + ((size_t)cta * 160 + tid) * 64);
  else if (tid < 310) prefetch_line(prm.wqkv + ((size_t)cta * 150 + tid - 160) * 64);
  if (tid == 384) { prefetch_tmap(&tmX); prefetch_tmap(&tmW128); prefetch_tmap(&tmW32); }
  if (tid == 256) { prefetch_tmap(&tmKin); prefetch_tmap(&tmVin); }
  if (tid == 0) {
    PROF(0);
    for (int i = 0; i < NST1; ++i) { mbar_init(bars + 8 * (B_FULL1 + i), 1); mbar_init(bars + 8 * (B_EMPTY1 + i), 16); }
    mbar_init(bars + 8 * B_RINGFREE, 1);
    mbar_init(bars + 8 * B_HALO, 1); mbar_init(bars + 8 * (B_HALO + 1), 1);
    for (int i = 0; i < NST2; ++i) { mbar_init(bars + 8 * (B_FULL2 + i), 1); mbar_init(bars + 8 * (B_EMPTY2 + i), 16); }
    mbar_init(bars + 8 * B_U, 1);
    mbar_init(bars + 8 * B_KVST, 8);
    mbar_init(bars + 8 * B_OST, 8); mbar_init(bars + 8 * (B_OST + 1), 8);
    mbar_init(bars + 8 * B_PRE, 1);
    mbar_init(bars + 8 * B_KTST, 4);
    mbar_init(bars + 8 * B_YST, 4); mbar_init(bars + 8 * (B_YST + 1), 4);
    mbar_init(bars + 8 * B_STGFREE, 1);
    asm volatile("fence.mbarrier_init.release.cluster;" ::: "memory");
  }
  __syncthreads();
  asm volatile("barrier.cluster.arrive.relaxed.aligned;\nbarrier.cluster.wait.aligned;" ::: "memory");

  if (wg == 3) {
    asm volatile("setmaxnreg.dec.sync.aligned.u32 40;");
    if (warp == 12 && lane == 0) {
      PROF(15);
      for (int it = 0; it < 10; ++it) {
        const int s = it % NST1;
        if (it >= NST1) mbar_wait(bars + 8 * (B_EMPTY1 + s), ((it / NST1) - 1) & 1);
        PROF(44 + it);
        const uint32_t st = sb + s * ST1, fb = bars + 8 * (B_FULL1 + s);
        mbar_expect(fb, ST1);
        tma2d(st, &tmX, it * 64, rb * 128, fb);
        tma3d_mc(st + ST1_B128 + rank * 12288, &tmW128, g8 * 80, it * 64 + rank * 32, 0, fb);
        tma3d_mc(st + ST1_B32 + rank * 3072, &tmW32, g8 * 80 + 64, it * 64 + rank * 32, 0, fb);
        if (it == PRE_AFTER) {
          mbar_expect(bars + 8 * B_PRE, 131 * 160 + 128 * 160);
          tma2d(sb + OFF_F, &tmKin, jt * 80, tau * 128 - 3, bars + 8 * B_PRE);
          tma2d(sb + OFF_F + 21120, &tmVin, jt * 80, tau * 128, bars + 8 * B_PRE);
        }
      }
      PROF(1);
      mbar_wait(bars + 8 * B_RINGFREE, 0);
      for (int p = 0; p < 2; ++p) {
        const uint32_t hb = bars + 8 * (B_HALO + p);
        if (rb == 0) { mbar_arrive(hb); continue; }
        poll_ge(cnt(C_KV + (g8 * 16 + rb - 1) * 2 + p), 1);
        if (rb >= 2) poll_ge(cnt(C_KV + (g8 * 16 + rb - 2) * 2 + p), 1);
        if (p == 0) PROF(2);
        mbar_expect(hb, (rb >= 2 ? 2 : 1) * PAIR);
        bulk_load(sb + SEG + p * PAIR, g_kv + (size_t)(g8 * 16 + rb - 1) * (SEG / 2) + p * (PAIR / 2), PAIR, hb);
        if (rb >= 2) bulk_load(sb + p * PAIR, g_kv + (size_t)(g8 * 16 + rb - 2) * (SEG / 2) + p * (PAIR / 2), PAIR, hb);
      }
      for (int it = 0; it < 8; ++it) {
        const int s = it & 3, p = it >> 2;
        mbar_wait(bars + 8 * (B_EMPTY2 + s), p);
        const uint32_t fb = bars + 8 * (B_FULL2 + s);
        mbar_expect(fb, ST2);
        tma5d(sb + s * ST2 + 20480, &tmWo, 0, 0, p, 2 * s, c2 * 5, fb);
        if (s == 0) { if (p == 0) PROF(3); poll_ge(cnt(C_O + rb2 * 2 + p), 8); if (p == 1) PROF(4); }
        bulk_load_mc(sb + s * ST2 + rank * 10240, g_o + (size_t)(rb2 * 80 + p * 40 + (2 * s + rank) * 5) * 1024, 10240, fb);
      }
      finish_role();
    } else if (warp == 13 && lane == 0) {
      prefetch_tmap(&tmWo); prefetch_tmap(&tmOut);
      mbar_wait(bars + 8 * B_KVST, 0);
      uint16_t* kd = g_kv + (size_t)(g8 * 16 + rb) * (SEG / 2);
      bulk_store(kd, sb + 2 * SEG, PAIR); bulk_commit();
      bulk_store(kd + PAIR / 2, sb + 2 * SEG + PAIR, PAIR); bulk_commit();
      bulk_wait<1>(); red_publish(cnt(C_KV + (g8 * 16 + rb) * 2));
      bulk_wait<0>(); red_publish(cnt(C_KV + (g8 * 16 + rb) * 2 + 1));
      PROF(24);
      for (int p = 0; p < 2; ++p) {
        mbar_wait(bars + 8 * (B_OST + p), 0);
        bulk_store(g_o + (size_t)(rb * 80 + p * 40 + g8 * 5) * 1024, sb + OFF_STG + p * 10240, 10240);
        bulk_commit(); bulk_wait<0>();
        red_publish(cnt(C_O + rb * 2 + p));
      }
      PROF(20);
    } else if (warp == 14 && lane == 0) {
      prefetch_tmap(&tmKT);
      mbar_wait(bars + 8 * B_KTST, 0);
      tma3d_store(&tmKT, 64 * tau, 0, jt * 80, sb + OFF_STG);
      bulk_commit(); bulk_wait<0>();
      mbar_arrive(bars + 8 * B_STGFREE);
      red_publish(cnt(C_PRE + jt));
      PROF(8);
      poll_ge(cnt(C_PRE + jt), 16);
      mbar_expect(bars + 8 * B_U, 5 * 4096);
      for (int i = 0; i < 10; ++i)
        bulk_load(sb + OFF_U + (i >> 1) * CH_U + (i & 1) * 2176 + 128, g_kvT + (size_t)(cta * 5) * SEQ + i * 1024, 2048, bars + 8 * B_U);
      PROF(9);
      mbar_wait(bars + 8 * B_YST, 0);
      for (int i = 0; i < 4; ++i) bulk_store(g_yT + (size_t)(cta * 5 + i) * SEQ, sb + OFF_U + i * CH_U, 4096);
      bulk_commit(); bulk_wait<0>();
      red_publish(cnt(C_Y + jt), 4);
      mbar_wait(bars + 8 * (B_YST + 1), 0);
      bulk_store(g_yT + (size_t)(cta * 5 + 4) * SEQ, sb + OFF_F + 4 * CH_F, 4096);
      bulk_commit(); bulk_wait<0>();
      red_publish(cnt(C_Y + jt), 1);
      PROF(11);
    }
  } else if (wg == 2) {
    asm volatile("setmaxnreg.inc.sync.aligned.u32 136;");
    const int ct = tid - 256, wc = warp - 8;
    const int t0 = tau * 128, c0 = jt * 80;
    const int mi = lane >> 3, r = lane & 7, g = lane >> 2, t = lane & 3;
    const uint32_t U = sb + OFF_U, F = sb + OFF_F;
    if (ct == 0) PROF(14);
    mbar_wait(bars + 8 * B_FULL1, 0);
#pragma unroll 1
    for (int i = ct; i < 259 * 2; i += 128) {
      const int row = i >> 1;
      const uint16_t* base = row < 131 ? prm.k + (size_t)max(t0 - 3 + row, 0) * DM : prm.v + (size_t)(t0 + row - 131) * DM;
      prefetch_line(base + c0 + (i & 1) * 64);
      if ((i & 1) && (c0 * 2) % 128 > 64) prefetch_line(base + c0 + 79);
    }
    if (ct < 32) for (int i = ct; i < 160; i += 32) prefetch_line(prm.ssm_k + (size_t)cta * 5 * SEQ + i * 64);
    {
      const uint32_t KT = F, VT = F + 21120;
      uint4 wv0[4];
#pragma unroll
      for (int u = 0; u < 4; ++u) wv0[u] = ldg_nc(prm.shift_k + (size_t)(c0 + (ct % 10) * 8 + 2 * u) * 4);
      mbar_wait(bars + 8 * B_PRE, 0);
      if (ct == 0) PROF(5);
#pragma unroll 1
      for (int item = ct; item < 160; item += 128) {
        int c = ct % 10, seg = ct / 10;
        if (item >= 128) {
          const int j = item - 128;
          const int idx = 128 + j; c = idx % 10; seg = idx / 10;
#pragma unroll
          for (int u = 0; u < 4; ++u) wv0[u] = ldg_nc(prm.shift_k + (size_t)(c0 + c * 8 + 2 * u) * 4);
        }
        uint32_t W[4][4];
#pragma unroll
        for (int u = 0; u < 4; ++u) {
          W[0][u] = __byte_perm(wv0[u].x, wv0[u].z, 0x5410); W[1][u] = __byte_perm(wv0[u].x, wv0[u].z, 0x7632);
          W[2][u] = __byte_perm(wv0[u].y, wv0[u].w, 0x5410); W[3][u] = __byte_perm(wv0[u].y, wv0[u].w, 0x7632);
        }
        const uint32_t ka = KT + seg * 8 * 160 + c * 16, va = VT + seg * 8 * 160 + c * 16;
        uint4 k0 = lds128(ka), k1 = lds128(ka + 160), k2 = lds128(ka + 320);
#pragma unroll
        for (int i = 0; i < 8; ++i) {
          const uint4 k3 = lds128(ka + (i + 3) * 160), vv = lds128(va + i * 160);
          uint32_t res[4];
#pragma unroll
          for (int u = 0; u < 4; ++u) {
            uint32_t acc = hadd2(hmul2((&k0.x)[u], W[3][u]), hmul2((&k1.x)[u], W[2][u]));
            acc = hadd2(acc, hmul2((&k2.x)[u], W[1][u]));
            acc = hadd2(acc, hmul2((&k3.x)[u], W[0][u]));
            res[u] = hmul2(acc, (&vv.x)[u]);
          }
          sts128(U + (seg * 8 + i) * 160 + c * 16, make_uint4(res[0], res[1], res[2], res[3]));
          k0 = k1; k1 = k2; k2 = k3;
        }
      }
    }
    if (ct == 0) PROF(6);
    named_sync(3, 128);
#pragma unroll 1
    for (int it = wc; it < 40; it += 4) {
      const int c = it % 10, rest = it / 10, h = rest & 1, iq = rest >> 1;
      const int tl = 16 * (4 * iq + (r >> 1)) + 15 - (8 * h + 2 * mi + (r & 1));
      uint4 v4;
      ldsm4t(v4.x, v4.y, v4.z, v4.w, U + tl * 160 + c * 16);
      sts128(sb + OFF_STG + (c * 8 + g) * 256 + h * 128 + (4 * iq + t) * 16, v4);
    }
    fence_async_smem();
    __syncwarp();
    if (lane == 0) mbar_arrive(bars + 8 * B_KTST);
    if (ct == 0) PROF(7);
    named_sync(3, 128);
    if (ct < 80) sts128(U + (ct >> 4) * CH_U + ((ct >> 3) & 1) * 2176 + (ct & 7) * 16, make_uint4(0, 0, 0, 0));
    {
      const int chb = cta * 5;
      uint4 fv[10]; uint32_t pv[10];
#pragma unroll
      for (int i = 0; i < 10; ++i) {
        const int cl = i >> 1, qq = ct + (i & 1) * 128;
        const uint16_t* src = prm.ssm_k + (size_t)(chb + cl) * SEQ + qq * 8;
        fv[i] = ldg_nc(src);
        pv[i] = qq > 0 ? (uint32_t)__ldg(src - 1) : 0u;
      }
#pragma unroll
      for (int i = 0; i < 10; ++i) {
        const int cl = i >> 1, qq = ct + (i & 1) * 128;
        const uint32_t a = F + cl * CH_F + 32 + qq * 16;
        sts128(a, fv[i]);
        sts128(a + 4160, make_uint4(__byte_perm(pv[i], fv[i].x, 0x5410), __byte_perm(fv[i].x, fv[i].y, 0x5432),
                                    __byte_perm(fv[i].y, fv[i].z, 0x5432), __byte_perm(fv[i].z, fv[i].w, 0x5432)));
      }
      if (ct < 20) sts128(F + (ct >> 2) * CH_F + ((ct >> 1) & 1) * 4160 + (ct & 1) * 16, make_uint4(0, 0, 0, 0));
    }
    named_sync(3, 128);
    mbar_wait(bars + 8 * B_U, 0);
    if (ct == 0) PROF(10);
#pragma unroll 1
    for (int pass = 0; pass < 2; ++pass) {
      const int cl = pass == 0 ? wc : 4;
      const int r0 = pass == 0 ? 0 : 2 * wc, r1 = pass == 0 ? 8 : 2 * wc + 2;
      const uint32_t Ub = U + cl * CH_U, Fb = F + cl * CH_F;
      const uint32_t laneU = Ub + (mi & 1) * 2176 + (8 + 8 * (mi >> 1) + r) * 16;
      const uint32_t laneF = (g & 1) ? Fb + 4160 + 2 * (17 - g + 2 * t) : Fb + 2 * (16 - g + 2 * t);
      float acc[16][4];
#pragma unroll
      for (int i = 0; i < 16; ++i) { acc[i][0] = 0.f; acc[i][1] = 0.f; acc[i][2] = 0.f; acc[i][3] = 0.f; }
#pragma unroll 1
      for (int rho = r0; rho < r1; ++rho) {
        uint32_t uf[16][2];
#pragma unroll
        for (int jj = 0; jj < 8; ++jj)
          ldsm4(uf[2 * jj][0], uf[2 * jj][1], uf[2 * jj + 1][0], uf[2 * jj + 1][1], laneU + jj * 256 - rho * 16);
        const uint32_t fb = laneF + 32 * rho;
#pragma unroll
        for (int mu = 0; mu < 16; ++mu) {
          const uint32_t a0 = lds32(fb + 256 * mu), a1 = lds32(fb + 256 * mu - 16), a2 = lds32(fb + 256 * mu + 16);
#pragma unroll
          for (int i = mu; i < 16; ++i) mma16816(acc[i], a0, a1, a2, a0, uf[i - mu][0], uf[i - mu][1]);
        }
      }
      const uint32_t dv = (uint32_t)__ldg(prm.ssm_D + cta * 5 + cl);
      const uint32_t D2 = dv | (dv << 16);
      if (pass == 0) {
        uint32_t res[8][4];
#pragma unroll
        for (int jj = 0; jj < 8; ++jj) {
          uint32_t u0, u1, u2, u3;
          ldsm4t(u0, u1, u2, u3, laneU + jj * 256);
          res[jj][0] = hadd2(pack_bf16(acc[2 * jj][0], acc[2 * jj][1]), hmul2(u0, D2));
          res[jj][1] = hadd2(pack_bf16(acc[2 * jj][2], acc[2 * jj][3]), hmul2(u1, D2));
          res[jj][2] = hadd2(pack_bf16(acc[2 * jj + 1][0], acc[2 * jj + 1][1]), hmul2(u2, D2));
          res[jj][3] = hadd2(pack_bf16(acc[2 * jj + 1][2], acc[2 * jj + 1][3]), hmul2(u3, D2));
        }
        __syncwarp();
#pragma unroll
        for (int jj = 0; jj < 8; ++jj)
          stsm4t(Ub + ((8 * (2 * jj + (mi >> 1)) + r) * 16 + 8 * (mi & 1)) * 2, res[jj][0], res[jj][1], res[jj][2], res[jj][3]);
        fence_async_smem();
        __syncwarp();
        if (lane == 0) mbar_arrive(bars + 8 * B_YST);
      } else {
        const uint32_t rbuf = F + wc * CH_F + lane * 16;
#pragma unroll
        for (int i = 0; i < 16; ++i)
          sts128(rbuf + i * 512, make_uint4(__float_as_uint(acc[i][0]), __float_as_uint(acc[i][1]),
                                            __float_as_uint(acc[i][2]), __float_as_uint(acc[i][3])));
        named_sync(3, 128);
        uint32_t res[2][4];
#pragma unroll
        for (int jj = 0; jj < 2; ++jj) {
          float sum[2][4];
#pragma unroll
          for (int hh = 0; hh < 2; ++hh) {
            const int tile = 4 * wc + 2 * jj + hh;
            sum[hh][0] = 0.f; sum[hh][1] = 0.f; sum[hh][2] = 0.f; sum[hh][3] = 0.f;
#pragma unroll
            for (int w = 0; w < 4; ++w) {
              const uint4 x = lds128(F + w * CH_F + lane * 16 + tile * 512);
              sum[hh][0] += __uint_as_float(x.x); sum[hh][1] += __uint_as_float(x.y);
              sum[hh][2] += __uint_as_float(x.z); sum[hh][3] += __uint_as_float(x.w);
            }
          }
          uint32_t u0, u1, u2, u3;
          ldsm4t(u0, u1, u2, u3, laneU + (2 * wc + jj) * 256);
          res[jj][0] = hadd2(pack_bf16(sum[0][0], sum[0][1]), hmul2(u0, D2));
          res[jj][1] = hadd2(pack_bf16(sum[0][2], sum[0][3]), hmul2(u1, D2));
          res[jj][2] = hadd2(pack_bf16(sum[1][0], sum[1][1]), hmul2(u2, D2));
          res[jj][3] = hadd2(pack_bf16(sum[1][2], sum[1][3]), hmul2(u3, D2));
        }
#pragma unroll
        for (int jj = 0; jj < 2; ++jj)
          stsm4t(F + 4 * CH_F + ((8 * (2 * (2 * wc + jj) + (mi >> 1)) + r) * 16 + 8 * (mi & 1)) * 2, res[jj][0], res[jj][1], res[jj][2], res[jj][3]);
        fence_async_smem();
        __syncwarp();
        if (lane == 0) mbar_arrive(bars + 8 * (B_YST + 1));
      }
    }
    uint4 qv[10];
#pragma unroll
    for (int i = 0; i < 10; ++i) {
      const int idx = ct + 128 * i, row = idx / 10, c = idx % 10;
      qv[i] = ldg_nc(prm.q + (size_t)(t0 + row) * DM + c0 + c * 8);
    }
    if (ct == 0) { poll_ge(cnt(C_Y + jt), 80); finish_role(); PROF(12); }
    named_sync(3, 128);
    const uint32_t YT = sb + OFF_U, YN = sb + OFF_F + 1024;
#pragma unroll
    for (int i = 0; i < 10; ++i) {
      const int idx = ct + 128 * i, ch = idx >> 4, cq = idx & 15;
      sts128(YT + ch * 272 + cq * 16, ldg_cg(g_yT + (size_t)(c0 + ch) * SEQ + t0 + cq * 8));
    }
    named_sync(3, 128);
#pragma unroll 1
    for (int it = wc; it < 40; it += 4) {
      const int c = it % 10, tq = it / 10;
      uint32_t x0, x1, x2, x3;
      ldsm4t(x0, x1, x2, x3, YT + (8 * c + r) * 272 + (4 * tq + mi) * 16);
      const int s = (8 * (4 * tq + mi) + r) ^ 15;
      stsm4(YN + s * 176 + c * 16, x0, x1, x2, x3);
    }
    named_sync(3, 128);
#pragma unroll
    for (int i = 0; i < 10; ++i) {
      const int idx = ct + 128 * i, row = idx / 10, c = idx % 10;
      const uint4 y = lds128(YN + row * 176 + c * 16);
      stg128(prm.out + (size_t)(t0 + row) * (2 * DM) + c0 + c * 8,
             make_uint4(hmul2(qv[i].x, y.x), hmul2(qv[i].y, y.y), hmul2(qv[i].z, y.z), hmul2(qv[i].w, y.w)));
    }
    if (ct == 0) PROF(13);
  } else {
    asm volatile("setmaxnreg.inc.sync.aligned.u32 168;");
    const int wq = __shfl_sync(0xffffffffu, warp, 0);
    const int mi = lane >> 3, r = lane & 7;
    const uint32_t stg = sb + OFF_STG;
    {
      float acc1[96], acc2[24];
#pragma unroll 1
      for (int it = 0; it < 10; ++it) {
        const int s = it % NST1;
        mbar_wait(bars + 8 * (B_FULL1 + s), (it / NST1) & 1);
        if (tid == 0) PROF(32 + it);
        const uint32_t st = sb + s * ST1;
        wg_fence();
#pragma unroll
        for (int kk = 0; kk < 4; ++kk) {
          const uint64_t da = make_desc(st + wg * 8192 + kk * 32, 16, 1024, 1);
          const uint64_t db1 = make_desc(st + ST1_B128 + (kk >> 1) * 12288 + (kk & 1) * 2048, 4096, 1024, 1);
          const uint64_t db2 = make_desc(st + ST1_B32 + (kk >> 1) * 3072 + (kk & 1) * 512, 1024, 256, 3);
          wgmma_n192(acc1, da, db1, (it | kk) != 0);
          wgmma_n48(acc2, da, db2, (it | kk) != 0);
        }
        wg_commit();
        wg_wait<0>();
        if (it + NST1 < 10 && lane < 2) mbar_arrive_cta(bars + 8 * (B_EMPTY1 + s), lane);
      }
      reg_fence(acc1); reg_fence(acc2);
      if (tid == 0) PROF(17);
      named_sync(1, 256);
      if (tid == 0) mbar_arrive(bars + 8 * B_RINGFREE);
      const uint32_t rowo = (16 * wq + 8 * (mi & 1) + r) * 16;
      const int t4 = lane & 3;
#pragma unroll
      for (int kv = 0; kv < 2; ++kv) {
#pragma unroll
        for (int tp = 0; tp < 5; ++tp) {
          uint32_t w[4];
#pragma unroll
          for (int hh = 0; hh < 2; ++hh) {
            const int tile = 2 * tp + hh;
            if (tile < 8) {
              const int o = 32 * (kv + 1) + 4 * tile;
              w[2 * hh] = pack_bf16(acc1[o], acc1[o + 1]); w[2 * hh + 1] = pack_bf16(acc1[o + 2], acc1[o + 3]);
            } else {
              const int o = 8 * (kv + 1) + 4 * (tile - 8);
              w[2 * hh] = pack_bf16(acc2[o], acc2[o + 1]); w[2 * hh + 1] = pack_bf16(acc2[o + 2], acc2[o + 3]);
            }
          }
          const int tA = 2 * tp, tB = 2 * tp + 1;
          const int plA = (tA / 5) * 11 + (kv ? 5 : 0) + tA % 5, plB = (tB / 5) * 11 + (kv ? 5 : 0) + tB % 5;
          if (kv == 1 && (tA % 5 == 2 || tB % 5 == 2)) {
            const int hh = (tA % 5 == 2) ? 0 : 1, pr = (hh ? tB : tA) / 5;
            const uint32_t x0 = w[2 * hh], x1 = w[2 * hh + 1];
            const uint32_t oneE = t4 == 2 ? 0x00003F80u : 0u, oneO = t4 == 0 ? 0x00003F80u : 0u;
            stsm2(sb + 2 * SEG + (pr * 11 + 10) * PLANE + (16 * wq + (lane & 15)) * 16, t4 >= 2 ? x0 : oneO, t4 >= 2 ? x1 : oneO);
            w[2 * hh] = t4 < 2 ? x0 : oneE; w[2 * hh + 1] = t4 < 2 ? x1 : oneE;
          }
          stsm4(sb + 2 * SEG + rowo + ((mi >> 1) ? plB : plA) * PLANE, w[0], w[1], w[2], w[3]);
        }
      }
      fence_async_smem();
      __syncwarp();
      if (lane == 0) mbar_arrive(bars + 8 * B_KVST);
      mbar_wait(bars + 8 * B_STGFREE, 0);
      const uint32_t rq = stg + rowo + (mi >> 1) * PLANE;
#pragma unroll
      for (int tp = 0; tp < 4; ++tp)
        stsm4(rq + tp * 2 * PLANE, pack_bf16(acc1[8 * tp], acc1[8 * tp + 1]), pack_bf16(acc1[8 * tp + 2], acc1[8 * tp + 3]),
              pack_bf16(acc1[8 * tp + 4], acc1[8 * tp + 5]), pack_bf16(acc1[8 * tp + 6], acc1[8 * tp + 7]));
      stsm4(rq + 8 * PLANE, pack_bf16(acc2[0], acc2[1]), pack_bf16(acc2[2], acc2[3]), pack_bf16(acc2[4], acc2[5]), pack_bf16(acc2[6], acc2[7]));
    }
    if (rb < 2) {
      const int nz = (2 - rb) * (SEG / 16);
#pragma unroll 1
      for (int i = tid; i < nz; i += 256) sts128(sb + i * 16, make_uint4(0, 0, 0, 0));
      fence_async_smem();
    }
    named_sync(2, 256);
    if (tid == 0) PROF(18);
    attn_all(sb, stg, bars, wq, lane, rb >= 2 ? 0 : 4 - 2 * rb);
    if (tid == 0) PROF(19);
    if (lane < 2 * NST2) mbar_arrive_cta(bars + 8 * (B_EMPTY2 + (lane >> 1)), lane & 1);
    float acc[40];
#pragma unroll 1
    for (int it = 0; it < 8; ++it) {
      const int s = it & 3;
      mbar_wait(bars + 8 * (B_FULL2 + s), it >> 2);
      if (it == 0 && tid == 0) PROF(21);
      if (it == 4 && tid == 0) PROF(25);
      const uint32_t st = sb + s * ST2;
      wg_fence();
#pragma unroll
      for (int kk = 0; kk < 5; ++kk)
        wgmma_n80(acc, make_desc(st + wg * 1024 + kk * 2 * PLANE, PLANE, 128, 0), make_desc(st + 20480 + kk * 512, 2560, 256, 3), (it | kk) != 0);
      wg_commit();
      wg_wait<0>();
      if (it < 4 && lane < 2) mbar_arrive_cta(bars + 8 * (B_EMPTY2 + s), lane);
    }
    reg_fence(acc);
    if (tid == 0) PROF(22);
    named_sync(1, 256);
    {
      const uint32_t rowa = sb + (16 * wq + 8 * (mi & 1) + r) * 160 + (mi >> 1) * 16;
#pragma unroll
      for (int tp = 0; tp < 5; ++tp)
        stsm4(rowa + tp * 32, pack_bf16(acc[8 * tp], acc[8 * tp + 1]), pack_bf16(acc[8 * tp + 2], acc[8 * tp + 3]),
              pack_bf16(acc[8 * tp + 4], acc[8 * tp + 5]), pack_bf16(acc[8 * tp + 6], acc[8 * tp + 7]));
      fence_async_smem();
      __syncwarp();
      if (lane == 0) {
        tma2d_store(&tmOut, DM + c2 * 80, rb2 * 128 + 16 * wq, sb + wq * 2560);
        bulk_commit();
        bulk_wait0_read();
      }
    }
    if (tid == 0) PROF(23);
  }
}

typedef CUresult (*EncodeFn)(CUtensorMap*, CUtensorMapDataType, cuuint32_t, void*, const cuuint64_t*, const cuuint64_t*,
                             const cuuint32_t*, const cuuint32_t*, CUtensorMapInterleave, CUtensorMapSwizzle,
                             CUtensorMapL2promotion, CUtensorMapFloatOOBfill);

CUtensorMap make_map(EncodeFn enc, const void* p, int rank, const cuuint64_t* dims, const cuuint64_t* strides,
                     const cuuint32_t* box, CUtensorMapSwizzle sw) {
  CUtensorMap m;
  const cuuint32_t es[5] = {1, 1, 1, 1, 1};
  enc(&m, CU_TENSOR_MAP_DATA_TYPE_BFLOAT16, rank, const_cast<void*>(p), dims, strides, box, es,
      CU_TENSOR_MAP_INTERLEAVE_NONE, sw, CU_TENSOR_MAP_L2_PROMOTION_L2_128B, CU_TENSOR_MAP_FLOAT_OOB_FILL_NONE);
  return m;
}

}

extern "C" void kernel_launch(void* const* d_in, const int* in_sizes, int n_in, void* d_out, int out_size) {
  (void)in_sizes; (void)n_in; (void)out_size;
  static EncodeFn enc = nullptr;
  static void* kt_ptr = nullptr;
  if (!enc) {
    void* fn = nullptr;
    cudaDriverEntryPointQueryResult qr;
    cudaGetDriverEntryPoint("cuTensorMapEncodeTiled", &fn, cudaEnableDefault, &qr);
    enc = (EncodeFn)fn;
    cudaGetSymbolAddress(&kt_ptr, g_kvT);
    cudaFuncSetAttribute(h3_swa_fused_kernel, cudaFuncAttributeMaxDynamicSharedMemorySize, SMEM_BYTES);
  }
  const void* x = d_in[6];
  const void* wqkv = d_in[7];
  const void* wo = d_in[8];
  CUtensorMap tmX, tmW128, tmW32, tmWo, tmOut, tmKT, tmKin, tmVin;
  { cuuint64_t d[2] = {640, 2048}, s[1] = {1280}; cuuint32_t b[2] = {64, 128};
    tmX = make_map(enc, x, 2, d, s, b, CU_TENSOR_MAP_SWIZZLE_128B); }
  { cuuint64_t d[3] = {640, 640, 3}, s[2] = {3840, 1280}; cuuint32_t b[3] = {64, 32, 3};
    tmW128 = make_map(enc, wqkv, 3, d, s, b, CU_TENSOR_MAP_SWIZZLE_128B); }
  { cuuint64_t d[3] = {640, 640, 3}, s[2] = {3840, 1280}; cuuint32_t b[3] = {16, 32, 3};
    tmW32 = make_map(enc, wqkv, 3, d, s, b, CU_TENSOR_MAP_SWIZZLE_32B); }
  {
    cuuint64_t d[5] = {16, 40, 2, 8, 40}, s[4] = {1280, 51200, 102400, 32}; cuuint32_t b[5] = {16, 40, 1, 2, 5};
    tmWo = make_map(enc, wo, 5, d, s, b, CU_TENSOR_MAP_SWIZZLE_32B); }
  { cuuint64_t d[2] = {1280, 2048}, s[1] = {2560}; cuuint32_t b[2] = {80, 16};
    tmOut = make_map(enc, d_out, 2, d, s, b, CU_TENSOR_MAP_SWIZZLE_NONE); }
  { cuuint64_t d[3] = {1024, 2, 640}, s[2] = {2048, 4096}; cuuint32_t b[3] = {64, 2, 80};
    tmKT = make_map(enc, kt_ptr, 3, d, s, b, CU_TENSOR_MAP_SWIZZLE_NONE); }
  { cuuint64_t d[2] = {640, 2048}, s[1] = {1280}; cuuint32_t b[2] = {80, 131};
    tmKin = make_map(enc, d_in[1], 2, d, s, b, CU_TENSOR_MAP_SWIZZLE_NONE); }
  { cuuint64_t d[2] = {640, 2048}, s[1] = {1280}; cuuint32_t b[2] = {80, 128};
    tmVin = make_map(enc, d_in[2], 2, d, s, b, CU_TENSOR_MAP_SWIZZLE_NONE); }
  Params prm;
  prm.q = (const uint16_t*)d_in[0]; prm.k = (const uint16_t*)d_in[1]; prm.v = (const uint16_t*)d_in[2];
  prm.x = (const uint16_t*)x; prm.wqkv = (const uint16_t*)wqkv; prm.wo = (const uint16_t*)wo;
  prm.shift_k = (const uint16_t*)d_in[3]; prm.ssm_k = (const uint16_t*)d_in[4];
  prm.ssm_D = (const uint16_t*)d_in[5]; prm.out = (uint16_t*)d_out;
  h3_swa_fused_kernel<<<128, 512, SMEM_BYTES>>>(tmX, tmW128, tmW32, tmWo, tmOut, tmKT, tmKin, tmVin, prm);
}
```

```cpp
#include <cuda_runtime.h>
#include <cuda.h>
#include <cuda_bf16.h>
#include <stdint.h>

#define DEVINL __device__ __forceinline__

namespace {

constexpr int SEQ = 2048;
constexpr int DM = 640;

constexpr int ST1 = 47104;
constexpr int ST1_B128 = 16384;
constexpr int ST1_B32 = 40960;
constexpr int NST1 = 4;
constexpr int ST2 = 33280;
constexpr int NST2 = 4;
constexpr int CH_U = 5120;
constexpr int UPL = 1280;
constexpr int CH_F = 8320;
constexpr int OFF_F = 3 * ST1;
constexpr int OFF_U = 4 * ST1;
constexpr int OFF_KT = OFF_F + 3 * CH_F;
constexpr int OFF_U4 = OFF_F + 5 * CH_F;
constexpr int OFF_STG = OFF_U + 21120;
constexpr int OFF_BAR = OFF_STG + 20480;
constexpr int SMEM_BYTES = OFF_BAR + 512;

constexpr int B_FULL1 = 0, B_EMPTY1 = 4, B_RINGFREE = 8, B_HALO = 9, B_FULL2 = 11, B_EMPTY2 = 15, B_U = 19, B_KVST = 20,
              B_OST = 21, B_PRE = 23, B_KTST = 24, B_U4 = 25, B_STGFREE = 26, B_FFREE = 27, B_CIN = 28, B_YST = 29, B_OPUB = 34, B_FRAW = 35;

__device__ __align__(1024) uint16_t g_kv[8 * 16 * 22 * 1024];
__device__ __align__(1024) uint16_t g_o[SEQ * DM];
__device__ __align__(1024) uint16_t g_kvT[DM * 2560];
__device__ __align__(1024) uint16_t g_yT[DM * SEQ];
__device__ __align__(1024) uint16_t g_woP[DM * DM];
constexpr int CS = 32;
constexpr int C_KV = 0, C_O = 256, C_PRE = 288, C_Y = 296, C_WO = 304, C_DONE = 312, C_NUM = 313;
__device__ unsigned g_cnt[C_NUM * CS];
__device__ unsigned g_err;
#define PROF(slot) do {} while (0)

#define POLL_SLEEP 0
DEVINL void mbar_init(uint32_t a, uint32_t c) { asm volatile("mbarrier.init.shared::cta.b64 [%0], %1;" ::"r"(a), "r"(c)); }
DEVINL void mbar_expect(uint32_t a, uint32_t b) {
  asm volatile("mbarrier.arrive.expect_tx.shared::cta.b64 _, [%0], %1;" ::"r"(a), "r"(b) : "memory");
}
DEVINL void mbar_arrive(uint32_t a) { asm volatile("mbarrier.arrive.shared::cta.b64 _, [%0];" ::"r"(a) : "memory"); }
DEVINL void mbar_arrive_cta(uint32_t a, uint32_t cta) {
  asm volatile("{\n.reg .b32 ra;\nmapa.shared::cluster.u32 ra, %0, %1;\nmbarrier.arrive.shared::cluster.b64 _, [ra];\n}"
               ::"r"(a), "r"(cta) : "memory");
}
DEVINL bool mbar_try(uint32_t a, uint32_t p) {
  uint32_t ok;
  asm volatile("{\n.reg .pred P;\nmbarrier.try_wait.parity.shared::cta.b64 P, [%1], %2;\nselp.u32 %0, 1, 0, P;\n}"
               : "=r"(ok) : "r"(a), "r"(p) : "memory");
  return ok;
}
DEVINL void mbar_wait(uint32_t a, uint32_t p) {
  if (mbar_try(a, p)) return;
  int n = 0;
  while (!mbar_try(a, p)) {
    if (++n > (1 << 18)) { g_err = 1; break; }
  }
}
DEVINL void poll_ge(const unsigned* p, unsigned target) {
  int n = 0;
  while (true) {
    unsigned v;
    asm volatile("ld.relaxed.gpu.global.u32 %0, [%1];" : "=r"(v) : "l"(p) : "memory");
    if (v >= target) break;
    if (++n > (1 << 20)) { g_err = 2; break; }
  }
}
DEVINL void red_publish(unsigned* p, unsigned n = 1) { asm volatile("red.release.gpu.global.add.u32 [%0], %1;" ::"l"(p), "r"(n) : "memory"); }
DEVINL void fence_async_smem() { asm volatile("fence.proxy.async.shared::cta;" ::: "memory"); }
DEVINL void named_sync(int id, int n) { asm volatile("bar.sync %0, %1;" ::"r"(id), "r"(n) : "memory"); }
DEVINL void named_arrive(int id, int n) { asm volatile("bar.arrive %0, %1;" ::"r"(id), "r"(n) : "memory"); }

DEVINL void tma2d(uint32_t dst, const CUtensorMap* m, int c0, int c1, uint32_t bar) {
  asm volatile("cp.async.bulk.tensor.2d.shared::cluster.global.mbarrier::complete_tx::bytes [%0], [%1, {%3, %4}], [%2];"
               ::"r"(dst), "l"(m), "r"(bar), "r"(c0), "r"(c1) : "memory");
}
DEVINL void tma2d_mc(uint32_t dst, const CUtensorMap* m, int c0, int c1, uint32_t bar) {
  asm volatile("cp.async.bulk.tensor.2d.shared::cluster.global.mbarrier::complete_tx::bytes.multicast::cluster [%0], [%1, {%3, %4}], [%2], %5;"
               ::"r"(dst), "l"(m), "r"(bar), "r"(c0), "r"(c1), "h"((uint16_t)3) : "memory");
}
DEVINL void tma3d(uint32_t dst, const CUtensorMap* m, int c0, int c1, int c2, uint32_t bar) {
  asm volatile("cp.async.bulk.tensor.3d.shared::cluster.global.mbarrier::complete_tx::bytes [%0], [%1, {%3, %4, %5}], [%2];"
               ::"r"(dst), "l"(m), "r"(bar), "r"(c0), "r"(c1), "r"(c2) : "memory");
}
DEVINL void tma3d_mc(uint32_t dst, const CUtensorMap* m, int c0, int c1, int c2, uint32_t bar) {
  asm volatile("cp.async.bulk.tensor.3d.shared::cluster.global.mbarrier::complete_tx::bytes.multicast::cluster [%0], [%1, {%3, %4, %5}], [%2], %6;"
               ::"r"(dst), "l"(m), "r"(bar), "r"(c0), "r"(c1), "r"(c2), "h"((uint16_t)3) : "memory");
}
DEVINL void tma2d_store(const CUtensorMap* m, int c0, int c1, uint32_t src) {
  asm volatile("cp.async.bulk.tensor.2d.global.shared::cta.bulk_group [%0, {%2, %3}], [%1];"
               ::"l"(m), "r"(src), "r"(c0), "r"(c1) : "memory");
}
DEVINL void tma3d_store(const CUtensorMap* m, int c0, int c1, int c2, uint32_t src) {
  asm volatile("cp.async.bulk.tensor.3d.global.shared::cta.bulk_group [%0, {%2, %3, %4}], [%1];"
               ::"l"(m), "r"(src), "r"(c0), "r"(c1), "r"(c2) : "memory");
}
DEVINL void bulk_load(uint32_t dst, const void* src, uint32_t bytes, uint32_t bar) {
  asm volatile("cp.async.bulk.shared::cluster.global.mbarrier::complete_tx::bytes [%0], [%1], %2, [%3];"
               ::"r"(dst), "l"(src), "r"(bytes), "r"(bar) : "memory");
}
DEVINL void bulk_load_mc(uint32_t dst, const void* src, uint32_t bytes, uint32_t bar) {
  asm volatile("cp.async.bulk.shared::cluster.global.mbarrier::complete_tx::bytes.multicast::cluster [%0], [%1], %2, [%3], %4;"
               ::"r"(dst), "l"(src), "r"(bytes), "r"(bar), "h"((uint16_t)3) : "memory");
}
DEVINL void tma5d(uint32_t dst, const CUtensorMap* m, int c0, int c1, int c2, int c3, int c4, uint32_t bar) {
  asm volatile("cp.async.bulk.tensor.5d.shared::cluster.global.mbarrier::complete_tx::bytes [%0], [%1, {%3, %4, %5, %6, %7}], [%2];"
               ::"r"(dst), "l"(m), "r"(bar), "r"(c0), "r"(c1), "r"(c2), "r"(c3), "r"(c4) : "memory");
}
DEVINL void prefetch_line(const void* p) { asm volatile("prefetch.global.L2 [%0];" ::"l"(p)); }
DEVINL void prefetch_l2(const void* p, uint32_t bytes) {
  asm volatile("cp.async.bulk.prefetch.L2.global [%0], %1;" ::"l"(p), "r"(bytes) : "memory");
}
template <int N> DEVINL void bulk_wait() { asm volatile("cp.async.bulk.wait_group %0;" ::"n"(N) : "memory"); }
DEVINL void bulk_store(void* dst, uint32_t src, uint32_t bytes) {
  asm volatile("cp.async.bulk.global.shared::cta.bulk_group [%0], [%1], %2;" ::"l"(dst), "r"(src), "r"(bytes) : "memory");
}
DEVINL void bulk_commit() { asm volatile("cp.async.bulk.commit_group;" ::: "memory"); }
DEVINL void bulk_wait0() { asm volatile("cp.async.bulk.wait_group 0;" ::: "memory"); }
DEVINL void bulk_wait0_read() { asm volatile("cp.async.bulk.wait_group.read 0;" ::: "memory"); }
DEVINL void prefetch_tmap(const CUtensorMap* m) { asm volatile("prefetch.tensormap [%0];" ::"l"(m) : "memory"); }

DEVINL uint64_t make_desc(uint32_t addr, uint32_t lbo, uint32_t sbo, uint32_t swz) {
  return (uint64_t)((addr & 0x3FFFF) >> 4) | ((uint64_t)(lbo >> 4) << 16) | ((uint64_t)(sbo >> 4) << 32) | ((uint64_t)swz << 62);
}
DEVINL void wg_fence() { asm volatile("wgmma.fence.sync.aligned;" ::: "memory"); }
DEVINL void wg_commit() { asm volatile("wgmma.commit_group.sync.aligned;" ::: "memory"); }
template <int N> DEVINL void wg_wait() { asm volatile("wgmma.wait_group.sync.aligned %0;" ::"n"(N) : "memory"); }

DEVINL void mma16816(float (&d)[4], uint32_t a0, uint32_t a1, uint32_t a2, uint32_t a3, uint32_t b0, uint32_t b1) {
  asm volatile("mma.sync.aligned.m16n8k16.row.col.f32.bf16.bf16.f32 {%0,%1,%2,%3},{%4,%5,%6,%7},{%8,%9},{%0,%1,%2,%3};"
               : "+f"(d[0]), "+f"(d[1]), "+f"(d[2]), "+f"(d[3]) : "r"(a0), "r"(a1), "r"(a2), "r"(a3), "r"(b0), "r"(b1));
}
DEVINL void mma16816_z(float (&d)[4], uint32_t a0, uint32_t a1, uint32_t a2, uint32_t a3, uint32_t b0, uint32_t b1) {
  asm volatile("mma.sync.aligned.m16n8k16.row.col.f32.bf16.bf16.f32 {%0,%1,%2,%3},{%4,%5,%6,%7},{%8,%9},{%10,%10,%10,%10};"
               : "=f"(d[0]), "=f"(d[1]), "=f"(d[2]), "=f"(d[3]) : "r"(a0), "r"(a1), "r"(a2), "r"(a3), "r"(b0), "r"(b1), "f"(0.f));
}
DEVINL void mma1688(float (&d)[4], uint32_t a0, uint32_t a1, uint32_t b0) {
  asm volatile("mma.sync.aligned.m16n8k8.row.col.f32.bf16.bf16.f32 {%0,%1,%2,%3},{%4,%5},{%6},{%0,%1,%2,%3};"
               : "+f"(d[0]), "+f"(d[1]), "+f"(d[2]), "+f"(d[3]) : "r"(a0), "r"(a1), "r"(b0));
}
DEVINL void ldsm4(uint32_t& r0, uint32_t& r1, uint32_t& r2, uint32_t& r3, uint32_t a) {
  asm volatile("ldmatrix.sync.aligned.m8n8.x4.shared.b16 {%0,%1,%2,%3}, [%4];" : "=r"(r0), "=r"(r1), "=r"(r2), "=r"(r3) : "r"(a));
}
DEVINL void ldsm2(uint32_t& r0, uint32_t& r1, uint32_t a) {
  asm volatile("ldmatrix.sync.aligned.m8n8.x2.shared.b16 {%0,%1}, [%2];" : "=r"(r0), "=r"(r1) : "r"(a));
}
DEVINL void ldsm4t(uint32_t& r0, uint32_t& r1, uint32_t& r2, uint32_t& r3, uint32_t a) {
  asm volatile("ldmatrix.sync.aligned.m8n8.x4.trans.shared.b16 {%0,%1,%2,%3}, [%4];" : "=r"(r0), "=r"(r1), "=r"(r2), "=r"(r3) : "r"(a));
}
DEVINL void ldsm2t(uint32_t& r0, uint32_t& r1, uint32_t a) {
  asm volatile("ldmatrix.sync.aligned.m8n8.x2.trans.shared.b16 {%0,%1}, [%2];" : "=r"(r0), "=r"(r1) : "r"(a));
}
DEVINL void stsm4(uint32_t a, uint32_t r0, uint32_t r1, uint32_t r2, uint32_t r3) {
  asm volatile("stmatrix.sync.aligned.m8n8.x4.shared.b16 [%0], {%1,%2,%3,%4};" ::"r"(a), "r"(r0), "r"(r1), "r"(r2), "r"(r3) : "memory");
}
DEVINL void stsm2(uint32_t a, uint32_t r0, uint32_t r1) {
  asm volatile("stmatrix.sync.aligned.m8n8.x2.shared.b16 [%0], {%1,%2};" ::"r"(a), "r"(r0), "r"(r1) : "memory");
}
DEVINL void stsm4t(uint32_t a, uint32_t r0, uint32_t r1, uint32_t r2, uint32_t r3) {
  asm volatile("stmatrix.sync.aligned.m8n8.x4.trans.shared.b16 [%0], {%1,%2,%3,%4};" ::"r"(a), "r"(r0), "r"(r1), "r"(r2), "r"(r3) : "memory");
}
DEVINL uint32_t lds32(uint32_t a) { uint32_t v; asm volatile("ld.shared.u32 %0, [%1];" : "=r"(v) : "r"(a)); return v; }
DEVINL uint4 lds128(uint32_t a) {
  uint4 v; asm volatile("ld.shared.v4.u32 {%0,%1,%2,%3}, [%4];" : "=r"(v.x), "=r"(v.y), "=r"(v.z), "=r"(v.w) : "r"(a)); return v;
}
DEVINL void sts32(uint32_t a, uint32_t v) { asm volatile("st.shared.u32 [%0], %1;" ::"r"(a), "r"(v) : "memory"); }
DEVINL void sts128(uint32_t a, uint4 v) {
  asm volatile("st.shared.v4.u32 [%0], {%1,%2,%3,%4};" ::"r"(a), "r"(v.x), "r"(v.y), "r"(v.z), "r"(v.w) : "memory");
}
DEVINL uint4 ldg_nc(const void* p) {
  uint4 v; asm volatile("ld.global.nc.L1::no_allocate.v4.u32 {%0,%1,%2,%3}, [%4];" : "=r"(v.x), "=r"(v.y), "=r"(v.z), "=r"(v.w) : "l"(p)); return v;
}
DEVINL uint4 ldg_cg(const void* p) {
  uint4 v; asm volatile("ld.global.cg.v4.u32 {%0,%1,%2,%3}, [%4];" : "=r"(v.x), "=r"(v.y), "=r"(v.z), "=r"(v.w) : "l"(p) : "memory"); return v;
}
DEVINL void stg128(void* p, uint4 v) {
  asm volatile("st.global.v4.u32 [%0], {%1,%2,%3,%4};" ::"l"(p), "r"(v.x), "r"(v.y), "r"(v.z), "r"(v.w) : "memory");
}
DEVINL uint32_t pack_bf16(float lo, float hi) {
  uint32_t r; asm("cvt.rn.bf16x2.f32 %0, %1, %2;" : "=r"(r) : "f"(hi), "f"(lo)); return r;
}
DEVINL uint32_t hmul2(uint32_t a, uint32_t b) { uint32_t r; asm("mul.rn.bf16x2 %0, %1, %2;" : "=r"(r) : "r"(a), "r"(b)); return r; }
DEVINL uint32_t hfma2(uint32_t a, uint32_t b, uint32_t c) { uint32_t r; asm("fma.rn.bf16x2 %0, %1, %2, %3;" : "=r"(r) : "r"(a), "r"(b), "r"(c)); return r; }
DEVINL uint32_t hadd2(uint32_t a, uint32_t b) { uint32_t r; asm("add.rn.bf16x2 %0, %1, %2;" : "=r"(r) : "r"(a), "r"(b)); return r; }
DEVINL float ex2(float x) { float r; asm("ex2.approx.ftz.f32 %0, %1;" : "=f"(r) : "f"(x)); return r; }

DEVINL void wgmma_n192(float (&d)[96], uint64_t da, uint64_t db, int scale_d) {
  asm volatile("{\n.reg .pred p;\nsetp.ne.b32 p, %98, 0;\n"
    "wgmma.mma_async.sync.aligned.m64n192k16.f32.bf16.bf16 "
    "{%0,%1,%2,%3,%4,%5,%6,%7,%8,%9,%10,%11,%12,%13,%14,%15,"
    "%16,%17,%18,%19,%20,%21,%22,%23,%24,%25,%26,%27,%28,%29,%30,%31,"
    "%32,%33,%34,%35,%36,%37,%38,%39,%40,%41,%42,%43,%44,%45,%46,%47,"
    "%48,%49,%50,%51,%52,%53,%54,%55,%56,%57,%58,%59,%60,%61,%62,%63,"
    "%64,%65,%66,%67,%68,%69,%70,%71,%72,%73,%74,%75,%76,%77,%78,%79,"
    "%80,%81,%82,%83,%84,%85,%86,%87,%88,%89,%90,%91,%92,%93,%94,%95}, "
    "%96, %97, p, 1, 1, 0, 1;\n}\n"
    : "+f"(d[0]), "+f"(d[1]), "+f"(d[2]), "+f"(d[3]), "+f"(d[4]), "+f"(d[5]), "+f"(d[6]), "+f"(d[7]),
      "+f"(d[8]), "+f"(d[9]), "+f"(d[10]), "+f"(d[11]), "+f"(d[12]), "+f"(d[13]), "+f"(d[14]), "+f"(d[15]),
      "+f"(d[16]), "+f"(d[17]), "+f"(d[18]), "+f"(d[19]), "+f"(d[20]), "+f"(d[21]), "+f"(d[22]), "+f"(d[23]),
      "+f"(d[24]), "+f"(d[25]), "+f"(d[26]), "+f"(d[27]), "+f"(d[28]), "+f"(d[29]), "+f"(d[30]), "+f"(d[31]),
      "+f"(d[32]), "+f"(d[33]), "+f"(d[34]), "+f"(d[35]), "+f"(d[36]), "+f"(d[37]), "+f"(d[38]), "+f"(d[39]),
      "+f"(d[40]), "+f"(d[41]), "+f"(d[42]), "+f"(d[43]), "+f"(d[44]), "+f"(d[45]), "+f"(d[46]), "+f"(d[47]),
      "+f"(d[48]), "+f"(d[49]), "+f"(d[50]), "+f"(d[51]), "+f"(d[52]), "+f"(d[53]), "+f"(d[54]), "+f"(d[55]),
      "+f"(d[56]), "+f"(d[57]), "+f"(d[58]), "+f"(d[59]), "+f"(d[60]), "+f"(d[61]), "+f"(d[62]), "+f"(d[63]),
      "+f"(d[64]), "+f"(d[65]), "+f"(d[66]), "+f"(d[67]), "+f"(d[68]), "+f"(d[69]), "+f"(d[70]), "+f"(d[71]),
      "+f"(d[72]), "+f"(d[73]), "+f"(d[74]), "+f"(d[75]), "+f"(d[76]), "+f"(d[77]), "+f"(d[78]), "+f"(d[79]),
      "+f"(d[80]), "+f"(d[81]), "+f"(d[82]), "+f"(d[83]), "+f"(d[84]), "+f"(d[85]), "+f"(d[86]), "+f"(d[87]),
      "+f"(d[88]), "+f"(d[89]), "+f"(d[90]), "+f"(d[91]), "+f"(d[92]), "+f"(d[93]), "+f"(d[94]), "+f"(d[95])
    : "l"(da), "l"(db), "r"(scale_d));
}

DEVINL void wgmma_n48(float (&d)[24], uint64_t da, uint64_t db, int scale_d) {
  asm volatile("{\n.reg .pred p;\nsetp.ne.b32 p, %26, 0;\n"
    "wgmma.mma_async.sync.aligned.m64n48k16.f32.bf16.bf16 "
    "{%0,%1,%2,%3,%4,%5,%6,%7,%8,%9,%10,%11,%12,%13,%14,%15,"
    "%16,%17,%18,%19,%20,%21,%22,%23}, "
    "%24, %25, p, 1, 1, 0, 1;\n}\n"
    : "+f"(d[0]), "+f"(d[1]), "+f"(d[2]), "+f"(d[3]), "+f"(d[4]), "+f"(d[5]), "+f"(d[6]), "+f"(d[7]),
      "+f"(d[8]), "+f"(d[9]), "+f"(d[10]), "+f"(d[11]), "+f"(d[12]), "+f"(d[13]), "+f"(d[14]), "+f"(d[15]),
      "+f"(d[16]), "+f"(d[17]), "+f"(d[18]), "+f"(d[19]), "+f"(d[20]), "+f"(d[21]), "+f"(d[22]), "+f"(d[23])
    : "l"(da), "l"(db), "r"(scale_d));
}

DEVINL void wgmma_n80(float (&d)[40], uint64_t da, uint64_t db, int scale_d) {
  asm volatile("{\n.reg .pred p;\nsetp.ne.b32 p, %42, 0;\n"
    "wgmma.mma_async.sync.aligned.m64n80k16.f32.bf16.bf16 "
    "{%0,%1,%2,%3,%4,%5,%6,%7,%8,%9,%10,%11,%12,%13,%14,%15,"
    "%16,%17,%18,%19,%20,%21,%22,%23,%24,%25,%26,%27,%28,%29,%30,%31,"
    "%32,%33,%34,%35,%36,%37,%38,%39}, "
    "%40, %41, p, 1, 1, 0, 1;\n}\n"
    : "+f"(d[0]), "+f"(d[1]), "+f"(d[2]), "+f"(d[3]), "+f"(d[4]), "+f"(d[5]), "+f"(d[6]), "+f"(d[7]),
      "+f"(d[8]), "+f"(d[9]), "+f"(d[10]), "+f"(d[11]), "+f"(d[12]), "+f"(d[13]), "+f"(d[14]), "+f"(d[15]),
      "+f"(d[16]), "+f"(d[17]), "+f"(d[18]), "+f"(d[19]), "+f"(d[20]), "+f"(d[21]), "+f"(d[22]), "+f"(d[23]),
      "+f"(d[24]), "+f"(d[25]), "+f"(d[26]), "+f"(d[27]), "+f"(d[28]), "+f"(d[29]), "+f"(d[30]), "+f"(d[31]),
      "+f"(d[32]), "+f"(d[33]), "+f"(d[34]), "+f"(d[35]), "+f"(d[36]), "+f"(d[37]), "+f"(d[38]), "+f"(d[39])
    : "l"(da), "l"(db), "r"(scale_d));
}

DEVINL void wgmma_qk_n64(float (&d)[32], uint32_t a0, uint32_t a1, uint32_t a2, uint32_t a3, uint64_t db, int scale_d) {
  asm volatile("{\n.reg .pred p;\nsetp.ne.b32 p, %37, 0;\n"
    "wgmma.mma_async.sync.aligned.m64n64k16.f32.bf16.bf16 "
    "{%0,%1,%2,%3,%4,%5,%6,%7,%8,%9,%10,%11,%12,%13,%14,%15,"
    "%16,%17,%18,%19,%20,%21,%22,%23,%24,%25,%26,%27,%28,%29,%30,%31}, "
    "{%32,%33,%34,%35}, %36, p, 1, 1, 0;\n}\n"
    : "+f"(d[0]), "+f"(d[1]), "+f"(d[2]), "+f"(d[3]), "+f"(d[4]), "+f"(d[5]), "+f"(d[6]), "+f"(d[7]),
      "+f"(d[8]), "+f"(d[9]), "+f"(d[10]), "+f"(d[11]), "+f"(d[12]), "+f"(d[13]), "+f"(d[14]), "+f"(d[15]),
      "+f"(d[16]), "+f"(d[17]), "+f"(d[18]), "+f"(d[19]), "+f"(d[20]), "+f"(d[21]), "+f"(d[22]), "+f"(d[23]),
      "+f"(d[24]), "+f"(d[25]), "+f"(d[26]), "+f"(d[27]), "+f"(d[28]), "+f"(d[29]), "+f"(d[30]), "+f"(d[31])
    : "r"(a0), "r"(a1), "r"(a2), "r"(a3), "l"(db), "r"(scale_d));
}

DEVINL void wgmma_pv_n24(float (&d)[12], uint32_t a0, uint32_t a1, uint32_t a2, uint32_t a3, uint64_t db, int scale_d) {
  asm volatile("{\n.reg .pred p;\nsetp.ne.b32 p, %17, 0;\n"
    "wgmma.mma_async.sync.aligned.m64n24k16.f32.bf16.bf16 "
    "{%0,%1,%2,%3,%4,%5,%6,%7,%8,%9,%10,%11}, "
    "{%12,%13,%14,%15}, %16, p, 1, 1, 1;\n}\n"
    : "+f"(d[0]), "+f"(d[1]), "+f"(d[2]), "+f"(d[3]), "+f"(d[4]), "+f"(d[5]), "+f"(d[6]), "+f"(d[7]),
      "+f"(d[8]), "+f"(d[9]), "+f"(d[10]), "+f"(d[11])
    : "r"(a0), "r"(a1), "r"(a2), "r"(a3), "l"(db), "r"(scale_d));
}

DEVINL void wgmma_qk_n64_z(float (&d)[32], uint32_t a0, uint32_t a1, uint32_t a2, uint32_t a3, uint64_t db) {
  asm volatile("{\n.reg .pred p;\nsetp.ne.b32 p, 0, 0;\n"
    "wgmma.mma_async.sync.aligned.m64n64k16.f32.bf16.bf16 "
    "{%0,%1,%2,%3,%4,%5,%6,%7,%8,%9,%10,%11,%12,%13,%14,%15,"
    "%16,%17,%18,%19,%20,%21,%22,%23,%24,%25,%26,%27,%28,%29,%30,%31}, "
    "{%32,%33,%34,%35}, %36, p, 1, 1, 0;\n}\n"
    : "=f"(d[0]), "=f"(d[1]), "=f"(d[2]), "=f"(d[3]), "=f"(d[4]), "=f"(d[5]), "=f"(d[6]), "=f"(d[7]),
      "=f"(d[8]), "=f"(d[9]), "=f"(d[10]), "=f"(d[11]), "=f"(d[12]), "=f"(d[13]), "=f"(d[14]), "=f"(d[15]),
      "=f"(d[16]), "=f"(d[17]), "=f"(d[18]), "=f"(d[19]), "=f"(d[20]), "=f"(d[21]), "=f"(d[22]), "=f"(d[23]),
      "=f"(d[24]), "=f"(d[25]), "=f"(d[26]), "=f"(d[27]), "=f"(d[28]), "=f"(d[29]), "=f"(d[30]), "=f"(d[31])
    : "r"(a0), "r"(a1), "r"(a2), "r"(a3), "l"(db));
}

DEVINL void wgmma_pv_n24_z(float (&d)[12], uint32_t a0, uint32_t a1, uint32_t a2, uint32_t a3, uint64_t db) {
  asm volatile("{\n.reg .pred p;\nsetp.ne.b32 p, 0, 0;\n"
    "wgmma.mma_async.sync.aligned.m64n24k16.f32.bf16.bf16 "
    "{%0,%1,%2,%3,%4,%5,%6,%7,%8,%9,%10,%11}, "
    "{%12,%13,%14,%15}, %16, p, 1, 1, 1;\n}\n"
    : "=f"(d[0]), "=f"(d[1]), "=f"(d[2]), "=f"(d[3]), "=f"(d[4]), "=f"(d[5]), "=f"(d[6]), "=f"(d[7]),
      "=f"(d[8]), "=f"(d[9]), "=f"(d[10]), "=f"(d[11])
    : "r"(a0), "r"(a1), "r"(a2), "r"(a3), "l"(db));
}

DEVINL void wgmma_cv_n64(float (&d)[32], uint32_t a0, uint32_t a1, uint32_t a2, uint32_t a3, uint64_t db) {
  asm volatile("{\n.reg .pred p;\nsetp.ne.b32 p, 1, 0;\n"
    "wgmma.mma_async.sync.aligned.m64n64k16.f32.bf16.bf16 "
    "{%0,%1,%2,%3,%4,%5,%6,%7,%8,%9,%10,%11,%12,%13,%14,%15,"
    "%16,%17,%18,%19,%20,%21,%22,%23,%24,%25,%26,%27,%28,%29,%30,%31}, "
    "{%32,%33,%34,%35}, %36, p, 1, 1, 0;\n}\n"
    : "+f"(d[0]), "+f"(d[1]), "+f"(d[2]), "+f"(d[3]), "+f"(d[4]), "+f"(d[5]), "+f"(d[6]), "+f"(d[7]),
      "+f"(d[8]), "+f"(d[9]), "+f"(d[10]), "+f"(d[11]), "+f"(d[12]), "+f"(d[13]), "+f"(d[14]), "+f"(d[15]),
      "+f"(d[16]), "+f"(d[17]), "+f"(d[18]), "+f"(d[19]), "+f"(d[20]), "+f"(d[21]), "+f"(d[22]), "+f"(d[23]),
      "+f"(d[24]), "+f"(d[25]), "+f"(d[26]), "+f"(d[27]), "+f"(d[28]), "+f"(d[29]), "+f"(d[30]), "+f"(d[31])
    : "r"(a0), "r"(a1), "r"(a2), "r"(a3), "l"(db));
}

DEVINL void wgmma_cv_n48(float (&d)[24], uint32_t a0, uint32_t a1, uint32_t a2, uint32_t a3, uint64_t db) {
  asm volatile("{\n.reg .pred p;\nsetp.ne.b32 p, 1, 0;\n"
    "wgmma.mma_async.sync.aligned.m64n48k16.f32.bf16.bf16 "
    "{%0,%1,%2,%3,%4,%5,%6,%7,%8,%9,%10,%11,%12,%13,%14,%15,"
    "%16,%17,%18,%19,%20,%21,%22,%23}, "
    "{%24,%25,%26,%27}, %28, p, 1, 1, 0;\n}\n"
    : "+f"(d[0]), "+f"(d[1]), "+f"(d[2]), "+f"(d[3]), "+f"(d[4]), "+f"(d[5]), "+f"(d[6]), "+f"(d[7]),
      "+f"(d[8]), "+f"(d[9]), "+f"(d[10]), "+f"(d[11]), "+f"(d[12]), "+f"(d[13]), "+f"(d[14]), "+f"(d[15]),
      "+f"(d[16]), "+f"(d[17]), "+f"(d[18]), "+f"(d[19]), "+f"(d[20]), "+f"(d[21]), "+f"(d[22]), "+f"(d[23])
    : "r"(a0), "r"(a1), "r"(a2), "r"(a3), "l"(db));
}

DEVINL void wgmma_cv_n32(float (&d)[16], uint32_t a0, uint32_t a1, uint32_t a2, uint32_t a3, uint64_t db) {
  asm volatile("{\n.reg .pred p;\nsetp.ne.b32 p, 1, 0;\n"
    "wgmma.mma_async.sync.aligned.m64n32k16.f32.bf16.bf16 "
    "{%0,%1,%2,%3,%4,%5,%6,%7,%8,%9,%10,%11,%12,%13,%14,%15}, "
    "{%16,%17,%18,%19}, %20, p, 1, 1, 0;\n}\n"
    : "+f"(d[0]), "+f"(d[1]), "+f"(d[2]), "+f"(d[3]), "+f"(d[4]), "+f"(d[5]), "+f"(d[6]), "+f"(d[7]),
      "+f"(d[8]), "+f"(d[9]), "+f"(d[10]), "+f"(d[11]), "+f"(d[12]), "+f"(d[13]), "+f"(d[14]), "+f"(d[15])
    : "r"(a0), "r"(a1), "r"(a2), "r"(a3), "l"(db));
}

DEVINL void wgmma_cv_n16(float (&d)[8], uint32_t a0, uint32_t a1, uint32_t a2, uint32_t a3, uint64_t db) {
  asm volatile("{\n.reg .pred p;\nsetp.ne.b32 p, 1, 0;\n"
    "wgmma.mma_async.sync.aligned.m64n16k16.f32.bf16.bf16 "
    "{%0,%1,%2,%3,%4,%5,%6,%7}, "
    "{%8,%9,%10,%11}, %12, p, 1, 1, 0;\n}\n"
    : "+f"(d[0]), "+f"(d[1]), "+f"(d[2]), "+f"(d[3]), "+f"(d[4]), "+f"(d[5]), "+f"(d[6]), "+f"(d[7])
    : "r"(a0), "r"(a1), "r"(a2), "r"(a3), "l"(db));
}

#define ATT_T(i) do {} while (0)
#define ATT_IMAX 0
#define ATT_WAIT0 0
#define ATT_SPLIT 3
constexpr float SM_C = 0.22360679774997896f * 1.4426950408889634f;
constexpr float NEG_INF = -INFINITY;
constexpr int PLANE = 2048;
constexpr int PAIR = 11 * PLANE;
constexpr int SEG = 2 * PAIR;
constexpr int PWIN = 3 * PAIR;

template <int N> DEVINL void reg_fence(float (&d)[N]) {
#pragma unroll
  for (int i = 0; i < N; ++i) asm volatile("" : "+f"(d[i])::"memory");
}
DEVINL float ex2v(float x) { float r; asm volatile("ex2.approx.ftz.f32 %0, %1;" : "=f"(r) : "f"(x)); return r; }
DEVINL uint32_t bsel(uint32_t a, uint32_t b, uint32_t m) { return (a & m) | (b & ~m); }
DEVINL float fsel(float a, float b, uint32_t m) { return __uint_as_float(bsel(__float_as_uint(a), __float_as_uint(b), m)); }
typedef uint64_t desc_t;
DEVINL desc_t kdesc(desc_t d) { return d; }
DEVINL desc_t vdesc(desc_t d) { return d; }

DEVINL void mma_qk(float (&s)[32], const uint32_t (&a)[4], const uint32_t (&a8)[2], desc_t kmain, desc_t ktail) {
  wgmma_qk_n64_z(s, a[0], a[1], a[2], a[3], kdesc(kmain));
  wgmma_qk_n64(s, a8[0], a8[1], 0u, 0u, kdesc(ktail), 1);
}
template <bool FIRST>
DEVINL void mma_pv(float (&o)[12], const uint32_t (&p)[16], desc_t v) {
  if (FIRST) wgmma_pv_n24_z(o, p[0], p[1], p[2], p[3], vdesc(v));
  else wgmma_pv_n24(o, p[0], p[1], p[2], p[3], vdesc(v), 1);
#pragma unroll
  for (int b = 1; b < 4; ++b) wgmma_pv_n24(o, p[4 * b], p[4 * b + 1], p[4 * b + 2], p[4 * b + 3], vdesc(v + b * 16), 1);
}
DEVINL void row_max_f(const float (&s)[32], float& x0o, float& x1o) {
  float x0 = fmaxf(s[0], s[1]), x1 = fmaxf(s[2], s[3]), y0 = fmaxf(s[4], s[5]), y1 = fmaxf(s[6], s[7]);
#pragma unroll
  for (int i = 2; i < 8; i += 2) {
    x0 = fmaxf(x0, fmaxf(s[4 * i], s[4 * i + 1]));
    x1 = fmaxf(x1, fmaxf(s[4 * i + 2], s[4 * i + 3]));
    y0 = fmaxf(y0, fmaxf(s[4 * i + 4], s[4 * i + 5]));
    y1 = fmaxf(y1, fmaxf(s[4 * i + 6], s[4 * i + 7]));
  }
  x0 = fmaxf(x0, y0); x1 = fmaxf(x1, y1);
  x0 = fmaxf(x0, __shfl_xor_sync(0xffffffffu, x0, 1));
  x1 = fmaxf(x1, __shfl_xor_sync(0xffffffffu, x1, 1));
  x0o = fmaxf(x0, __shfl_xor_sync(0xffffffffu, x0, 2));
  x1o = fmaxf(x1, __shfl_xor_sync(0xffffffffu, x1, 2));
}
DEVINL void row_max(const float (&s)[32], float pm0, float pm1, float& x0o, float& x1o) {
#define FI(i) __float_as_int(s[i])
  int x0 = __vimax3_s32(FI(0), FI(1), FI(4)), x1 = __vimax3_s32(FI(2), FI(3), FI(6));
  int y0 = __vimax3_s32(FI(5), FI(8), FI(9)), y1 = __vimax3_s32(FI(7), FI(10), FI(11));
  x0 = __vimax3_s32(x0, FI(12), FI(13)); x1 = __vimax3_s32(x1, FI(14), FI(15));
  y0 = __vimax3_s32(y0, FI(16), FI(17)); y1 = __vimax3_s32(y1, FI(18), FI(19));
  x0 = __vimax3_s32(x0, FI(20), FI(21)); x1 = __vimax3_s32(x1, FI(22), FI(23));
  y0 = __vimax3_s32(y0, FI(24), FI(25)); y1 = __vimax3_s32(y1, FI(26), FI(27));
  x0 = __vimax3_s32(x0, FI(28), FI(29)); x1 = __vimax3_s32(x1, FI(30), FI(31));
#undef FI
  x0 = max(x0, y0); x1 = max(x1, y1);
  x0 = max(x0, __shfl_xor_sync(0xffffffffu, x0, 1));
  x1 = max(x1, __shfl_xor_sync(0xffffffffu, x1, 1));
  x0 = max(x0, __shfl_xor_sync(0xffffffffu, x0, 2));
  x1 = max(x1, __shfl_xor_sync(0xffffffffu, x1, 2));
  float f0 = __int_as_float(x0), f1 = __int_as_float(x1);
  if (__any_sync(0xffffffffu, (x0 < 0 && !(pm0 >= 0.f)) || (x1 < 0 && !(pm1 >= 0.f)))) {
    f0 = s[0]; f1 = s[2];
#pragma unroll
    for (int i = 0; i < 8; ++i) {
      f0 = fmaxf(f0, fmaxf(s[4 * i], s[4 * i + 1]));
      f1 = fmaxf(f1, fmaxf(s[4 * i + 2], s[4 * i + 3]));
    }
    f0 = fmaxf(f0, __shfl_xor_sync(0xffffffffu, f0, 1));
    f1 = fmaxf(f1, __shfl_xor_sync(0xffffffffu, f1, 1));
    f0 = fmaxf(f0, __shfl_xor_sync(0xffffffffu, f0, 2));
    f1 = fmaxf(f1, __shfl_xor_sync(0xffffffffu, f1, 2));
  }
  x0o = f0; x1o = f1;
}
template <int I0, int I1>
DEVINL void sm_exp(const float (&s)[32], uint32_t (&p)[16], float n0, float n1) {
#pragma unroll
  for (int i = I0; i < I1; ++i) {
    const float e0 = ex2v(fmaf(s[4 * i], SM_C, n0)), e1 = ex2v(fmaf(s[4 * i + 1], SM_C, n0));
    const float e2 = ex2v(fmaf(s[4 * i + 2], SM_C, n1)), e3 = ex2v(fmaf(s[4 * i + 3], SM_C, n1));
    p[2 * i] = pack_bf16(e0, e1);
    p[2 * i + 1] = pack_bf16(e2, e3);
  }
}
DEVINL void rescale(float (&o)[12], float al0, float al1) {
#pragma unroll
  for (int n = 0; n < 3; ++n) { o[4 * n] *= al0; o[4 * n + 1] *= al0; o[4 * n + 2] *= al1; o[4 * n + 3] *= al1; }
}
struct SoftmaxState { float m0, m1, n0, n1, al0, al1; };
DEVINL void next_max(SoftmaxState& st, float x0, float x1, bool valid) {
  x0 = fmaxf(valid ? x0 : NEG_INF, st.m0); x1 = fmaxf(valid ? x1 : NEG_INF, st.m1);
  const float c0 = -x0 * SM_C, c1 = -x1 * SM_C;
  st.al0 = ex2(fmaf(st.m0, SM_C, c0)); st.al1 = ex2(fmaf(st.m1, SM_C, c1));
  st.m0 = x0; st.m1 = x1;
  st.n0 = valid ? c0 : NEG_INF; st.n1 = valid ? c1 : NEG_INF;
}
template <bool PVPEND, int SPLIT>
DEVINL void step(const float (&cur)[32], float (&nxt)[32], float (&o)[12], uint32_t (&p)[16], SoftmaxState& st, bool valid_nxt) {
  const float n0 = st.n0, n1 = st.n1, pa0 = st.al0, pa1 = st.al1;
  sm_exp<0, SPLIT>(cur, p, n0, n1);
  wg_wait<(PVPEND && !ATT_WAIT0) ? 1 : 0>();
  reg_fence(nxt);
  float x0, x1;
  row_max_f(nxt, x0, x1);
  sm_exp<SPLIT, 8>(cur, p, n0, n1);
  next_max(st, x0, x1, valid_nxt);
  if (PVPEND) { wg_wait<0>(); reg_fence(o); rescale(o, pa0, pa1); }
}

DEVINL void attn_all(uint32_t ring, uint32_t stg, uint32_t bars, int wq, int lane, int cmin) {
  const int wg = wq >> 2, w = wq & 3;
  const int g = lane >> 2, t = lane & 3, mi = lane >> 3, r = lane & 7;
  const uint32_t T0 = (2 * t > g) ? 0xFFFFFFFFu : 0u, T1 = (2 * t + 1 > g) ? 0xFFFFFFFFu : 0u;
  const uint32_t tri = (T0 & 0xFFFFu) | (T1 & 0xFFFF0000u);
  const uint32_t rowQ = stg + (mi >> 1) * PLANE + (16 * wq + r + 8 * (mi & 1)) * 16;
  const uint32_t rowQ8 = stg + 2 * PLANE + (16 * wq + (lane & 15)) * 16;
  constexpr uint32_t S16 = PAIR >> 4, P16 = PLANE >> 4;
  const uint32_t aE = ((ring + wg * 1024) & 0x3FFFF) >> 4, aO = ((ring + wg * PAIR + (wg ^ 1) * 1024) & 0x3FFFF) >> 4;
  const desc_t kE = (desc_t)(aE | (P16 << 16)) | ((desc_t)(128 >> 4) << 32), kO = (desc_t)(aO | (P16 << 16)) | ((desc_t)(128 >> 4) << 32);
  const desc_t vE = (desc_t)(aE | ((128 >> 4) << 16)) | ((desc_t)P16 << 32), vO = (desc_t)(aO | ((128 >> 4) << 16)) | ((desc_t)P16 << 32);
  uint32_t a[4], a8[2];
  float sX[32], sY[32], o[12];
  uint32_t pA[16], pB[16];
  mbar_wait(bars + 8 * B_HALO, 0);
  ldsm4(a[0], a[1], a[2], a[3], rowQ);
  ldsm2(a8[0], a8[1], rowQ8);
  if (t >= 2) { a8[0] = 0u; a8[1] = 0u; }
  wg_fence();
  mma_qk(sX, a, a8, kE, kE + 2 * P16);
  mma_qk(sY, a, a8, kE + 2 * S16, kE + 2 * S16 + 2 * P16);
  wg_commit();
#pragma unroll 1
  for (int h = 0; h < 4; ++h) {
    const int p = h >> 1, odd = h & 1;
    const uint32_t km = (p * 33 + odd * 3) * P16, kt = (p * 33 + 2) * P16, vp = (p * 33 + 5 + odd * 3) * P16;
    SoftmaxState st;
    ATT_T(0);
    wg_wait<0>();
    reg_fence(sX); reg_fence(sY);
    ATT_T(1);
    if (cmin > 0) {
#pragma unroll
      for (int i = 0; i < 32; ++i) sX[i] = NEG_INF;
    }
#pragma unroll
    for (int b = 0; b < 4; ++b) {
      const uint32_t gt = b > w ? 0xFFFFFFFFu : 0u, ge = b >= w ? 0xFFFFFFFFu : 0u, eq = ge & ~gt;
      const uint32_t e0 = gt | (eq & T0), e1 = gt | (eq & T1);
      sX[8 * b + 0] = fsel(sX[8 * b + 0], sY[8 * b + 0], e0);
      sX[8 * b + 1] = fsel(sX[8 * b + 1], sY[8 * b + 1], e1);
      sX[8 * b + 2] = fsel(sX[8 * b + 2], sY[8 * b + 2], gt);
      sX[8 * b + 3] = fsel(sX[8 * b + 3], sY[8 * b + 3], gt);
      sX[8 * b + 4] = fsel(sX[8 * b + 4], sY[8 * b + 4], ge);
      sX[8 * b + 5] = fsel(sX[8 * b + 5], sY[8 * b + 5], ge);
      sX[8 * b + 6] = fsel(sX[8 * b + 6], sY[8 * b + 6], e0);
      sX[8 * b + 7] = fsel(sX[8 * b + 7], sY[8 * b + 7], e1);
    }
    wg_fence();
    mma_qk(sY, a, a8, kO + km, kO + kt);
    wg_commit();
    ATT_T(2);
    row_max_f(sX, st.m0, st.m1);
    st.n0 = -st.m0 * SM_C; st.n1 = -st.m1 * SM_C;
    ATT_T(3);
    step<false, ATT_SPLIT>(sX, sY, o, pA, st, wg + 1 >= cmin);
    ATT_T(4);
#pragma unroll
    for (int b = 0; b < 4; ++b) {
      const uint32_t gt = b > w ? 0xFFFFFFFFu : 0u, ge = b >= w ? 0xFFFFFFFFu : 0u, eq = ge & ~gt;
      const uint32_t mt = gt | (eq & tri);
      pB[4 * b + 0] = pA[4 * b + 0] & ~mt; pA[4 * b + 0] &= mt;
      pB[4 * b + 1] = pA[4 * b + 1] & ~gt; pA[4 * b + 1] &= gt;
      pB[4 * b + 2] = pA[4 * b + 2] & ~ge; pA[4 * b + 2] &= ge;
      pB[4 * b + 3] = pA[4 * b + 3] & ~mt; pA[4 * b + 3] &= mt;
    }
    wg_fence();
    mma_qk(sX, a, a8, kE + S16 + km, kE + S16 + kt);
    wg_commit();
    mma_pv<true>(o, pA, vE + vp);
    mma_pv<false>(o, pB, vE + 2 * S16 + vp);
    wg_commit();
    ATT_T(5);
    step<true, ATT_SPLIT>(sY, sX, o, pB, st, wg + 2 >= cmin);
    ATT_T(6);
    wg_fence();
    mma_qk(sY, a, a8, kO + S16 + km, kO + S16 + kt);
    wg_commit();
    mma_pv<false>(o, pB, vO + vp);
    wg_commit();
    ATT_T(7);
    step<true, ATT_SPLIT>(sX, sY, o, pA, st, wg + 3 >= cmin);
    ATT_T(8);
    const int hn = h < 3 ? h + 1 : h, pn = hn >> 1, on = hn & 1;
    const uint32_t kmn = (pn * 33 + on * 3) * P16, ktn = (pn * 33 + 2) * P16;
    if (h == 1) mbar_wait(bars + 8 * (B_HALO + 1), 0);
    ldsm4(a[0], a[1], a[2], a[3], rowQ + (pn * 5 + on * 3) * PLANE);
    ldsm2(a8[0], a8[1], rowQ8 + pn * 5 * PLANE);
    if ((t >= 2) != (on != 0)) { a8[0] = 0u; a8[1] = 0u; }
    wg_fence();
    mma_pv<false>(o, pA, vE + S16 + vp);
    mma_qk(sX, a, a8, kE + kmn, kE + ktn);
    wg_commit();
    ATT_T(9);
    sm_exp<0, 8>(sY, pB, st.n0, st.n1);
    ATT_T(10);
    wg_wait<0>();
    reg_fence(o); reg_fence(sX);
    rescale(o, st.al0, st.al1);
    wg_fence();
    mma_pv<false>(o, pB, vO + S16 + vp);
    wg_commit();
    wg_fence();
    mma_qk(sY, a, a8, kE + 2 * S16 + kmn, kE + 2 * S16 + ktn);
    wg_commit();
    ATT_T(11);
    wg_wait<1>();
    reg_fence(o);
    const int src = (lane & ~3) | (odd ? 0 : 2);
    const float i0 = __fdividef(1.f, __shfl_sync(0xffffffffu, o[8], src)), i1 = __fdividef(1.f, __shfl_sync(0xffffffffu, o[10], src));
    const uint32_t ob = stg + p * 5 * PLANE + (16 * wq + g) * 16 + t * 4;
    const uint32_t om = ob + odd * 3 * PLANE;
    sts32(om, pack_bf16(o[0] * i0, o[1] * i0)); sts32(om + 128, pack_bf16(o[2] * i1, o[3] * i1));
    sts32(om + PLANE, pack_bf16(o[4] * i0, o[5] * i0)); sts32(om + PLANE + 128, pack_bf16(o[6] * i1, o[7] * i1));
    if ((t >= 2) == (odd != 0)) { sts32(ob + 2 * PLANE, pack_bf16(o[8] * i0, o[9] * i0)); sts32(ob + 2 * PLANE + 128, pack_bf16(o[10] * i1, o[11] * i1)); }
    if (odd) {
      fence_async_smem();
      __syncwarp();
      if (lane == 0) mbar_arrive(bars + 8 * (B_OST + p));
      if (lane < 4) mbar_arrive_cta(bars + 8 * (B_EMPTY2 + 2 * p + (lane >> 1)), lane & 1);
    }
    ATT_T(12);
  }
  wg_wait<0>();
  reg_fence(sX); reg_fence(sY);
  __syncwarp();
}

#define NO_G 1
#define OPUB_GATE 1
#define KT_IN_F 0
#define EXP_NOLD 0
#define PF_MODE 2
#define KVPF_AT 3
#define PRE_LDG 0
#define PRE_AFTER 4
#define PRE_WAIT 1
struct Params {
  const uint16_t* q; const uint16_t* k; const uint16_t* v; const uint16_t* shift_k; const uint16_t* ssm_k;
  const uint16_t* ssm_D; const uint16_t* x; const uint16_t* wqkv; const uint16_t* wo; uint16_t* out;
};

DEVINL unsigned* cnt(int i) { return &g_cnt[i * CS]; }

DEVINL void finish_role() {
  unsigned old = atomicAdd(cnt(C_DONE), 1u);
  if (old == 255u) {
    __threadfence();
    for (int i = 0; i < C_NUM; ++i) *cnt(i) = 0u;
    __threadfence();
  }
}

DEVINL void conv_channel(uint32_t sb, int cl, int wc, int lane, uint32_t D2, int bar_id) {
  const int mi = lane >> 3, r = lane & 7, g = lane >> 2, t = lane & 3;
  const int h = wc >> 1, rr = wc & 1;
  const uint32_t Ub = cl < 4 ? sb + OFF_U + cl * CH_U : sb + OFF_U4, Fb = sb + OFF_F + cl * CH_F;
  const uint32_t fw = ((g & 1) ? Fb + 4160 + 2 * (33 - g + 2 * t) : Fb + 2 * (32 - g + 2 * t)) + 1024 * h - 32 * rr;
  const uint32_t ub = (((Ub & 0x3FFFF) >> 4) + 16) | ((UPL >> 4) << 16);
  float d[32], d2[16];
#pragma unroll
  for (int i = 0; i < 32; ++i) d[i] = 0.f;
#pragma unroll
  for (int i = 0; i < 16; ++i) d2[i] = 0.f;
#pragma unroll 1
  for (int rq = 0; rq < 4; ++rq) {
#pragma unroll
    for (int bt = 0; bt < 2; ++bt) {
      const int rho = 4 * rq + 2 * bt;
      const uint32_t fb = fw + 64 * rho;
      uint32_t x[2][2][5];
      wg_wait<1>();
#pragma unroll
      for (int e = 0; e < 2; ++e)
#pragma unroll
        for (int j = 0; j < 5; ++j) { x[e][0][j] = lds32(fb + 64 * e - 16 + 16 * j); x[e][1][j] = lds32(fb + 64 * e + 2048 - 16 + 16 * j); }
      wg_fence();
#pragma unroll
      for (int e = 0; e < 2; ++e) {
        const uint64_t b0 = (uint64_t)(ub - rho - e) | ((uint64_t)(128 >> 4) << 32), b1 = b0 + 2 * (UPL >> 4);
        wgmma_cv_n64(d, x[e][0][1], x[e][0][0], x[e][0][2], x[e][0][1], b0);
        wgmma_cv_n64(d, x[e][0][3], x[e][0][2], x[e][0][4], x[e][0][3], b1);
        wgmma_cv_n32(d2, x[e][1][1], x[e][1][0], x[e][1][2], x[e][1][1], b0);
        wgmma_cv_n32(d2, x[e][1][3], x[e][1][2], x[e][1][4], x[e][1][3], b1);
      }
      wg_commit();
    }
  }
  wg_wait<0>();
  reg_fence(d); reg_fence(d2);
#pragma unroll
  for (int i = 0; i < 16; ++i) d[16 + i] += d2[i];
  named_sync(bar_id, 128);
  const uint32_t xb = Fb + wc * 2048 + lane * 16;
#pragma unroll
  for (int j = 0; j < 4; ++j) {
    const float4 v = h == 0 ? make_float4(d[16 + 4 * j], d[17 + 4 * j], d[18 + 4 * j], d[19 + 4 * j])
                            : make_float4(d[4 * j], d[1 + 4 * j], d[2 + 4 * j], d[3 + 4 * j]);
    sts128(xb + j * 512, make_uint4(__float_as_uint(v.x), __float_as_uint(v.y), __float_as_uint(v.z), __float_as_uint(v.w)));
  }
  named_sync(bar_id, 128);
  const uint32_t xr = Fb + (wc ^ 2) * 2048 + lane * 16;
  float f[4][4];
#pragma unroll
  for (int j = 0; j < 4; ++j) {
    const uint4 ov = lds128(xr + (h == 0 ? (j >= 2 ? j - 2 : 0) : j) * 512);
    const float z = (h == 0 && j < 2) ? 0.f : 1.f;
    f[j][0] = (h == 0 ? d[4 * j] : d[8 + 4 * j]) + z * __uint_as_float(ov.x);
    f[j][1] = (h == 0 ? d[4 * j + 1] : d[9 + 4 * j]) + z * __uint_as_float(ov.y);
    f[j][2] = (h == 0 ? d[4 * j + 2] : d[10 + 4 * j]) + z * __uint_as_float(ov.z);
    f[j][3] = (h == 0 ? d[4 * j + 3] : d[11 + 4 * j]) + z * __uint_as_float(ov.w);
  }
  uint32_t res[2][4];
#pragma unroll
  for (int jj = 0; jj < 2; ++jj) {
    const int tile = 4 * h + 2 * jj + (mi >> 1);
    uint32_t u0, u1, u2, u3;
    ldsm4t(u0, u1, u2, u3, Ub + (2 * rr + (mi & 1)) * UPL + (16 + 8 * tile + r) * 16);
    res[jj][0] = hadd2(pack_bf16(f[2 * jj][0], f[2 * jj][1]), hmul2(u0, D2));
    res[jj][1] = hadd2(pack_bf16(f[2 * jj][2], f[2 * jj][3]), hmul2(u1, D2));
    res[jj][2] = hadd2(pack_bf16(f[2 * jj + 1][0], f[2 * jj + 1][1]), hmul2(u2, D2));
    res[jj][3] = hadd2(pack_bf16(f[2 * jj + 1][2], f[2 * jj + 1][3]), hmul2(u3, D2));
  }
  named_sync(bar_id, 128);
#pragma unroll
  for (int jj = 0; jj < 2; ++jj) {
    const int tile = 4 * h + 2 * jj + (mi >> 1);
    stsm4t(Fb + ((8 * tile + r) * 32 + 16 * rr + 8 * (mi & 1)) * 2, res[jj][0], res[jj][1], res[jj][2], res[jj][3]);
  }
  fence_async_smem();
  __syncwarp();
  if (lane == 0) mbar_arrive(sb + OFF_BAR + 8 * (B_YST + cl));
}

__global__ void __cluster_dims__(2, 1, 1) __launch_bounds__(512, 1)
h3_swa_fused_kernel(const __grid_constant__ CUtensorMap tmX, const __grid_constant__ CUtensorMap tmW128,
                    const __grid_constant__ CUtensorMap tmW32,
                    const __grid_constant__ CUtensorMap tmOut, const __grid_constant__ CUtensorMap tmKT,
                    const __grid_constant__ CUtensorMap tmKin, const __grid_constant__ CUtensorMap tmVin,
                    const Params prm) {
  extern __shared__ uint8_t smem_raw[];
  const uint32_t sb = (uint32_t)__cvta_generic_to_shared(smem_raw);
  if ((sb & 1023u) != 0u) { g_err = 3; return; }
  const uint32_t bars = sb + OFF_BAR;
  const int tid = threadIdx.x, warp = tid >> 5, lane = tid & 31, wg = tid >> 7;
  const int cta = blockIdx.x;
  const uint32_t rank = cta & 1;
  const int g8 = (cta >> 1) & 7, rp = cta >> 4;
  const int rb = 2 * rp + rank;
  const int rb2 = 2 * rp + (g8 & 1);
  const int c2 = 2 * (g8 >> 1) + rank;
  const int tau = cta & 15, jt = cta >> 4;

  if (tid == 384) { prefetch_tmap(&tmX); prefetch_tmap(&tmW128); prefetch_tmap(&tmW32); }
  if (tid == 0) {
    PROF(0);
    for (int i = 0; i < NST1; ++i) { mbar_init(bars + 8 * (B_FULL1 + i), 1); mbar_init(bars + 8 * (B_EMPTY1 + i), 16); }
    mbar_init(bars + 8 * B_RINGFREE, 1);
    mbar_init(bars + 8 * B_HALO, 1); mbar_init(bars + 8 * (B_HALO + 1), 1);
    for (int i = 0; i < NST2; ++i) { mbar_init(bars + 8 * (B_FULL2 + i), 1); mbar_init(bars + 8 * (B_EMPTY2 + i), 16); }
    mbar_init(bars + 8 * B_U, 1);
    mbar_init(bars + 8 * B_KVST, 8);
    mbar_init(bars + 8 * B_OST, 8); mbar_init(bars + 8 * (B_OST + 1), 8);
    mbar_init(bars + 8 * B_KTST, 4);
    for (int i = 0; i < 5; ++i) mbar_init(bars + 8 * (B_YST + i), 4);
    mbar_init(bars + 8 * B_CIN, 4);
    mbar_init(bars + 8 * B_OPUB, 1);
    mbar_init(bars + 8 * B_PRE, 1);
    mbar_init(bars + 8 * B_FRAW, 1);
    mbar_init(bars + 8 * B_U4, 1);
    mbar_init(bars + 8 * B_STGFREE, 4);
    mbar_init(bars + 8 * B_FFREE, 8);
    asm volatile("fence.mbarrier_init.release.cluster;" ::: "memory");
  }
  __syncthreads();
  asm volatile("barrier.cluster.arrive.relaxed.aligned;\nbarrier.cluster.wait.aligned;" ::: "memory");

  if (wg == 3) {
    asm volatile("setmaxnreg.dec.sync.aligned.u32 32;");
    if (warp == 12 && lane == 0) {
      PROF(15);
      for (int it = 0; it < 10; ++it) {
        const int s = it % NST1;
        if (it >= NST1) mbar_wait(bars + 8 * (B_EMPTY1 + s), ((it / NST1) - 1) & 1);
        PROF(44 + it);
        const uint32_t st = sb + s * ST1, fb = bars + 8 * (B_FULL1 + s);
        mbar_expect(fb, ST1);
        tma2d(st, &tmX, it * 64, rb * 128, fb);
        tma3d_mc(st + ST1_B128 + rank * 12288, &tmW128, g8 * 80, it * 64 + rank * 32, 0, fb);
        tma3d_mc(st + ST1_B32 + rank * 3072, &tmW32, g8 * 80 + 64, it * 64 + rank * 32, 0, fb);
        if (it == PRE_AFTER) {
          mbar_expect(bars + 8 * B_PRE, 131 * 160 + 128 * 160);
          tma2d(sb + OFF_U, &tmKin, jt * 80, tau * 128 - 3, bars + 8 * B_PRE);
          tma2d(sb + OFF_STG, &tmVin, jt * 80, tau * 128, bars + 8 * B_PRE);
        }
        if (it == KVPF_AT) { prefetch_l2(prm.k + (size_t)cta * 10240, 20480); prefetch_l2(prm.v + (size_t)cta * 10240, 20480); }
        if (it == KVPF_AT + 2) prefetch_l2(prm.ssm_k + (size_t)cta * 5 * SEQ, 5 * SEQ * 2);
      }
      PROF(1);
      mbar_wait(bars + 8 * B_RINGFREE, 0);
      for (int p = 0; p < 2; ++p) {
        const uint32_t hb = bars + 8 * (B_HALO + p);
        if (rb == 0) { mbar_arrive(hb); continue; }
        poll_ge(cnt(C_KV + (g8 * 16 + rb - 1) * 2 + p), 1);
        if (rb >= 2) poll_ge(cnt(C_KV + (g8 * 16 + rb - 2) * 2 + p), 1);
        if (p == 0) PROF(2);
        mbar_expect(hb, (rb >= 2 ? 2 : 1) * PAIR);
        bulk_load(sb + p * PWIN + PAIR, g_kv + (size_t)(g8 * 16 + rb - 1) * (SEG / 2) + p * (PAIR / 2), PAIR, hb);
        if (rb >= 2) bulk_load(sb + p * PWIN, g_kv + (size_t)(g8 * 16 + rb - 2) * (SEG / 2) + p * (PAIR / 2), PAIR, hb);
      }
      poll_ge(cnt(C_WO + c2), 16);
#pragma unroll 1
      for (int it = 0; it < 8; ++it) {
        const int s = it & 3, p = it >> 2;
        if (it == 2) mbar_wait(bars + 8 * B_OPUB, 0);
        mbar_wait(bars + 8 * (B_EMPTY2 + s), p);
        const uint32_t fb = bars + 8 * (B_FULL2 + s);
        mbar_expect(fb, ST2);
        const uint16_t* asrc = g_o + (size_t)(rb2 * 80 + p * 40 + (2 * s + rank) * 5) * 1024;
        if (it == 0) { PROF(3); poll_ge(cnt(C_O + rb2 * 2), 8); }
        if (it != 4) {
          if (it != 5 ) bulk_load_mc(sb + s * ST2 + rank * 10240, asrc, 10240, fb);
        }
        bulk_load(sb + s * ST2 + 20480, g_woP + (size_t)(c2 * 8 + it) * 6400, 12800, fb);
        if (it == 5) {
          poll_ge(cnt(C_O + rb2 * 2 + 1), 8);
          PROF(4);
          bulk_load_mc(sb + rank * 10240, asrc - 10 * 1024, 10240, bars + 8 * B_FULL2);
          bulk_load_mc(sb + ST2 + rank * 10240, asrc, 10240, fb);
        }
      }
      finish_role();
    } else if (warp == 13 && lane == 0) {
      prefetch_tmap(&tmOut);
      mbar_wait(bars + 8 * B_KVST, 0);
      uint16_t* kd = g_kv + (size_t)(g8 * 16 + rb) * (SEG / 2);
      bulk_store(kd, sb + 2 * PAIR, PAIR); bulk_commit();
      bulk_wait<0>(); red_publish(cnt(C_KV + (g8 * 16 + rb) * 2));
      PROF(55);
      bulk_store(kd + PAIR / 2, sb + PWIN + 2 * PAIR, PAIR); bulk_commit();
      bulk_wait<0>(); red_publish(cnt(C_KV + (g8 * 16 + rb) * 2 + 1));
      PROF(24);
      for (int p = 0; p < 2; ++p) {
        mbar_wait(bars + 8 * (B_OST + p), 0);
        if (p == 1) PROF(31);
        bulk_store(g_o + (size_t)(rb * 80 + p * 40 + g8 * 5) * 1024, sb + OFF_STG + p * 10240, 10240);
        bulk_commit(); bulk_wait<0>();
        if (p == 1) PROF(54);
        red_publish(cnt(C_O + rb * 2 + p));
      }
      mbar_arrive(bars + 8 * B_OPUB);
      PROF(20);
    } else if (warp == 15) {
      const int run = rp * 2 + (g8 & 1);
      const int gg = run >> 1, pp = run & 1;
      mbar_wait(bars + 8 * (B_FULL1 + 3), 0);
#pragma unroll 1
      for (int i0 = 0; i0 < 13; i0 += 4) {
        uint4 v[4];
#pragma unroll
        for (int i = 0; i < 4; ++i) {
          const int idx = lane + 32 * (i0 + i), j = idx / 10, n8 = idx % 10;
          if (idx < 400) v[i] = ldg_nc(prm.wo + (size_t)(gg * 80 + pp * 40 + j) * DM + c2 * 80 + n8 * 8);
        }
#pragma unroll
        for (int i = 0; i < 4; ++i) {
          const int idx = lane + 32 * (i0 + i), j = idx / 10, n8 = idx % 10;
          if (idx < 400) stg128(g_woP + (size_t)((c2 * 8 + pp * 4 + (gg >> 1)) * 10 + n8) * 640 + ((gg & 1) * 40 + j) * 8, v[i]);
        }
      }
      if (lane == 0) {
        mbar_wait(bars + 8 * B_FFREE, 0);
        mbar_expect(bars + 8 * B_FRAW, 5 * 4096);
        for (int c = 0; c < 5; ++c) bulk_load(sb + OFF_F + c * CH_F + 64, prm.ssm_k + (size_t)(cta * 5 + c) * SEQ, 4096, bars + 8 * B_FRAW);
      }
      __syncwarp();
      asm volatile("fence.acq_rel.gpu;" ::: "memory");
      __syncwarp();
      if (lane == 0) asm volatile("red.relaxed.gpu.global.add.u32 [%0], 1;" ::"l"(cnt(C_WO + c2)) : "memory");
    } else if (warp == 14 && lane == 0) {
      prefetch_tmap(&tmKT);
      mbar_wait(bars + 8 * B_KTST, 0);
      tma3d_store(&tmKT, 128 + 32 * tau, 0, jt * 80, sb + OFF_U);
      bulk_commit();
      bulk_wait<0>();
      red_publish(cnt(C_PRE + jt));
      PROF(8);
      poll_ge(cnt(C_PRE + jt), 16);
      mbar_expect(bars + 8 * B_U, 4 * CH_U);
      bulk_load(sb + OFF_U, g_kvT + (size_t)(cta * 5) * 2560, 4 * CH_U, bars + 8 * B_U);
      mbar_expect(bars + 8 * B_U4, CH_U);
      bulk_load(sb + OFF_U4, g_kvT + (size_t)(cta * 5 + 4) * 2560, CH_U, bars + 8 * B_U4);
      PROF(9);
      for (int c = 0; c < 5; ++c) {
        mbar_wait(bars + 8 * (B_YST + c), 0);
        bulk_store(g_yT + (size_t)(cta * 5 + c) * SEQ, sb + OFF_F + c * CH_F, 4096);
        bulk_commit();
      }
      bulk_wait<0>();
      red_publish(cnt(C_Y + jt), 5);
      PROF(11);
    }
  } else if (wg == 2) {
    asm volatile("setmaxnreg.inc.sync.aligned.u32 144;");
    const int ct = tid - 256, wc = __shfl_sync(0xffffffffu, warp, 0) - 8;
    const int t0 = tau * 128, c0 = jt * 80;
    const int mi = lane >> 3, r = lane & 7, g = lane >> 2, t = lane & 3;
    const uint32_t U = sb + OFF_U, F = sb + OFF_F;
    if (ct == 0) PROF(14);
    uint32_t dpack = lane < 5 ? (uint32_t)__ldg(prm.ssm_D + cta * 5 + lane) : 0u;
    dpack |= dpack << 16;
    {
      const int c = ct % 10, seg = ct / 10;
      uint4 wv[4];
#pragma unroll
      for (int u = 0; u < 4; ++u) wv[u] = ldg_nc(prm.shift_k + (size_t)(c0 + c * 8 + 2 * u) * 4);
      uint32_t W[4][4];
#pragma unroll
      for (int u = 0; u < 4; ++u) {
        W[0][u] = __byte_perm(wv[u].x, wv[u].z, 0x5410); W[1][u] = __byte_perm(wv[u].x, wv[u].z, 0x7632);
        W[2][u] = __byte_perm(wv[u].y, wv[u].w, 0x5410); W[3][u] = __byte_perm(wv[u].y, wv[u].w, 0x7632);
      }
      mbar_wait(bars + 8 * B_PRE, 0);
      if (ct == 0) PROF(5);
      if (ct < 120) {
        const int nrow = seg == 11 ? 7 : 11;
        const uint32_t ka = U + seg * 11 * 160 + c * 16, va = sb + OFF_STG + seg * 11 * 160 + c * 16;
        uint4 kk[14], vv[11];
#pragma unroll
        for (int i = 0; i < 14; ++i) kk[i] = i < nrow + 3 ? lds128(ka + i * 160) : make_uint4(0, 0, 0, 0);
#pragma unroll
        for (int i = 0; i < 11; ++i) vv[i] = i < nrow ? lds128(va + i * 160) : make_uint4(0, 0, 0, 0);
#pragma unroll
        for (int i = 0; i < 11; ++i) {
          uint32_t res[4];
#pragma unroll
          for (int u = 0; u < 4; ++u) {
            uint32_t acc = hmul2((&kk[i].x)[u], W[3][u]);
            acc = hfma2((&kk[i + 1].x)[u], W[2][u], acc);
            acc = hfma2((&kk[i + 2].x)[u], W[1][u], acc);
            acc = hfma2((&kk[i + 3].x)[u], W[0][u], acc);
            res[u] = hmul2(acc, (&vv[i].x)[u]);
          }
          if (i < nrow) sts128(va + i * 160, make_uint4(res[0], res[1], res[2], res[3]));
        }
      }
    }
    if (ct == 0) PROF(6);
    named_sync(3, 128);
    {
      uint4 v4[10];
#pragma unroll
      for (int k = 0; k < 10; ++k) {
        const int it = wc + 4 * k, c = it % 10, q = it / 10;
        const int tl = 32 * (r >> 1) + 31 - (8 * q + 2 * mi + (r & 1));
        ldsm4t(v4[k].x, v4[k].y, v4[k].z, v4[k].w, sb + OFF_STG + tl * 160 + c * 16);
      }
#pragma unroll
      for (int k = 0; k < 10; ++k) {
        const int it = wc + 4 * k, c = it % 10, q = it / 10;
        sts128(U + (c * 8 + g) * 256 + q * 64 + t * 16, v4[k]);
      }
    }
    fence_async_smem();
    __syncwarp();
    if (lane == 0) { mbar_arrive(bars + 8 * B_KTST); mbar_arrive(bars + 8 * B_STGFREE); }
    if (ct == 0) PROF(7);
    if (ct < 32) prefetch_line(prm.q + ((size_t)cta * 160 + 128 + ct) * 64);
    prefetch_line(prm.q + ((size_t)cta * 160 + ct) * 64);
    mbar_wait(bars + 8 * B_FRAW, 0);
    {
      uint4 fv[10]; uint32_t pv[10];
#pragma unroll
      for (int i = 0; i < 10; ++i) {
        const int cl = i >> 1, qq = ct + (i & 1) * 128;
        const uint32_t a = F + cl * CH_F + 64 + qq * 16;
        fv[i] = lds128(a);
        pv[i] = qq > 0 ? lds32(a - 4) >> 16 : 0u;
      }
#pragma unroll
      for (int i = 0; i < 10; ++i) {
        const int cl = i >> 1, qq = ct + (i & 1) * 128;
        sts128(F + cl * CH_F + 64 + qq * 16 + 4160,
               make_uint4(__byte_perm(pv[i], fv[i].x, 0x5410), __byte_perm(fv[i].x, fv[i].y, 0x5432),
                          __byte_perm(fv[i].y, fv[i].z, 0x5432), __byte_perm(fv[i].z, fv[i].w, 0x5432)));
      }
      if (ct < 40) sts128(F + (ct >> 3) * CH_F + ((ct >> 2) & 1) * 4160 + (ct & 3) * 16, make_uint4(0, 0, 0, 0));
    }
    mbar_wait(bars + 8 * B_U, 0);
    for (int i = ct; i < 256; i += 128) sts128(U + (i >> 6) * CH_U + ((i >> 4) & 3) * UPL + (i & 15) * 16, make_uint4(0, 0, 0, 0));
    fence_async_smem();
    named_sync(3, 128);
    if (ct == 0) PROF(10);
    if (lane == 0) mbar_arrive(bars + 8 * B_CIN);
    constexpr int NOWN = 5;
#pragma unroll 1
    for (int i = 0; i < NOWN; ++i) {
      const int cl = NOWN == 5 ? i : (i == 0 ? 0 : i + 2);
      if (cl == 4) {
        mbar_wait(bars + 8 * B_U4, 0);
        if (ct < 64) sts128(sb + OFF_U4 + (ct >> 4) * UPL + (ct & 15) * 16, make_uint4(0, 0, 0, 0));
        fence_async_smem();
        named_sync(3, 128);
      }
      conv_channel(sb, cl, wc, lane, __shfl_sync(0xffffffffu, dpack, cl), 3);
      if (ct == 0 && i == 0) PROF(27);
    }
    if (ct == 0) PROF(30);
    uint4 qv[10];
#pragma unroll
    for (int i = 0; i < 10; ++i) {
      const int idx = ct + 128 * i, row = idx / 10, c = idx % 10;
      qv[i] = ldg_nc(prm.q + (size_t)(t0 + row) * DM + c0 + c * 8);
    }
    if (ct == 0) { poll_ge(cnt(C_Y + jt), 80); finish_role(); PROF(12); }
    named_sync(3, 128);
    const uint32_t YT = sb + OFF_F, YN = sb + OFF_F + 21760;
#pragma unroll
    for (int i = 0; i < 10; ++i) {
      const int idx = ct + 128 * i, ch = idx >> 4, cq = idx & 15;
      sts128(YT + ch * 272 + cq * 16, ldg_cg(g_yT + (size_t)(c0 + ch) * SEQ + t0 + cq * 8));
    }
    named_sync(3, 128);
#pragma unroll 1
    for (int it = wc; it < 40; it += 4) {
      const int c = it % 10, tq = it / 10;
      uint32_t x0, x1, x2, x3;
      ldsm4t(x0, x1, x2, x3, YT + (8 * c + r) * 272 + (4 * tq + mi) * 16);
      const int s = (8 * (4 * tq + mi) + r) ^ 31;
      stsm4(YN + s * 176 + c * 16, x0, x1, x2, x3);
    }
    named_sync(3, 128);
#pragma unroll
    for (int i = 0; i < 10; ++i) {
      const int idx = ct + 128 * i, row = idx / 10, c = idx % 10;
      const uint4 y = lds128(YN + row * 176 + c * 16);
      stg128(prm.out + (size_t)(t0 + row) * (2 * DM) + c0 + c * 8,
             make_uint4(hmul2(qv[i].x, y.x), hmul2(qv[i].y, y.y), hmul2(qv[i].z, y.z), hmul2(qv[i].w, y.w)));
    }
    if (ct == 0) PROF(13);
  } else {
    asm volatile("setmaxnreg.inc.sync.aligned.u32 168;");
    const int wq = __shfl_sync(0xffffffffu, warp, 0);
    const int mi = lane >> 3, r = lane & 7;
    const uint32_t stg = sb + OFF_STG;
    {
      float acc1[96], acc2[24];
#pragma unroll 1
      for (int it = 0; it < 10; ++it) {
        const int s = it % NST1;
        mbar_wait(bars + 8 * (B_FULL1 + s), (it / NST1) & 1);
        if (tid == 0) PROF(32 + it);
        const uint32_t st = sb + s * ST1;
        wg_fence();
#pragma unroll
        for (int kk = 0; kk < 4; ++kk) {
          const uint64_t da = make_desc(st + wg * 8192 + kk * 32, 16, 1024, 1);
          const uint64_t db1 = make_desc(st + ST1_B128 + (kk >> 1) * 12288 + (kk & 1) * 2048, 4096, 1024, 1);
          const uint64_t db2 = make_desc(st + ST1_B32 + (kk >> 1) * 3072 + (kk & 1) * 512, 1024, 256, 3);
          wgmma_n192(acc1, da, db1, (it | kk) != 0);
          wgmma_n48(acc2, da, db2, (it | kk) != 0);
        }
        wg_commit();
        wg_wait<0>();
        if (it + NST1 < 10 && lane < 2) mbar_arrive_cta(bars + 8 * (B_EMPTY1 + s), lane);
        if (it == 7 && lane == 0) mbar_arrive(bars + 8 * B_FFREE);
      }
      reg_fence(acc1); reg_fence(acc2);
      if (tid == 0) PROF(17);
      named_sync(1, 256);
      if (tid == 0) mbar_arrive(bars + 8 * B_RINGFREE);
      const uint32_t rowo = (16 * wq + 8 * (mi & 1) + r) * 16;
      const int t4 = lane & 3;
#pragma unroll
      for (int kv = 0; kv < 2; ++kv) {
#pragma unroll
        for (int tp = 0; tp < 5; ++tp) {
          uint32_t w[4];
#pragma unroll
          for (int hh = 0; hh < 2; ++hh) {
            const int tile = 2 * tp + hh;
            if (tile < 8) {
              const int o = 32 * (kv + 1) + 4 * tile;
              w[2 * hh] = pack_bf16(acc1[o], acc1[o + 1]); w[2 * hh + 1] = pack_bf16(acc1[o + 2], acc1[o + 3]);
            } else {
              const int o = 8 * (kv + 1) + 4 * (tile - 8);
              w[2 * hh] = pack_bf16(acc2[o], acc2[o + 1]); w[2 * hh + 1] = pack_bf16(acc2[o + 2], acc2[o + 3]);
            }
          }
          const int tA = 2 * tp, tB = 2 * tp + 1;
          const int plA = (tA / 5) * 33 + (kv ? 5 : 0) + tA % 5, plB = (tB / 5) * 33 + (kv ? 5 : 0) + tB % 5;
          if (kv == 1 && (tA % 5 == 2 || tB % 5 == 2)) {
            const int hh = (tA % 5 == 2) ? 0 : 1, pr = (hh ? tB : tA) / 5;
            const uint32_t x0 = w[2 * hh], x1 = w[2 * hh + 1];
            const uint32_t oneE = t4 == 2 ? 0x00003F80u : 0u, oneO = t4 == 0 ? 0x00003F80u : 0u;
            stsm2(sb + 2 * PAIR + (pr * 33 + 10) * PLANE + (16 * wq + (lane & 15)) * 16, t4 >= 2 ? x0 : oneO, t4 >= 2 ? x1 : oneO);
            w[2 * hh] = t4 < 2 ? x0 : oneE; w[2 * hh + 1] = t4 < 2 ? x1 : oneE;
          }
          stsm4(sb + 2 * PAIR + rowo + ((mi >> 1) ? plB : plA) * PLANE, w[0], w[1], w[2], w[3]);
        }
      }
      fence_async_smem();
      __syncwarp();
      if (lane == 0) mbar_arrive(bars + 8 * B_KVST);
      mbar_wait(bars + 8 * B_STGFREE, 0);
      const uint32_t rq = stg + rowo + (mi >> 1) * PLANE;
#pragma unroll
      for (int tp = 0; tp < 4; ++tp)
        stsm4(rq + tp * 2 * PLANE, pack_bf16(acc1[8 * tp], acc1[8 * tp + 1]), pack_bf16(acc1[8 * tp + 2], acc1[8 * tp + 3]),
              pack_bf16(acc1[8 * tp + 4], acc1[8 * tp + 5]), pack_bf16(acc1[8 * tp + 6], acc1[8 * tp + 7]));
      stsm4(rq + 8 * PLANE, pack_bf16(acc2[0], acc2[1]), pack_bf16(acc2[2], acc2[3]), pack_bf16(acc2[4], acc2[5]), pack_bf16(acc2[6], acc2[7]));
    }
    if (rb < 2) {
      const int nz = (2 - rb) * (PAIR / 16);
#pragma unroll 1
      for (int i = tid; i < 2 * nz; i += 256) sts128(sb + (i >= nz ? PWIN + (i - nz) * 16 : i * 16), make_uint4(0, 0, 0, 0));
      fence_async_smem();
    }
    named_sync(2, 256);
    if (tid == 0) PROF(18);
    attn_all(sb, stg, bars, wq, lane, rb >= 2 ? 0 : 4 - 2 * rb);
    if (tid == 0) PROF(19);
    float acc[40];
#pragma unroll 1
    for (int it = 0; it < 8; ++it) {
      const int s = it & 3;
      mbar_wait(bars + 8 * (B_FULL2 + s), it >> 2);
      if (it == 0 && tid == 0) PROF(21);
      if (it == 4 && tid == 0) PROF(25);
      const uint32_t st = sb + s * ST2;
      wg_fence();
#pragma unroll
      for (int kk = 0; kk < 5; ++kk)
        wgmma_n80(acc, make_desc(st + wg * 1024 + kk * 2 * PLANE, PLANE, 128, 0), make_desc(st + 20480 + kk * 256, 128, 1280, 0), (it | kk) != 0);
      wg_commit();
      wg_wait<0>();
      if (it < 4 && lane < 2) mbar_arrive_cta(bars + 8 * (B_EMPTY2 + s), lane);
    }
    reg_fence(acc);
    if (tid == 0) PROF(22);
    named_sync(1, 256);
    {
      const uint32_t rowa = sb + (16 * wq + 8 * (mi & 1) + r) * 160 + (mi >> 1) * 16;
#pragma unroll
      for (int tp = 0; tp < 5; ++tp)
        stsm4(rowa + tp * 32, pack_bf16(acc[8 * tp], acc[8 * tp + 1]), pack_bf16(acc[8 * tp + 2], acc[8 * tp + 3]),
              pack_bf16(acc[8 * tp + 4], acc[8 * tp + 5]), pack_bf16(acc[8 * tp + 6], acc[8 * tp + 7]));
      fence_async_smem();
      __syncwarp();
      if (lane == 0) {
        tma2d_store(&tmOut, DM + c2 * 80, rb2 * 128 + 16 * wq, sb + wq * 2560);
        bulk_commit();
        bulk_wait0_read();
      }
    }
    if (tid == 0) PROF(23);
  }
}

typedef CUresult (*EncodeFn)(CUtensorMap*, CUtensorMapDataType, cuuint32_t, void*, const cuuint64_t*, const cuuint64_t*,
                             const cuuint32_t*, const cuuint32_t*, CUtensorMapInterleave, CUtensorMapSwizzle,
                             CUtensorMapL2promotion, CUtensorMapFloatOOBfill);

CUtensorMap make_map(EncodeFn enc, const void* p, int rank, const cuuint64_t* dims, const cuuint64_t* strides,
                     const cuuint32_t* box, CUtensorMapSwizzle sw) {
  CUtensorMap m;
  const cuuint32_t es[5] = {1, 1, 1, 1, 1};
  enc(&m, CU_TENSOR_MAP_DATA_TYPE_BFLOAT16, rank, const_cast<void*>(p), dims, strides, box, es,
      CU_TENSOR_MAP_INTERLEAVE_NONE, sw, CU_TENSOR_MAP_L2_PROMOTION_L2_128B, CU_TENSOR_MAP_FLOAT_OOB_FILL_NONE);
  return m;
}

}

extern "C" void kernel_launch(void* const* d_in, const int* in_sizes, int n_in, void* d_out, int out_size) {
  (void)in_sizes; (void)n_in; (void)out_size;
  static EncodeFn enc = nullptr;
  static void* kt_ptr = nullptr;
  if (!enc) {
    void* fn = nullptr;
    cudaDriverEntryPointQueryResult qr;
    cudaGetDriverEntryPoint("cuTensorMapEncodeTiled", &fn, cudaEnableDefault, &qr);
    enc = (EncodeFn)fn;
    cudaGetSymbolAddress(&kt_ptr, g_kvT);
    cudaFuncSetAttribute(h3_swa_fused_kernel, cudaFuncAttributeMaxDynamicSharedMemorySize, SMEM_BYTES);
  }
  const void* x = d_in[6];
  const void* wqkv = d_in[7];
  const void* wo = d_in[8];
  CUtensorMap tmX, tmW128, tmW32, tmOut, tmKT, tmKin, tmVin;
  { cuuint64_t d[2] = {640, 2048}, s[1] = {1280}; cuuint32_t b[2] = {64, 128};
    tmX = make_map(enc, x, 2, d, s, b, CU_TENSOR_MAP_SWIZZLE_128B); }
  { cuuint64_t d[3] = {640, 640, 3}, s[2] = {3840, 1280}; cuuint32_t b[3] = {64, 32, 3};
    tmW128 = make_map(enc, wqkv, 3, d, s, b, CU_TENSOR_MAP_SWIZZLE_128B); }
  { cuuint64_t d[3] = {640, 640, 3}, s[2] = {3840, 1280}; cuuint32_t b[3] = {16, 32, 3};
    tmW32 = make_map(enc, wqkv, 3, d, s, b, CU_TENSOR_MAP_SWIZZLE_32B); }
  { cuuint64_t d[2] = {1280, 2048}, s[1] = {2560}; cuuint32_t b[2] = {80, 16};
    tmOut = make_map(enc, d_out, 2, d, s, b, CU_TENSOR_MAP_SWIZZLE_NONE); }
  { cuuint64_t d[3] = {640, 4, 640}, s[2] = {1280, 5120}; cuuint32_t b[3] = {32, 4, 80};
    tmKT = make_map(enc, kt_ptr, 3, d, s, b, CU_TENSOR_MAP_SWIZZLE_NONE); }
  { cuuint64_t d[2] = {640, 2048}, s[1] = {1280}; cuuint32_t b[2] = {80, 131};
    tmKin = make_map(enc, d_in[1], 2, d, s, b, CU_TENSOR_MAP_SWIZZLE_NONE); }
  { cuuint64_t d[2] = {640, 2048}, s[1] = {1280}; cuuint32_t b[2] = {80, 128};
    tmVin = make_map(enc, d_in[2], 2, d, s, b, CU_TENSOR_MAP_SWIZZLE_NONE); }
  Params prm;
  prm.q = (const uint16_t*)d_in[0]; prm.k = (const uint16_t*)d_in[1]; prm.v = (const uint16_t*)d_in[2];
  prm.x = (const uint16_t*)x; prm.wqkv = (const uint16_t*)wqkv; prm.wo = (const uint16_t*)wo;
  prm.shift_k = (const uint16_t*)d_in[3]; prm.ssm_k = (const uint16_t*)d_in[4];
  prm.ssm_D = (const uint16_t*)d_in[5]; prm.out = (uint16_t*)d_out;
  h3_swa_fused_kernel<<<128, 512, SMEM_BYTES>>>(tmX, tmW128, tmW32, tmOut, tmKT, tmKin, tmVin, prm);
}
```

```cpp
#include <cuda_runtime.h>
#include <cuda.h>
#include <cuda_bf16.h>
#include <stdint.h>

#define DEVINL __device__ __forceinline__

namespace {

constexpr int SEQ = 2048;
constexpr int DM = 640;

constexpr int ST1 = 47104;
constexpr int ST1_B128 = 16384;
constexpr int ST1_B32 = 40960;
constexpr int NST1 = 4;
constexpr int ST2 = 33280;
constexpr int NST2 = 4;
constexpr int CH_U = 5120;
constexpr int UPL = 1280;
constexpr int CH_F = 8320;
constexpr int OFF_F = 3 * ST1;
constexpr int OFF_U = 4 * ST1;
constexpr int OFF_KT = OFF_F + 3 * CH_F;
constexpr int OFF_U4 = OFF_F + 5 * CH_F;
constexpr int OFF_STG = OFF_U + 21120;
constexpr int OFF_BAR = OFF_STG + 20480;
constexpr int SMEM_BYTES = OFF_BAR + 512;

constexpr int B_FULL1 = 0, B_EMPTY1 = 4, B_RINGFREE = 8, B_HALO = 9, B_FULL2 = 11, B_EMPTY2 = 15, B_U = 19, B_KVST = 20,
              B_OST = 21, B_PRE = 23, B_KTST = 24, B_U4 = 25, B_STGFREE = 26, B_FFREE = 27, B_CIN = 28, B_YST = 29, B_OPUB = 34, B_FRAW = 35, B_QT = 36, B_YT = 37, B_P0PUB = 38;

__device__ __align__(1024) uint16_t g_kv[8 * 16 * 22 * 1024];
__device__ __align__(1024) uint16_t g_o[SEQ * DM];
__device__ __align__(1024) uint16_t g_kvT[DM * SEQ];
__device__ __align__(1024) uint16_t g_yT[DM * SEQ];
__device__ __align__(1024) uint16_t g_woP[DM * DM];
constexpr int CS = 32;
constexpr int C_KV = 0, C_O = 256, C_PRE = 288, C_Y = 296, C_WO = 304, C_DONE = 312, C_NUM = 313;
__device__ unsigned g_cnt[C_NUM * CS];
__device__ unsigned g_err;
#define PROF(slot) do {} while (0)

#define POLL_SLEEP 0
DEVINL void mbar_init(uint32_t a, uint32_t c) { asm volatile("mbarrier.init.shared::cta.b64 [%0], %1;" ::"r"(a), "r"(c)); }
DEVINL void mbar_expect(uint32_t a, uint32_t b) {
  asm volatile("mbarrier.arrive.expect_tx.shared::cta.b64 _, [%0], %1;" ::"r"(a), "r"(b) : "memory");
}
DEVINL void mbar_arrive(uint32_t a) { asm volatile("mbarrier.arrive.shared::cta.b64 _, [%0];" ::"r"(a) : "memory"); }
DEVINL void mbar_arrive_cta(uint32_t a, uint32_t cta) {
  asm volatile("{\n.reg .b32 ra;\nmapa.shared::cluster.u32 ra, %0, %1;\nmbarrier.arrive.shared::cluster.b64 _, [ra];\n}"
               ::"r"(a), "r"(cta) : "memory");
}
DEVINL bool mbar_try(uint32_t a, uint32_t p) {
  uint32_t ok;
  asm volatile("{\n.reg .pred P;\nmbarrier.try_wait.parity.shared::cta.b64 P, [%1], %2;\nselp.u32 %0, 1, 0, P;\n}"
               : "=r"(ok) : "r"(a), "r"(p) : "memory");
  return ok;
}
DEVINL void mbar_wait(uint32_t a, uint32_t p) {
  if (mbar_try(a, p)) return;
  int n = 0;
  while (!mbar_try(a, p)) {
    if (++n > (1 << 18)) { g_err = 1; break; }
  }
}
DEVINL void poll_ge(const unsigned* p, unsigned target) {
  int n = 0;
  while (true) {
    unsigned v;
    asm volatile("ld.relaxed.gpu.global.u32 %0, [%1];" : "=r"(v) : "l"(p) : "memory");
    if (v >= target) break;
    if (++n > (1 << 20)) { g_err = 2; break; }
  }
}
DEVINL void red_publish(unsigned* p, unsigned n = 1) { asm volatile("red.release.gpu.global.add.u32 [%0], %1;" ::"l"(p), "r"(n) : "memory"); }
DEVINL void fence_async_smem() { asm volatile("fence.proxy.async.shared::cta;" ::: "memory"); }
DEVINL void named_sync(int id, int n) { asm volatile("bar.sync %0, %1;" ::"r"(id), "r"(n) : "memory"); }
DEVINL void named_arrive(int id, int n) { asm volatile("bar.arrive %0, %1;" ::"r"(id), "r"(n) : "memory"); }

DEVINL void tma2d(uint32_t dst, const CUtensorMap* m, int c0, int c1, uint32_t bar) {
  asm volatile("cp.async.bulk.tensor.2d.shared::cluster.global.mbarrier::complete_tx::bytes [%0], [%1, {%3, %4}], [%2];"
               ::"r"(dst), "l"(m), "r"(bar), "r"(c0), "r"(c1) : "memory");
}
DEVINL void tma2d_mc(uint32_t dst, const CUtensorMap* m, int c0, int c1, uint32_t bar) {
  asm volatile("cp.async.bulk.tensor.2d.shared::cluster.global.mbarrier::complete_tx::bytes.multicast::cluster [%0], [%1, {%3, %4}], [%2], %5;"
               ::"r"(dst), "l"(m), "r"(bar), "r"(c0), "r"(c1), "h"((uint16_t)3) : "memory");
}
DEVINL void tma3d(uint32_t dst, const CUtensorMap* m, int c0, int c1, int c2, uint32_t bar) {
  asm volatile("cp.async.bulk.tensor.3d.shared::cluster.global.mbarrier::complete_tx::bytes [%0], [%1, {%3, %4, %5}], [%2];"
               ::"r"(dst), "l"(m), "r"(bar), "r"(c0), "r"(c1), "r"(c2) : "memory");
}
DEVINL void tma3d_mc(uint32_t dst, const CUtensorMap* m, int c0, int c1, int c2, uint32_t bar) {
  asm volatile("cp.async.bulk.tensor.3d.shared::cluster.global.mbarrier::complete_tx::bytes.multicast::cluster [%0], [%1, {%3, %4, %5}], [%2], %6;"
               ::"r"(dst), "l"(m), "r"(bar), "r"(c0), "r"(c1), "r"(c2), "h"((uint16_t)3) : "memory");
}
DEVINL void tma2d_store(const CUtensorMap* m, int c0, int c1, uint32_t src) {
  asm volatile("cp.async.bulk.tensor.2d.global.shared::cta.bulk_group [%0, {%2, %3}], [%1];"
               ::"l"(m), "r"(src), "r"(c0), "r"(c1) : "memory");
}
DEVINL void tma3d_store(const CUtensorMap* m, int c0, int c1, int c2, uint32_t src) {
  asm volatile("cp.async.bulk.tensor.3d.global.shared::cta.bulk_group [%0, {%2, %3, %4}], [%1];"
               ::"l"(m), "r"(src), "r"(c0), "r"(c1), "r"(c2) : "memory");
}
DEVINL void bulk_load(uint32_t dst, const void* src, uint32_t bytes, uint32_t bar) {
  asm volatile("cp.async.bulk.shared::cluster.global.mbarrier::complete_tx::bytes [%0], [%1], %2, [%3];"
               ::"r"(dst), "l"(src), "r"(bytes), "r"(bar) : "memory");
}
DEVINL void bulk_load_mc(uint32_t dst, const void* src, uint32_t bytes, uint32_t bar) {
  asm volatile("cp.async.bulk.shared::cluster.global.mbarrier::complete_tx::bytes.multicast::cluster [%0], [%1], %2, [%3], %4;"
               ::"r"(dst), "l"(src), "r"(bytes), "r"(bar), "h"((uint16_t)3) : "memory");
}
DEVINL void tma4d(uint32_t dst, const CUtensorMap* m, int c0, int c1, int c2, int c3, uint32_t bar) {
  asm volatile("cp.async.bulk.tensor.4d.shared::cluster.global.mbarrier::complete_tx::bytes [%0], [%1, {%3, %4, %5, %6}], [%2];"
               ::"r"(dst), "l"(m), "r"(bar), "r"(c0), "r"(c1), "r"(c2), "r"(c3) : "memory");
}
DEVINL void tma5d(uint32_t dst, const CUtensorMap* m, int c0, int c1, int c2, int c3, int c4, uint32_t bar) {
  asm volatile("cp.async.bulk.tensor.5d.shared::cluster.global.mbarrier::complete_tx::bytes [%0], [%1, {%3, %4, %5, %6, %7}], [%2];"
               ::"r"(dst), "l"(m), "r"(bar), "r"(c0), "r"(c1), "r"(c2), "r"(c3), "r"(c4) : "memory");
}
DEVINL void prefetch_line(const void* p) { asm volatile("prefetch.global.L2 [%0];" ::"l"(p)); }
DEVINL void prefetch_l2(const void* p, uint32_t bytes) {
  asm volatile("cp.async.bulk.prefetch.L2.global [%0], %1;" ::"l"(p), "r"(bytes) : "memory");
}
template <int N> DEVINL void bulk_wait() { asm volatile("cp.async.bulk.wait_group %0;" ::"n"(N) : "memory"); }
DEVINL void bulk_store(void* dst, uint32_t src, uint32_t bytes) {
  asm volatile("cp.async.bulk.global.shared::cta.bulk_group [%0], [%1], %2;" ::"l"(dst), "r"(src), "r"(bytes) : "memory");
}
DEVINL void bulk_commit() { asm volatile("cp.async.bulk.commit_group;" ::: "memory"); }
DEVINL void bulk_wait0() { asm volatile("cp.async.bulk.wait_group 0;" ::: "memory"); }
DEVINL void bulk_wait0_read() { asm volatile("cp.async.bulk.wait_group.read 0;" ::: "memory"); }
DEVINL void prefetch_tmap(const CUtensorMap* m) { asm volatile("prefetch.tensormap [%0];" ::"l"(m) : "memory"); }

DEVINL uint64_t make_desc(uint32_t addr, uint32_t lbo, uint32_t sbo, uint32_t swz) {
  return (uint64_t)((addr & 0x3FFFF) >> 4) | ((uint64_t)(lbo >> 4) << 16) | ((uint64_t)(sbo >> 4) << 32) | ((uint64_t)swz << 62);
}
DEVINL void wg_fence() { asm volatile("wgmma.fence.sync.aligned;" ::: "memory"); }
DEVINL void wg_commit() { asm volatile("wgmma.commit_group.sync.aligned;" ::: "memory"); }
template <int N> DEVINL void wg_wait() { asm volatile("wgmma.wait_group.sync.aligned %0;" ::"n"(N) : "memory"); }

DEVINL void mma16816(float (&d)[4], uint32_t a0, uint32_t a1, uint32_t a2, uint32_t a3, uint32_t b0, uint32_t b1) {
  asm volatile("mma.sync.aligned.m16n8k16.row.col.f32.bf16.bf16.f32 {%0,%1,%2,%3},{%4,%5,%6,%7},{%8,%9},{%0,%1,%2,%3};"
               : "+f"(d[0]), "+f"(d[1]), "+f"(d[2]), "+f"(d[3]) : "r"(a0), "r"(a1), "r"(a2), "r"(a3), "r"(b0), "r"(b1));
}
DEVINL void mma16816_z(float (&d)[4], uint32_t a0, uint32_t a1, uint32_t a2, uint32_t a3, uint32_t b0, uint32_t b1) {
  asm volatile("mma.sync.aligned.m16n8k16.row.col.f32.bf16.bf16.f32 {%0,%1,%2,%3},{%4,%5,%6,%7},{%8,%9},{%10,%10,%10,%10};"
               : "=f"(d[0]), "=f"(d[1]), "=f"(d[2]), "=f"(d[3]) : "r"(a0), "r"(a1), "r"(a2), "r"(a3), "r"(b0), "r"(b1), "f"(0.f));
}
DEVINL void mma1688(float (&d)[4], uint32_t a0, uint32_t a1, uint32_t b0) {
  asm volatile("mma.sync.aligned.m16n8k8.row.col.f32.bf16.bf16.f32 {%0,%1,%2,%3},{%4,%5},{%6},{%0,%1,%2,%3};"
               : "+f"(d[0]), "+f"(d[1]), "+f"(d[2]), "+f"(d[3]) : "r"(a0), "r"(a1), "r"(b0));
}
DEVINL void ldsm4(uint32_t& r0, uint32_t& r1, uint32_t& r2, uint32_t& r3, uint32_t a) {
  asm volatile("ldmatrix.sync.aligned.m8n8.x4.shared.b16 {%0,%1,%2,%3}, [%4];" : "=r"(r0), "=r"(r1), "=r"(r2), "=r"(r3) : "r"(a));
}
DEVINL void ldsm2(uint32_t& r0, uint32_t& r1, uint32_t a) {
  asm volatile("ldmatrix.sync.aligned.m8n8.x2.shared.b16 {%0,%1}, [%2];" : "=r"(r0), "=r"(r1) : "r"(a));
}
DEVINL void ldsm4t(uint32_t& r0, uint32_t& r1, uint32_t& r2, uint32_t& r3, uint32_t a) {
  asm volatile("ldmatrix.sync.aligned.m8n8.x4.trans.shared.b16 {%0,%1,%2,%3}, [%4];" : "=r"(r0), "=r"(r1), "=r"(r2), "=r"(r3) : "r"(a));
}
DEVINL void ldsm2t(uint32_t& r0, uint32_t& r1, uint32_t a) {
  asm volatile("ldmatrix.sync.aligned.m8n8.x2.trans.shared.b16 {%0,%1}, [%2];" : "=r"(r0), "=r"(r1) : "r"(a));
}
DEVINL void stsm4(uint32_t a, uint32_t r0, uint32_t r1, uint32_t r2, uint32_t r3) {
  asm volatile("stmatrix.sync.aligned.m8n8.x4.shared.b16 [%0], {%1,%2,%3,%4};" ::"r"(a), "r"(r0), "r"(r1), "r"(r2), "r"(r3) : "memory");
}
DEVINL void stsm2(uint32_t a, uint32_t r0, uint32_t r1) {
  asm volatile("stmatrix.sync.aligned.m8n8.x2.shared.b16 [%0], {%1,%2};" ::"r"(a), "r"(r0), "r"(r1) : "memory");
}
DEVINL void stsm4t(uint32_t a, uint32_t r0, uint32_t r1, uint32_t r2, uint32_t r3) {
  asm volatile("stmatrix.sync.aligned.m8n8.x4.trans.shared.b16 [%0], {%1,%2,%3,%4};" ::"r"(a), "r"(r0), "r"(r1), "r"(r2), "r"(r3) : "memory");
}
DEVINL uint32_t lds32(uint32_t a) { uint32_t v; asm volatile("ld.shared.u32 %0, [%1];" : "=r"(v) : "r"(a)); return v; }
DEVINL uint32_t lds32v(uint32_t a) { uint32_t v; asm volatile("ld.volatile.shared.u32 %0, [%1];" : "=r"(v) : "r"(a) : "memory"); return v; }
DEVINL uint4 lds128(uint32_t a) {
  uint4 v; asm volatile("ld.shared.v4.u32 {%0,%1,%2,%3}, [%4];" : "=r"(v.x), "=r"(v.y), "=r"(v.z), "=r"(v.w) : "r"(a)); return v;
}
DEVINL void sts32(uint32_t a, uint32_t v) { asm volatile("st.shared.u32 [%0], %1;" ::"r"(a), "r"(v) : "memory"); }
DEVINL void sts128(uint32_t a, uint4 v) {
  asm volatile("st.shared.v4.u32 [%0], {%1,%2,%3,%4};" ::"r"(a), "r"(v.x), "r"(v.y), "r"(v.z), "r"(v.w) : "memory");
}
DEVINL uint4 ldg_nc(const void* p) {
  uint4 v; asm volatile("ld.global.nc.L1::no_allocate.v4.u32 {%0,%1,%2,%3}, [%4];" : "=r"(v.x), "=r"(v.y), "=r"(v.z), "=r"(v.w) : "l"(p)); return v;
}
DEVINL uint4 ldg_cg(const void* p) {
  uint4 v; asm volatile("ld.global.cg.v4.u32 {%0,%1,%2,%3}, [%4];" : "=r"(v.x), "=r"(v.y), "=r"(v.z), "=r"(v.w) : "l"(p) : "memory"); return v;
}
DEVINL void stg128(void* p, uint4 v) {
  asm volatile("st.global.v4.u32 [%0], {%1,%2,%3,%4};" ::"l"(p), "r"(v.x), "r"(v.y), "r"(v.z), "r"(v.w) : "memory");
}
DEVINL uint32_t pack_bf16(float lo, float hi) {
  uint32_t r; asm("cvt.rn.bf16x2.f32 %0, %1, %2;" : "=r"(r) : "f"(hi), "f"(lo)); return r;
}
DEVINL uint32_t hmul2(uint32_t a, uint32_t b) { uint32_t r; asm("mul.rn.bf16x2 %0, %1, %2;" : "=r"(r) : "r"(a), "r"(b)); return r; }
DEVINL uint32_t hfma2(uint32_t a, uint32_t b, uint32_t c) { uint32_t r; asm("fma.rn.bf16x2 %0, %1, %2, %3;" : "=r"(r) : "r"(a), "r"(b), "r"(c)); return r; }
DEVINL uint32_t hadd2(uint32_t a, uint32_t b) { uint32_t r; asm("add.rn.bf16x2 %0, %1, %2;" : "=r"(r) : "r"(a), "r"(b)); return r; }
DEVINL float ex2(float x) { float r; asm("ex2.approx.ftz.f32 %0, %1;" : "=f"(r) : "f"(x)); return r; }

DEVINL void wgmma_n192(float (&d)[96], uint64_t da, uint64_t db, int scale_d) {
  asm volatile("{\n.reg .pred p;\nsetp.ne.b32 p, %98, 0;\n"
    "wgmma.mma_async.sync.aligned.m64n192k16.f32.bf16.bf16 "
    "{%0,%1,%2,%3,%4,%5,%6,%7,%8,%9,%10,%11,%12,%13,%14,%15,"
    "%16,%17,%18,%19,%20,%21,%22,%23,%24,%25,%26,%27,%28,%29,%30,%31,"
    "%32,%33,%34,%35,%36,%37,%38,%39,%40,%41,%42,%43,%44,%45,%46,%47,"
    "%48,%49,%50,%51,%52,%53,%54,%55,%56,%57,%58,%59,%60,%61,%62,%63,"
    "%64,%65,%66,%67,%68,%69,%70,%71,%72,%73,%74,%75,%76,%77,%78,%79,"
    "%80,%81,%82,%83,%84,%85,%86,%87,%88,%89,%90,%91,%92,%93,%94,%95}, "
    "%96, %97, p, 1, 1, 0, 1;\n}\n"
    : "+f"(d[0]), "+f"(d[1]), "+f"(d[2]), "+f"(d[3]), "+f"(d[4]), "+f"(d[5]), "+f"(d[6]), "+f"(d[7]),
      "+f"(d[8]), "+f"(d[9]), "+f"(d[10]), "+f"(d[11]), "+f"(d[12]), "+f"(d[13]), "+f"(d[14]), "+f"(d[15]),
      "+f"(d[16]), "+f"(d[17]), "+f"(d[18]), "+f"(d[19]), "+f"(d[20]), "+f"(d[21]), "+f"(d[22]), "+f"(d[23]),
      "+f"(d[24]), "+f"(d[25]), "+f"(d[26]), "+f"(d[27]), "+f"(d[28]), "+f"(d[29]), "+f"(d[30]), "+f"(d[31]),
      "+f"(d[32]), "+f"(d[33]), "+f"(d[34]), "+f"(d[35]), "+f"(d[36]), "+f"(d[37]), "+f"(d[38]), "+f"(d[39]),
      "+f"(d[40]), "+f"(d[41]), "+f"(d[42]), "+f"(d[43]), "+f"(d[44]), "+f"(d[45]), "+f"(d[46]), "+f"(d[47]),
      "+f"(d[48]), "+f"(d[49]), "+f"(d[50]), "+f"(d[51]), "+f"(d[52]), "+f"(d[53]), "+f"(d[54]), "+f"(d[55]),
      "+f"(d[56]), "+f"(d[57]), "+f"(d[58]), "+f"(d[59]), "+f"(d[60]), "+f"(d[61]), "+f"(d[62]), "+f"(d[63]),
      "+f"(d[64]), "+f"(d[65]), "+f"(d[66]), "+f"(d[67]), "+f"(d[68]), "+f"(d[69]), "+f"(d[70]), "+f"(d[71]),
      "+f"(d[72]), "+f"(d[73]), "+f"(d[74]), "+f"(d[75]), "+f"(d[76]), "+f"(d[77]), "+f"(d[78]), "+f"(d[79]),
      "+f"(d[80]), "+f"(d[81]), "+f"(d[82]), "+f"(d[83]), "+f"(d[84]), "+f"(d[85]), "+f"(d[86]), "+f"(d[87]),
      "+f"(d[88]), "+f"(d[89]), "+f"(d[90]), "+f"(d[91]), "+f"(d[92]), "+f"(d[93]), "+f"(d[94]), "+f"(d[95])
    : "l"(da), "l"(db), "r"(scale_d));
}

DEVINL void wgmma_n48(float (&d)[24], uint64_t da, uint64_t db, int scale_d) {
  asm volatile("{\n.reg .pred p;\nsetp.ne.b32 p, %26, 0;\n"
    "wgmma.mma_async.sync.aligned.m64n48k16.f32.bf16.bf16 "
    "{%0,%1,%2,%3,%4,%5,%6,%7,%8,%9,%10,%11,%12,%13,%14,%15,"
    "%16,%17,%18,%19,%20,%21,%22,%23}, "
    "%24, %25, p, 1, 1, 0, 1;\n}\n"
    : "+f"(d[0]), "+f"(d[1]), "+f"(d[2]), "+f"(d[3]), "+f"(d[4]), "+f"(d[5]), "+f"(d[6]), "+f"(d[7]),
      "+f"(d[8]), "+f"(d[9]), "+f"(d[10]), "+f"(d[11]), "+f"(d[12]), "+f"(d[13]), "+f"(d[14]), "+f"(d[15]),
      "+f"(d[16]), "+f"(d[17]), "+f"(d[18]), "+f"(d[19]), "+f"(d[20]), "+f"(d[21]), "+f"(d[22]), "+f"(d[23])
    : "l"(da), "l"(db), "r"(scale_d));
}

DEVINL void wgmma_n80(float (&d)[40], uint64_t da, uint64_t db, int scale_d) {
  asm volatile("{\n.reg .pred p;\nsetp.ne.b32 p, %42, 0;\n"
    "wgmma.mma_async.sync.aligned.m64n80k16.f32.bf16.bf16 "
    "{%0,%1,%2,%3,%4,%5,%6,%7,%8,%9,%10,%11,%12,%13,%14,%15,"
    "%16,%17,%18,%19,%20,%21,%22,%23,%24,%25,%26,%27,%28,%29,%30,%31,"
    "%32,%33,%34,%35,%36,%37,%38,%39}, "
    "%40, %41, p, 1, 1, 0, 1;\n}\n"
    : "+f"(d[0]), "+f"(d[1]), "+f"(d[2]), "+f"(d[3]), "+f"(d[4]), "+f"(d[5]), "+f"(d[6]), "+f"(d[7]),
      "+f"(d[8]), "+f"(d[9]), "+f"(d[10]), "+f"(d[11]), "+f"(d[12]), "+f"(d[13]), "+f"(d[14]), "+f"(d[15]),
      "+f"(d[16]), "+f"(d[17]), "+f"(d[18]), "+f"(d[19]), "+f"(d[20]), "+f"(d[21]), "+f"(d[22]), "+f"(d[23]),
      "+f"(d[24]), "+f"(d[25]), "+f"(d[26]), "+f"(d[27]), "+f"(d[28]), "+f"(d[29]), "+f"(d[30]), "+f"(d[31]),
      "+f"(d[32]), "+f"(d[33]), "+f"(d[34]), "+f"(d[35]), "+f"(d[36]), "+f"(d[37]), "+f"(d[38]), "+f"(d[39])
    : "l"(da), "l"(db), "r"(scale_d));
}

DEVINL void wgmma_qk_n64(float (&d)[32], uint32_t a0, uint32_t a1, uint32_t a2, uint32_t a3, uint64_t db, int scale_d) {
  asm volatile("{\n.reg .pred p;\nsetp.ne.b32 p, %37, 0;\n"
    "wgmma.mma_async.sync.aligned.m64n64k16.f32.bf16.bf16 "
    "{%0,%1,%2,%3,%4,%5,%6,%7,%8,%9,%10,%11,%12,%13,%14,%15,"
    "%16,%17,%18,%19,%20,%21,%22,%23,%24,%25,%26,%27,%28,%29,%30,%31}, "
    "{%32,%33,%34,%35}, %36, p, 1, 1, 0;\n}\n"
    : "+f"(d[0]), "+f"(d[1]), "+f"(d[2]), "+f"(d[3]), "+f"(d[4]), "+f"(d[5]), "+f"(d[6]), "+f"(d[7]),
      "+f"(d[8]), "+f"(d[9]), "+f"(d[10]), "+f"(d[11]), "+f"(d[12]), "+f"(d[13]), "+f"(d[14]), "+f"(d[15]),
      "+f"(d[16]), "+f"(d[17]), "+f"(d[18]), "+f"(d[19]), "+f"(d[20]), "+f"(d[21]), "+f"(d[22]), "+f"(d[23]),
      "+f"(d[24]), "+f"(d[25]), "+f"(d[26]), "+f"(d[27]), "+f"(d[28]), "+f"(d[29]), "+f"(d[30]), "+f"(d[31])
    : "r"(a0), "r"(a1), "r"(a2), "r"(a3), "l"(db), "r"(scale_d));
}

DEVINL void wgmma_pv_n24(float (&d)[12], uint32_t a0, uint32_t a1, uint32_t a2, uint32_t a3, uint64_t db, int scale_d) {
  asm volatile("{\n.reg .pred p;\nsetp.ne.b32 p, %17, 0;\n"
    "wgmma.mma_async.sync.aligned.m64n24k16.f32.bf16.bf16 "
    "{%0,%1,%2,%3,%4,%5,%6,%7,%8,%9,%10,%11}, "
    "{%12,%13,%14,%15}, %16, p, 1, 1, 1;\n}\n"
    : "+f"(d[0]), "+f"(d[1]), "+f"(d[2]), "+f"(d[3]), "+f"(d[4]), "+f"(d[5]), "+f"(d[6]), "+f"(d[7]),
      "+f"(d[8]), "+f"(d[9]), "+f"(d[10]), "+f"(d[11])
    : "r"(a0), "r"(a1), "r"(a2), "r"(a3), "l"(db), "r"(scale_d));
}

DEVINL void wgmma_qk_n64_z(float (&d)[32], uint32_t a0, uint32_t a1, uint32_t a2, uint32_t a3, uint64_t db) {
  asm volatile("{\n.reg .pred p;\nsetp.ne.b32 p, 0, 0;\n"
    "wgmma.mma_async.sync.aligned.m64n64k16.f32.bf16.bf16 "
    "{%0,%1,%2,%3,%4,%5,%6,%7,%8,%9,%10,%11,%12,%13,%14,%15,"
    "%16,%17,%18,%19,%20,%21,%22,%23,%24,%25,%26,%27,%28,%29,%30,%31}, "
    "{%32,%33,%34,%35}, %36, p, 1, 1, 0;\n}\n"
    : "=f"(d[0]), "=f"(d[1]), "=f"(d[2]), "=f"(d[3]), "=f"(d[4]), "=f"(d[5]), "=f"(d[6]), "=f"(d[7]),
      "=f"(d[8]), "=f"(d[9]), "=f"(d[10]), "=f"(d[11]), "=f"(d[12]), "=f"(d[13]), "=f"(d[14]), "=f"(d[15]),
      "=f"(d[16]), "=f"(d[17]), "=f"(d[18]), "=f"(d[19]), "=f"(d[20]), "=f"(d[21]), "=f"(d[22]), "=f"(d[23]),
      "=f"(d[24]), "=f"(d[25]), "=f"(d[26]), "=f"(d[27]), "=f"(d[28]), "=f"(d[29]), "=f"(d[30]), "=f"(d[31])
    : "r"(a0), "r"(a1), "r"(a2), "r"(a3), "l"(db));
}

DEVINL void wgmma_pv_n24_z(float (&d)[12], uint32_t a0, uint32_t a1, uint32_t a2, uint32_t a3, uint64_t db) {
  asm volatile("{\n.reg .pred p;\nsetp.ne.b32 p, 0, 0;\n"
    "wgmma.mma_async.sync.aligned.m64n24k16.f32.bf16.bf16 "
    "{%0,%1,%2,%3,%4,%5,%6,%7,%8,%9,%10,%11}, "
    "{%12,%13,%14,%15}, %16, p, 1, 1, 1;\n}\n"
    : "=f"(d[0]), "=f"(d[1]), "=f"(d[2]), "=f"(d[3]), "=f"(d[4]), "=f"(d[5]), "=f"(d[6]), "=f"(d[7]),
      "=f"(d[8]), "=f"(d[9]), "=f"(d[10]), "=f"(d[11])
    : "r"(a0), "r"(a1), "r"(a2), "r"(a3), "l"(db));
}

DEVINL void wgmma_cv_n64(float (&d)[32], uint32_t a0, uint32_t a1, uint32_t a2, uint32_t a3, uint64_t db) {
  asm volatile("{\n.reg .pred p;\nsetp.ne.b32 p, 1, 0;\n"
    "wgmma.mma_async.sync.aligned.m64n64k16.f32.bf16.bf16 "
    "{%0,%1,%2,%3,%4,%5,%6,%7,%8,%9,%10,%11,%12,%13,%14,%15,"
    "%16,%17,%18,%19,%20,%21,%22,%23,%24,%25,%26,%27,%28,%29,%30,%31}, "
    "{%32,%33,%34,%35}, %36, p, 1, 1, 0;\n}\n"
    : "+f"(d[0]), "+f"(d[1]), "+f"(d[2]), "+f"(d[3]), "+f"(d[4]), "+f"(d[5]), "+f"(d[6]), "+f"(d[7]),
      "+f"(d[8]), "+f"(d[9]), "+f"(d[10]), "+f"(d[11]), "+f"(d[12]), "+f"(d[13]), "+f"(d[14]), "+f"(d[15]),
      "+f"(d[16]), "+f"(d[17]), "+f"(d[18]), "+f"(d[19]), "+f"(d[20]), "+f"(d[21]), "+f"(d[22]), "+f"(d[23]),
      "+f"(d[24]), "+f"(d[25]), "+f"(d[26]), "+f"(d[27]), "+f"(d[28]), "+f"(d[29]), "+f"(d[30]), "+f"(d[31])
    : "r"(a0), "r"(a1), "r"(a2), "r"(a3), "l"(db));
}

DEVINL void wgmma_cv_n48(float (&d)[24], uint32_t a0, uint32_t a1, uint32_t a2, uint32_t a3, uint64_t db) {
  asm volatile("{\n.reg .pred p;\nsetp.ne.b32 p, 1, 0;\n"
    "wgmma.mma_async.sync.aligned.m64n48k16.f32.bf16.bf16 "
    "{%0,%1,%2,%3,%4,%5,%6,%7,%8,%9,%10,%11,%12,%13,%14,%15,"
    "%16,%17,%18,%19,%20,%21,%22,%23}, "
    "{%24,%25,%26,%27}, %28, p, 1, 1, 0;\n}\n"
    : "+f"(d[0]), "+f"(d[1]), "+f"(d[2]), "+f"(d[3]), "+f"(d[4]), "+f"(d[5]), "+f"(d[6]), "+f"(d[7]),
      "+f"(d[8]), "+f"(d[9]), "+f"(d[10]), "+f"(d[11]), "+f"(d[12]), "+f"(d[13]), "+f"(d[14]), "+f"(d[15]),
      "+f"(d[16]), "+f"(d[17]), "+f"(d[18]), "+f"(d[19]), "+f"(d[20]), "+f"(d[21]), "+f"(d[22]), "+f"(d[23])
    : "r"(a0), "r"(a1), "r"(a2), "r"(a3), "l"(db));
}

DEVINL void wgmma_cv_n32(float (&d)[16], uint32_t a0, uint32_t a1, uint32_t a2, uint32_t a3, uint64_t db) {
  asm volatile("{\n.reg .pred p;\nsetp.ne.b32 p, 1, 0;\n"
    "wgmma.mma_async.sync.aligned.m64n32k16.f32.bf16.bf16 "
    "{%0,%1,%2,%3,%4,%5,%6,%7,%8,%9,%10,%11,%12,%13,%14,%15}, "
    "{%16,%17,%18,%19}, %20, p, 1, 1, 0;\n}\n"
    : "+f"(d[0]), "+f"(d[1]), "+f"(d[2]), "+f"(d[3]), "+f"(d[4]), "+f"(d[5]), "+f"(d[6]), "+f"(d[7]),
      "+f"(d[8]), "+f"(d[9]), "+f"(d[10]), "+f"(d[11]), "+f"(d[12]), "+f"(d[13]), "+f"(d[14]), "+f"(d[15])
    : "r"(a0), "r"(a1), "r"(a2), "r"(a3), "l"(db));
}

DEVINL void wgmma_cv_n16(float (&d)[8], uint32_t a0, uint32_t a1, uint32_t a2, uint32_t a3, uint64_t db) {
  asm volatile("{\n.reg .pred p;\nsetp.ne.b32 p, 1, 0;\n"
    "wgmma.mma_async.sync.aligned.m64n16k16.f32.bf16.bf16 "
    "{%0,%1,%2,%3,%4,%5,%6,%7}, "
    "{%8,%9,%10,%11}, %12, p, 1, 1, 0;\n}\n"
    : "+f"(d[0]), "+f"(d[1]), "+f"(d[2]), "+f"(d[3]), "+f"(d[4]), "+f"(d[5]), "+f"(d[6]), "+f"(d[7])
    : "r"(a0), "r"(a1), "r"(a2), "r"(a3), "l"(db));
}

#define ATT_T(i) do {} while (0)
#define ATT_IMAX 0
#define ATT_WAIT0 0
#define ATT_SPLIT 2
constexpr float SM_C = 0.22360679774997896f * 1.4426950408889634f;
constexpr float NEG_INF = -INFINITY;
constexpr int PLANE = 2048;
constexpr int PAIR = 11 * PLANE;
constexpr int SEG = 2 * PAIR;
constexpr int PWIN = 3 * PAIR;

template <int N> DEVINL void reg_fence(float (&d)[N]) {
#pragma unroll
  for (int i = 0; i < N; ++i) asm volatile("" : "+f"(d[i])::"memory");
}
DEVINL float ex2v(float x) { float r; asm volatile("ex2.approx.ftz.f32 %0, %1;" : "=f"(r) : "f"(x)); return r; }
DEVINL uint32_t bsel(uint32_t a, uint32_t b, uint32_t m) { return (a & m) | (b & ~m); }
DEVINL float fsel(float a, float b, uint32_t m) { return __uint_as_float(bsel(__float_as_uint(a), __float_as_uint(b), m)); }
typedef uint64_t desc_t;
DEVINL desc_t kdesc(desc_t d) { return d; }
DEVINL desc_t vdesc(desc_t d) { return d; }

DEVINL void mma_qk(float (&s)[32], const uint32_t (&a)[4], const uint32_t (&a8)[2], desc_t kmain, desc_t ktail) {
  wgmma_qk_n64_z(s, a[0], a[1], a[2], a[3], kdesc(kmain));
  wgmma_qk_n64(s, a8[0], a8[1], 0u, 0u, kdesc(ktail), 1);
}
template <bool FIRST>
DEVINL void mma_pv(float (&o)[12], const uint32_t (&p)[16], desc_t v) {
  if (FIRST) wgmma_pv_n24_z(o, p[0], p[1], p[2], p[3], vdesc(v));
  else wgmma_pv_n24(o, p[0], p[1], p[2], p[3], vdesc(v), 1);
#pragma unroll
  for (int b = 1; b < 4; ++b) wgmma_pv_n24(o, p[4 * b], p[4 * b + 1], p[4 * b + 2], p[4 * b + 3], vdesc(v + b * 16), 1);
}
DEVINL void row_max_f(const float (&s)[32], float& x0o, float& x1o) {
  float x0 = fmaxf(s[0], s[1]), x1 = fmaxf(s[2], s[3]), y0 = fmaxf(s[4], s[5]), y1 = fmaxf(s[6], s[7]);
#pragma unroll
  for (int i = 2; i < 8; i += 2) {
    x0 = fmaxf(x0, fmaxf(s[4 * i], s[4 * i + 1]));
    x1 = fmaxf(x1, fmaxf(s[4 * i + 2], s[4 * i + 3]));
    y0 = fmaxf(y0, fmaxf(s[4 * i + 4], s[4 * i + 5]));
    y1 = fmaxf(y1, fmaxf(s[4 * i + 6], s[4 * i + 7]));
  }
  x0 = fmaxf(x0, y0); x1 = fmaxf(x1, y1);
  x0 = fmaxf(x0, __shfl_xor_sync(0xffffffffu, x0, 1));
  x1 = fmaxf(x1, __shfl_xor_sync(0xffffffffu, x1, 1));
  x0o = fmaxf(x0, __shfl_xor_sync(0xffffffffu, x0, 2));
  x1o = fmaxf(x1, __shfl_xor_sync(0xffffffffu, x1, 2));
}
DEVINL void row_max(const float (&s)[32], float pm0, float pm1, float& x0o, float& x1o) {
#define FI(i) __float_as_int(s[i])
  int x0 = __vimax3_s32(FI(0), FI(1), FI(4)), x1 = __vimax3_s32(FI(2), FI(3), FI(6));
  int y0 = __vimax3_s32(FI(5), FI(8), FI(9)), y1 = __vimax3_s32(FI(7), FI(10), FI(11));
  x0 = __vimax3_s32(x0, FI(12), FI(13)); x1 = __vimax3_s32(x1, FI(14), FI(15));
  y0 = __vimax3_s32(y0, FI(16), FI(17)); y1 = __vimax3_s32(y1, FI(18), FI(19));
  x0 = __vimax3_s32(x0, FI(20), FI(21)); x1 = __vimax3_s32(x1, FI(22), FI(23));
  y0 = __vimax3_s32(y0, FI(24), FI(25)); y1 = __vimax3_s32(y1, FI(26), FI(27));
  x0 = __vimax3_s32(x0, FI(28), FI(29)); x1 = __vimax3_s32(x1, FI(30), FI(31));
#undef FI
  x0 = max(x0, y0); x1 = max(x1, y1);
  x0 = max(x0, __shfl_xor_sync(0xffffffffu, x0, 1));
  x1 = max(x1, __shfl_xor_sync(0xffffffffu, x1, 1));
  x0 = max(x0, __shfl_xor_sync(0xffffffffu, x0, 2));
  x1 = max(x1, __shfl_xor_sync(0xffffffffu, x1, 2));
  float f0 = __int_as_float(x0), f1 = __int_as_float(x1);
  if (__any_sync(0xffffffffu, (x0 < 0 && !(pm0 >= 0.f)) || (x1 < 0 && !(pm1 >= 0.f)))) {
    f0 = s[0]; f1 = s[2];
#pragma unroll
    for (int i = 0; i < 8; ++i) {
      f0 = fmaxf(f0, fmaxf(s[4 * i], s[4 * i + 1]));
      f1 = fmaxf(f1, fmaxf(s[4 * i + 2], s[4 * i + 3]));
    }
    f0 = fmaxf(f0, __shfl_xor_sync(0xffffffffu, f0, 1));
    f1 = fmaxf(f1, __shfl_xor_sync(0xffffffffu, f1, 1));
    f0 = fmaxf(f0, __shfl_xor_sync(0xffffffffu, f0, 2));
    f1 = fmaxf(f1, __shfl_xor_sync(0xffffffffu, f1, 2));
  }
  x0o = f0; x1o = f1;
}
template <int I0, int I1>
DEVINL void sm_exp(const float (&s)[32], uint32_t (&p)[16], float n0, float n1) {
#pragma unroll
  for (int i = I0; i < I1; ++i) {
    const float e0 = ex2v(fmaf(s[4 * i], SM_C, n0)), e1 = ex2v(fmaf(s[4 * i + 1], SM_C, n0));
    const float e2 = ex2v(fmaf(s[4 * i + 2], SM_C, n1)), e3 = ex2v(fmaf(s[4 * i + 3], SM_C, n1));
    p[2 * i] = pack_bf16(e0, e1);
    p[2 * i + 1] = pack_bf16(e2, e3);
  }
}
DEVINL void rescale(float (&o)[12], float al0, float al1) {
#pragma unroll
  for (int n = 0; n < 3; ++n) { o[4 * n] *= al0; o[4 * n + 1] *= al0; o[4 * n + 2] *= al1; o[4 * n + 3] *= al1; }
}
struct SoftmaxState { float m0, m1, n0, n1, al0, al1; };
DEVINL void next_max(SoftmaxState& st, float x0, float x1, bool valid) {
  x0 = fmaxf(valid ? x0 : NEG_INF, st.m0); x1 = fmaxf(valid ? x1 : NEG_INF, st.m1);
  const float c0 = -x0 * SM_C, c1 = -x1 * SM_C;
  st.al0 = ex2(fmaf(st.m0, SM_C, c0)); st.al1 = ex2(fmaf(st.m1, SM_C, c1));
  st.m0 = x0; st.m1 = x1;
  st.n0 = valid ? c0 : NEG_INF; st.n1 = valid ? c1 : NEG_INF;
}
template <bool PVPEND, int SPLIT>
DEVINL void step(const float (&cur)[32], float (&nxt)[32], float (&o)[12], uint32_t (&p)[16], SoftmaxState& st, bool valid_nxt) {
  const float n0 = st.n0, n1 = st.n1, pa0 = st.al0, pa1 = st.al1;
  sm_exp<0, SPLIT>(cur, p, n0, n1);
  wg_wait<(PVPEND && !ATT_WAIT0) ? 1 : 0>();
  reg_fence(nxt);
  float x0, x1;
  row_max_f(nxt, x0, x1);
  sm_exp<SPLIT, 8>(cur, p, n0, n1);
  next_max(st, x0, x1, valid_nxt);
  if (PVPEND) { wg_wait<0>(); reg_fence(o); rescale(o, pa0, pa1); }
}

DEVINL void attn_all(uint32_t ring, uint32_t stg, uint32_t bars, int wq, int lane, int cmin) {
  const int wg = wq >> 2, w = wq & 3;
  const int g = lane >> 2, t = lane & 3, mi = lane >> 3, r = lane & 7;
  const uint32_t T0 = (2 * t > g) ? 0xFFFFFFFFu : 0u, T1 = (2 * t + 1 > g) ? 0xFFFFFFFFu : 0u;
  const uint32_t tri = (T0 & 0xFFFFu) | (T1 & 0xFFFF0000u);
  const uint32_t rowQ = stg + (mi >> 1) * PLANE + (16 * wq + r + 8 * (mi & 1)) * 16;
  const uint32_t rowQ8 = stg + 2 * PLANE + (16 * wq + (lane & 15)) * 16;
  constexpr uint32_t S16 = PAIR >> 4, P16 = PLANE >> 4;
  const uint32_t aE = ((ring + wg * 1024) & 0x3FFFF) >> 4, aO = ((ring + wg * PAIR + (wg ^ 1) * 1024) & 0x3FFFF) >> 4;
  const desc_t kE = (desc_t)(aE | (P16 << 16)) | ((desc_t)(128 >> 4) << 32), kO = (desc_t)(aO | (P16 << 16)) | ((desc_t)(128 >> 4) << 32);
  const desc_t vE = (desc_t)(aE | ((128 >> 4) << 16)) | ((desc_t)P16 << 32), vO = (desc_t)(aO | ((128 >> 4) << 16)) | ((desc_t)P16 << 32);
  uint32_t a[4], a8[2];
  float sX[32], sY[32], o[12];
  uint32_t pA[16], pB[16];
  mbar_wait(bars + 8 * B_HALO, 0);
  ldsm4(a[0], a[1], a[2], a[3], rowQ);
  ldsm2(a8[0], a8[1], rowQ8);
  if (t >= 2) { a8[0] = 0u; a8[1] = 0u; }
  wg_fence();
  mma_qk(sX, a, a8, kE, kE + 2 * P16);
  mma_qk(sY, a, a8, kE + 2 * S16, kE + 2 * S16 + 2 * P16);
  wg_commit();
#pragma unroll 1
  for (int h = 0; h < 4; ++h) {
    const int p = h >> 1, odd = h & 1;
    const uint32_t km = (p * 33 + odd * 3) * P16, kt = (p * 33 + 2) * P16, vp = (p * 33 + 5 + odd * 3) * P16;
    SoftmaxState st;
    ATT_T(0);
    wg_wait<0>();
    reg_fence(sX); reg_fence(sY);
    ATT_T(1);
    if (cmin > 0) {
#pragma unroll
      for (int i = 0; i < 32; ++i) sX[i] = NEG_INF;
    }
#pragma unroll
    for (int b = 0; b < 4; ++b) {
      const uint32_t gt = b > w ? 0xFFFFFFFFu : 0u, ge = b >= w ? 0xFFFFFFFFu : 0u, eq = ge & ~gt;
      const uint32_t e0 = gt | (eq & T0), e1 = gt | (eq & T1);
      sX[8 * b + 0] = fsel(sX[8 * b + 0], sY[8 * b + 0], e0);
      sX[8 * b + 1] = fsel(sX[8 * b + 1], sY[8 * b + 1], e1);
      sX[8 * b + 2] = fsel(sX[8 * b + 2], sY[8 * b + 2], gt);
      sX[8 * b + 3] = fsel(sX[8 * b + 3], sY[8 * b + 3], gt);
      sX[8 * b + 4] = fsel(sX[8 * b + 4], sY[8 * b + 4], ge);
      sX[8 * b + 5] = fsel(sX[8 * b + 5], sY[8 * b + 5], ge);
      sX[8 * b + 6] = fsel(sX[8 * b + 6], sY[8 * b + 6], e0);
      sX[8 * b + 7] = fsel(sX[8 * b + 7], sY[8 * b + 7], e1);
    }
    wg_fence();
    mma_qk(sY, a, a8, kO + km, kO + kt);
    wg_commit();
    ATT_T(2);
    row_max_f(sX, st.m0, st.m1);
    st.n0 = -st.m0 * SM_C; st.n1 = -st.m1 * SM_C;
    ATT_T(3);
    step<false, ATT_SPLIT>(sX, sY, o, pA, st, wg + 1 >= cmin);
    ATT_T(4);
#pragma unroll
    for (int b = 0; b < 4; ++b) {
      const uint32_t gt = b > w ? 0xFFFFFFFFu : 0u, ge = b >= w ? 0xFFFFFFFFu : 0u, eq = ge & ~gt;
      const uint32_t mt = gt | (eq & tri);
      pB[4 * b + 0] = pA[4 * b + 0] & ~mt; pA[4 * b + 0] &= mt;
      pB[4 * b + 1] = pA[4 * b + 1] & ~gt; pA[4 * b + 1] &= gt;
      pB[4 * b + 2] = pA[4 * b + 2] & ~ge; pA[4 * b + 2] &= ge;
      pB[4 * b + 3] = pA[4 * b + 3] & ~mt; pA[4 * b + 3] &= mt;
    }
    wg_fence();
    mma_qk(sX, a, a8, kE + S16 + km, kE + S16 + kt);
    wg_commit();
    mma_pv<true>(o, pA, vE + vp);
    mma_pv<false>(o, pB, vE + 2 * S16 + vp);
    wg_commit();
    ATT_T(5);
    step<true, ATT_SPLIT>(sY, sX, o, pB, st, wg + 2 >= cmin);
    ATT_T(6);
    wg_fence();
    mma_qk(sY, a, a8, kO + S16 + km, kO + S16 + kt);
    wg_commit();
    mma_pv<false>(o, pB, vO + vp);
    wg_commit();
    ATT_T(7);
    step<true, ATT_SPLIT>(sX, sY, o, pA, st, wg + 3 >= cmin);
    ATT_T(8);
    const int hn = h < 3 ? h + 1 : h, pn = hn >> 1, on = hn & 1;
    const uint32_t kmn = (pn * 33 + on * 3) * P16, ktn = (pn * 33 + 2) * P16;
    if (h == 1) mbar_wait(bars + 8 * (B_HALO + 1), 0);
    ldsm4(a[0], a[1], a[2], a[3], rowQ + (pn * 5 + on * 3) * PLANE);
    ldsm2(a8[0], a8[1], rowQ8 + pn * 5 * PLANE);
    if ((t >= 2) != (on != 0)) { a8[0] = 0u; a8[1] = 0u; }
    wg_fence();
    mma_pv<false>(o, pA, vE + S16 + vp);
    mma_qk(sX, a, a8, kE + kmn, kE + ktn);
    wg_commit();
    ATT_T(9);
    sm_exp<0, 8>(sY, pB, st.n0, st.n1);
    ATT_T(10);
    wg_wait<0>();
    reg_fence(o); reg_fence(sX);
    rescale(o, st.al0, st.al1);
    wg_fence();
    mma_pv<false>(o, pB, vO + S16 + vp);
    wg_commit();
    wg_fence();
    mma_qk(sY, a, a8, kE + 2 * S16 + kmn, kE + 2 * S16 + ktn);
    wg_commit();
    ATT_T(11);
    wg_wait<1>();
    reg_fence(o);
    const int src = (lane & ~3) | (odd ? 0 : 2);
    const float i0 = __fdividef(1.f, __shfl_sync(0xffffffffu, o[8], src)), i1 = __fdividef(1.f, __shfl_sync(0xffffffffu, o[10], src));
    const uint32_t ob = stg + p * 5 * PLANE + (16 * wq + g) * 16 + t * 4;
    const uint32_t om = ob + odd * 3 * PLANE;
    sts32(om, pack_bf16(o[0] * i0, o[1] * i0)); sts32(om + 128, pack_bf16(o[2] * i1, o[3] * i1));
    sts32(om + PLANE, pack_bf16(o[4] * i0, o[5] * i0)); sts32(om + PLANE + 128, pack_bf16(o[6] * i1, o[7] * i1));
    if ((t >= 2) == (odd != 0)) { sts32(ob + 2 * PLANE, pack_bf16(o[8] * i0, o[9] * i0)); sts32(ob + 2 * PLANE + 128, pack_bf16(o[10] * i1, o[11] * i1)); }
    if (odd) {
      fence_async_smem();
      __syncwarp();
      if (lane == 0) mbar_arrive(bars + 8 * (B_OST + p));
      if (lane < 4) mbar_arrive_cta(bars + 8 * (B_EMPTY2 + 2 * p + (lane >> 1)), lane & 1);
    }
    ATT_T(12);
  }
  wg_wait<0>();
  reg_fence(sX); reg_fence(sY);
  __syncwarp();
}

#define NO_G 1
#define CONV_DUP 0
#define CONV_YIELD 0
#define FPF_AT 6
#define KT_GATE 0
#define OPUB_GATE 1
#define KT_IN_F 0
#define EXP_NOLD 0
#define PF_MODE 2
#define KVPF_AT 3
#define PRE_LDG 0
#define PRE_AFTER 2
#define PRE_WAIT 1
struct Params {
  const uint16_t* q; const uint16_t* k; const uint16_t* v; const uint16_t* shift_k; const uint16_t* ssm_k;
  const uint16_t* ssm_D; const uint16_t* x; const uint16_t* wqkv; const uint16_t* wo; uint16_t* out;
};

DEVINL unsigned* cnt(int i) { return &g_cnt[i * CS]; }

DEVINL void finish_role() {
  unsigned old = atomicAdd(cnt(C_DONE), 1u);
  if (old == 255u) {
    __threadfence();
    for (int i = 0; i < C_NUM; ++i) *cnt(i) = 0u;
    __threadfence();
  }
}

DEVINL void conv_channel(uint32_t sb, int cl, int wc, int lane, uint32_t D2, int bar_id) {
  const int mi = lane >> 3, r = lane & 7, g = lane >> 2, t = lane & 3;
  const int h = wc >> 1, rr = wc & 1;
  const uint32_t Ub = cl < 4 ? sb + OFF_U + cl * CH_U : sb + OFF_U4, Fb = sb + OFF_F + cl * CH_F;
  const uint32_t fw = ((g & 1) ? Fb + 4160 + 2 * (33 - g + 2 * t) : Fb + 2 * (32 - g + 2 * t)) + 1024 * h - 32 * rr;
  const uint64_t ub = (uint64_t)((((Ub & 0x3FFFF) >> 4) + 16) | ((UPL >> 4) << 16)) | ((uint64_t)(128 >> 4) << 32);
  uint64_t bcur = ub;
  float d[32], d2[16];
#pragma unroll
  for (int i = 0; i < 32; ++i) d[i] = 0.f;
#pragma unroll
  for (int i = 0; i < 16; ++i) d2[i] = 0.f;
#pragma unroll 1
  for (int rq = 0; rq < 4; ++rq) {
#pragma unroll
    for (int bt = 0; bt < 2; ++bt) {
      const int rho = 4 * rq + 2 * bt;
      const uint32_t fb = fw + 64 * rho;
      uint32_t x[2][2][2][4];
      wg_wait<1>();
#pragma unroll
      for (int e = 0; e < 2; ++e)
#pragma unroll
        for (int nu = 0; nu < 2; ++nu) {
          const uint32_t a = fb + 64 * e + 2048 * nu;
          x[e][nu][0][0] = lds32(a); x[e][nu][0][1] = lds32(a - 16); x[e][nu][0][2] = lds32(a + 16); x[e][nu][0][3] = x[e][nu][0][0];
          x[e][nu][1][0] = lds32(a + 32); x[e][nu][1][1] = x[e][nu][0][2]; x[e][nu][1][2] = lds32(a + 48); x[e][nu][1][3] = x[e][nu][1][0];
        }
      wg_fence();
#pragma unroll
      for (int e = 0; e < 2; ++e) {
        const uint64_t b0 = bcur - e, b1 = b0 + 2 * (UPL >> 4);
        wgmma_cv_n64(d, x[e][0][0][0], x[e][0][0][1], x[e][0][0][2], x[e][0][0][3], b0);
        wgmma_cv_n64(d, x[e][0][1][0], x[e][0][1][1], x[e][0][1][2], x[e][0][1][3], b1);
        wgmma_cv_n32(d2, x[e][1][0][0], x[e][1][0][1], x[e][1][0][2], x[e][1][0][3], b0);
        wgmma_cv_n32(d2, x[e][1][1][0], x[e][1][1][1], x[e][1][1][2], x[e][1][1][3], b1);
      }
      wg_commit();
      bcur -= 2;
    }
  }
  wg_wait<0>();
  reg_fence(d); reg_fence(d2);
#pragma unroll
  for (int i = 0; i < 16; ++i) d[16 + i] += d2[i];
  named_sync(bar_id, 128);
  const uint32_t xb = Fb + wc * 2048 + lane * 16;
#pragma unroll
  for (int j = 0; j < 4; ++j) {
    const float4 v = h == 0 ? make_float4(d[16 + 4 * j], d[17 + 4 * j], d[18 + 4 * j], d[19 + 4 * j])
                            : make_float4(d[4 * j], d[1 + 4 * j], d[2 + 4 * j], d[3 + 4 * j]);
    sts128(xb + j * 512, make_uint4(__float_as_uint(v.x), __float_as_uint(v.y), __float_as_uint(v.z), __float_as_uint(v.w)));
  }
  named_sync(bar_id, 128);
  const uint32_t xr = Fb + (wc ^ 2) * 2048 + lane * 16;
  float f[4][4];
#pragma unroll
  for (int j = 0; j < 4; ++j) {
    const uint4 ov = lds128(xr + (h == 0 ? (j >= 2 ? j - 2 : 0) : j) * 512);
    const float z = (h == 0 && j < 2) ? 0.f : 1.f;
    f[j][0] = (h == 0 ? d[4 * j] : d[8 + 4 * j]) + z * __uint_as_float(ov.x);
    f[j][1] = (h == 0 ? d[4 * j + 1] : d[9 + 4 * j]) + z * __uint_as_float(ov.y);
    f[j][2] = (h == 0 ? d[4 * j + 2] : d[10 + 4 * j]) + z * __uint_as_float(ov.z);
    f[j][3] = (h == 0 ? d[4 * j + 3] : d[11 + 4 * j]) + z * __uint_as_float(ov.w);
  }
  uint32_t res[2][4];
#pragma unroll
  for (int jj = 0; jj < 2; ++jj) {
    const int tile = 4 * h + 2 * jj + (mi >> 1);
    uint32_t u0, u1, u2, u3;
    ldsm4t(u0, u1, u2, u3, Ub + (2 * rr + (mi & 1)) * UPL + (16 + 8 * tile + r) * 16);
    res[jj][0] = hadd2(pack_bf16(f[2 * jj][0], f[2 * jj][1]), hmul2(u0, D2));
    res[jj][1] = hadd2(pack_bf16(f[2 * jj][2], f[2 * jj][3]), hmul2(u1, D2));
    res[jj][2] = hadd2(pack_bf16(f[2 * jj + 1][0], f[2 * jj + 1][1]), hmul2(u2, D2));
    res[jj][3] = hadd2(pack_bf16(f[2 * jj + 1][2], f[2 * jj + 1][3]), hmul2(u3, D2));
  }
  named_sync(bar_id, 128);
#pragma unroll
  for (int jj = 0; jj < 2; ++jj) {
    const int tile = 4 * h + 2 * jj + (mi >> 1);
    stsm4t(Fb + ((8 * tile + r) * 32 + 16 * rr + 8 * (mi & 1)) * 2, res[jj][0], res[jj][1], res[jj][2], res[jj][3]);
  }
  fence_async_smem();
  __syncwarp();
  if (lane == 0) mbar_arrive(sb + OFF_BAR + 8 * (B_YST + cl));
}

__global__ void __cluster_dims__(2, 1, 1) __launch_bounds__(512, 1)
h3_swa_fused_kernel(const __grid_constant__ CUtensorMap tmX, const __grid_constant__ CUtensorMap tmW128,
                    const __grid_constant__ CUtensorMap tmW32,
                    const __grid_constant__ CUtensorMap tmOut, const __grid_constant__ CUtensorMap tmKT,
                    const __grid_constant__ CUtensorMap tmKin, const __grid_constant__ CUtensorMap tmVin,
                    const __grid_constant__ CUtensorMap tmQ, const __grid_constant__ CUtensorMap tmYT,
                    const __grid_constant__ CUtensorMap tmU4, const __grid_constant__ CUtensorMap tmU1,
                    const Params prm) {
  extern __shared__ uint8_t smem_raw[];
  const uint32_t sb = (uint32_t)__cvta_generic_to_shared(smem_raw);
  if ((sb & 1023u) != 0u) { g_err = 3; return; }
  const uint32_t bars = sb + OFF_BAR;
  const int tid = threadIdx.x, warp = tid >> 5, lane = tid & 31, wg = tid >> 7;
  const int cta = blockIdx.x;
  const uint32_t rank = cta & 1;
  const int g8 = (cta >> 1) & 7, rp = cta >> 4;
  const int rb = 2 * rp + rank;
  const int rb2 = 2 * rp + (g8 & 1);
  const int c2 = 2 * (g8 >> 1) + rank;
  const int tau = cta & 15, jt = cta >> 4;

  if (tid == 384) { prefetch_tmap(&tmX); prefetch_tmap(&tmW128); prefetch_tmap(&tmW32); }
  if (tid == 0) {
    PROF(0);
    for (int i = 0; i < NST1; ++i) { mbar_init(bars + 8 * (B_FULL1 + i), 1); mbar_init(bars + 8 * (B_EMPTY1 + i), 16); }
    mbar_init(bars + 8 * B_RINGFREE, 1);
    mbar_init(bars + 8 * B_HALO, 1); mbar_init(bars + 8 * (B_HALO + 1), 1);
    for (int i = 0; i < NST2; ++i) { mbar_init(bars + 8 * (B_FULL2 + i), 1); mbar_init(bars + 8 * (B_EMPTY2 + i), 16); }
    mbar_init(bars + 8 * B_U, 1);
    mbar_init(bars + 8 * B_KVST, 8);
    mbar_init(bars + 8 * B_OST, 8); mbar_init(bars + 8 * (B_OST + 1), 8);
    mbar_init(bars + 8 * B_KTST, 4);
    for (int i = 0; i < 5; ++i) mbar_init(bars + 8 * (B_YST + i), 4);
    mbar_init(bars + 8 * B_CIN, 4);
    mbar_init(bars + 8 * B_OPUB, 1);
    mbar_init(bars + 8 * B_PRE, 1);
    mbar_init(bars + 8 * B_FRAW, 1);
    mbar_init(bars + 8 * B_QT, 1);
    mbar_init(bars + 8 * B_P0PUB, 1);
    mbar_init(bars + 8 * B_YT, 1);
    mbar_init(bars + 8 * B_U4, 1);
    mbar_init(bars + 8 * B_STGFREE, 4);
    mbar_init(bars + 8 * B_FFREE, 8);
    asm volatile("fence.mbarrier_init.release.cluster;" ::: "memory");
  }
  __syncthreads();
  asm volatile("barrier.cluster.arrive.relaxed.aligned;\nbarrier.cluster.wait.aligned;" ::: "memory");

  if (wg == 3) {
    asm volatile("setmaxnreg.dec.sync.aligned.u32 32;");
    if (warp == 12 && lane == 0) {
      PROF(15);
      for (int it = 0; it < 10; ++it) {
        const int s = it % NST1;
        if (it >= NST1) mbar_wait(bars + 8 * (B_EMPTY1 + s), ((it / NST1) - 1) & 1);
        PROF(44 + it);
        const uint32_t st = sb + s * ST1, fb = bars + 8 * (B_FULL1 + s);
        mbar_expect(fb, ST1);
        tma2d(st, &tmX, it * 64, rb * 128, fb);
        tma3d_mc(st + ST1_B128 + rank * 12288, &tmW128, g8 * 80, it * 64 + rank * 32, 0, fb);
        tma3d_mc(st + ST1_B32 + rank * 3072, &tmW32, g8 * 80 + 64, it * 64 + rank * 32, 0, fb);
        if (it == PRE_AFTER) {
          mbar_expect(bars + 8 * B_PRE, 131 * 160 + 128 * 160);
          tma2d(sb + OFF_U, &tmKin, jt * 80, tau * 128 - 3, bars + 8 * B_PRE);
          tma2d(sb + OFF_STG, &tmVin, jt * 80, tau * 128, bars + 8 * B_PRE);
        }
        if (it == FPF_AT) prefetch_l2(prm.ssm_k + (size_t)cta * 5 * SEQ, 5 * SEQ * 2);
      }
      PROF(1);
      mbar_wait(bars + 8 * B_RINGFREE, 0);
      for (int p = 0; p < 2; ++p) {
        const uint32_t hb = bars + 8 * (B_HALO + p);
        if (rb == 0) { mbar_arrive(hb); continue; }
        poll_ge(cnt(C_KV + (g8 * 16 + rb - 1) * 2 + p), 1);
        if (rb >= 2) poll_ge(cnt(C_KV + (g8 * 16 + rb - 2) * 2 + p), 1);
        if (p == 0) PROF(2);
        mbar_expect(hb, (rb >= 2 ? 2 : 1) * PAIR);
        bulk_load(sb + p * PWIN + PAIR, g_kv + (size_t)(g8 * 16 + rb - 1) * (SEG / 2) + p * (PAIR / 2), PAIR, hb);
        if (rb >= 2) bulk_load(sb + p * PWIN, g_kv + (size_t)(g8 * 16 + rb - 2) * (SEG / 2) + p * (PAIR / 2), PAIR, hb);
      }
      poll_ge(cnt(C_WO + c2), 16);
#pragma unroll 1
      for (int it = 0; it < 8; ++it) {
        const int s = it & 3, p = it >> 2;
        if (it == 2) mbar_wait(bars + 8 * B_OPUB, 0);
        mbar_wait(bars + 8 * (B_EMPTY2 + s), p);
        const uint32_t fb = bars + 8 * (B_FULL2 + s);
        mbar_expect(fb, ST2);
        const uint16_t* asrc = g_o + (size_t)(rb2 * 80 + p * 40 + (2 * s + rank) * 5) * 1024;
        if (it == 0) { PROF(3); poll_ge(cnt(C_O + rb2 * 2), 8); }
        if (it != 4) {
          if (it != 5 ) bulk_load_mc(sb + s * ST2 + rank * 10240, asrc, 10240, fb);
        }
        bulk_load(sb + s * ST2 + 20480, g_woP + (size_t)(c2 * 8 + it) * 6400, 12800, fb);
        if (it == 5) {
          poll_ge(cnt(C_O + rb2 * 2 + 1), 8);
          PROF(4);
          bulk_load_mc(sb + rank * 10240, asrc - 10 * 1024, 10240, bars + 8 * B_FULL2);
          bulk_load_mc(sb + ST2 + rank * 10240, asrc, 10240, fb);
        }
      }
      finish_role();
    } else if (warp == 13 && lane == 0) {
      prefetch_tmap(&tmOut);
      mbar_wait(bars + 8 * B_FFREE, 0);
      mbar_expect(bars + 8 * B_FRAW, 5 * 4096);
      for (int c = 0; c < 5; ++c) bulk_load(sb + OFF_F + c * CH_F + 64, prm.ssm_k + (size_t)(cta * 5 + c) * SEQ, 4096, bars + 8 * B_FRAW);
      mbar_wait(bars + 8 * B_KVST, 0);
      uint16_t* kd = g_kv + (size_t)(g8 * 16 + rb) * (SEG / 2);
      bulk_store(kd, sb + 2 * PAIR, PAIR); bulk_commit();
      bulk_wait<0>(); red_publish(cnt(C_KV + (g8 * 16 + rb) * 2));
      mbar_arrive(bars + 8 * B_P0PUB);
      PROF(55);
      bulk_store(kd + PAIR / 2, sb + PWIN + 2 * PAIR, PAIR); bulk_commit();
      bulk_wait<0>(); red_publish(cnt(C_KV + (g8 * 16 + rb) * 2 + 1));
      PROF(24);
      for (int p = 0; p < 2; ++p) {
        mbar_wait(bars + 8 * (B_OST + p), 0);
        if (p == 1) PROF(31);
        bulk_store(g_o + (size_t)(rb * 80 + p * 40 + g8 * 5) * 1024, sb + OFF_STG + p * 10240, 10240);
        bulk_commit(); bulk_wait<0>();
        if (p == 1) PROF(54);
        red_publish(cnt(C_O + rb * 2 + p));
      }
      mbar_arrive(bars + 8 * B_OPUB);
      PROF(20);
    } else if (warp == 15) {
      const int run = rp * 2 + (g8 & 1);
      const int gg = run >> 1, pp = run & 1;
      mbar_wait(bars + 8 * (B_FULL1 + 3), 0);
#pragma unroll 1
      for (int i0 = 0; i0 < 13; i0 += 4) {
        uint4 v[4];
#pragma unroll
        for (int i = 0; i < 4; ++i) {
          const int idx = lane + 32 * (i0 + i), j = idx / 10, n8 = idx % 10;
          if (idx < 400) v[i] = ldg_nc(prm.wo + (size_t)(gg * 80 + pp * 40 + j) * DM + c2 * 80 + n8 * 8);
        }
#pragma unroll
        for (int i = 0; i < 4; ++i) {
          const int idx = lane + 32 * (i0 + i), j = idx / 10, n8 = idx % 10;
          if (idx < 400) stg128(g_woP + (size_t)((c2 * 8 + pp * 4 + (gg >> 1)) * 10 + n8) * 640 + ((gg & 1) * 40 + j) * 8, v[i]);
        }
      }
      asm volatile("fence.acq_rel.gpu;" ::: "memory");
      __syncwarp();
      if (lane == 0) asm volatile("red.relaxed.gpu.global.add.u32 [%0], 1;" ::"l"(cnt(C_WO + c2)) : "memory");
    } else if (warp == 14 && lane == 0) {
      prefetch_tmap(&tmKT); prefetch_tmap(&tmU4); prefetch_tmap(&tmU1);
      mbar_wait(bars + 8 * B_KTST, 0);
      tma3d_store(&tmKT, 0, tau, jt * 80, sb + OFF_U);
      bulk_commit();
      bulk_wait<0>();
      red_publish(cnt(C_PRE + jt));
      PROF(8);
      poll_ge(cnt(C_PRE + jt), 16);
      mbar_expect(bars + 8 * B_U, 4 * CH_U);
      tma4d(sb + OFF_U, &tmU4, 0, -4, 0, cta * 5, bars + 8 * B_U);
      mbar_wait(bars + 8 * B_FFREE, 0);
      mbar_expect(bars + 8 * B_U4, CH_U);
      tma4d(sb + OFF_U4, &tmU1, 0, -4, 0, cta * 5 + 4, bars + 8 * B_U4);
      PROF(9);
      for (int c = 0; c < 5; ++c) {
        mbar_wait(bars + 8 * (B_YST + c), 0);
        bulk_store(g_yT + (size_t)(cta * 5 + c) * SEQ, sb + OFF_F + c * CH_F, 4096);
        bulk_commit();
      }
      prefetch_tmap(&tmQ); prefetch_tmap(&tmYT);
      mbar_expect(bars + 8 * B_QT, 128 * 160);
      tma2d(sb + OFF_U, &tmQ, jt * 80, tau * 128, bars + 8 * B_QT);
      bulk_wait<0>();
      red_publish(cnt(C_Y + jt), 5);
      PROF(11);
      poll_ge(cnt(C_Y + jt), 80);
      PROF(12);
      mbar_expect(bars + 8 * B_YT, 80 * 256);
      tma2d(sb + OFF_F, &tmYT, tau * 128, jt * 80, bars + 8 * B_YT);
      tma2d(sb + OFF_F + 10240, &tmYT, tau * 128 + 64, jt * 80, bars + 8 * B_YT);
      finish_role();
    }
  } else if (wg == 2) {
    asm volatile("setmaxnreg.inc.sync.aligned.u32 144;");
    const int ct = tid - 256, wc = __shfl_sync(0xffffffffu, warp, 0) - 8;
    const int t0 = tau * 128, c0 = jt * 80;
    const int mi = lane >> 3, r = lane & 7, g = lane >> 2, t = lane & 3;
    const uint32_t U = sb + OFF_U, F = sb + OFF_F;
    if (ct == 0) PROF(14);
    uint32_t dpack = lane < 5 ? (uint32_t)__ldg(prm.ssm_D + cta * 5 + lane) : 0u;
    dpack |= dpack << 16;
    {
      const int c = ct % 10, seg = ct / 10;
      uint4 wv[4];
#pragma unroll
      for (int u = 0; u < 4; ++u) wv[u] = ldg_nc(prm.shift_k + (size_t)(c0 + c * 8 + 2 * u) * 4);
      uint32_t W[4][4];
#pragma unroll
      for (int u = 0; u < 4; ++u) {
        W[0][u] = __byte_perm(wv[u].x, wv[u].z, 0x5410); W[1][u] = __byte_perm(wv[u].x, wv[u].z, 0x7632);
        W[2][u] = __byte_perm(wv[u].y, wv[u].w, 0x5410); W[3][u] = __byte_perm(wv[u].y, wv[u].w, 0x7632);
      }
      mbar_wait(bars + 8 * B_PRE, 0);
      if (ct == 0) PROF(5);
      if (ct < 120) {
        const int nrow = seg == 11 ? 7 : 11;
        const uint32_t ka = U + seg * 11 * 160 + c * 16, va = sb + OFF_STG + seg * 11 * 160 + c * 16;
        uint4 kk[14], vv[11];
#pragma unroll
        for (int i = 0; i < 14; ++i) kk[i] = i < nrow + 3 ? lds128(ka + i * 160) : make_uint4(0, 0, 0, 0);
#pragma unroll
        for (int i = 0; i < 11; ++i) vv[i] = i < nrow ? lds128(va + i * 160) : make_uint4(0, 0, 0, 0);
#pragma unroll
        for (int i = 0; i < 11; ++i) {
          uint32_t res[4];
#pragma unroll
          for (int u = 0; u < 4; ++u) {
            uint32_t acc = hmul2((&kk[i].x)[u], W[3][u]);
            acc = hfma2((&kk[i + 1].x)[u], W[2][u], acc);
            acc = hfma2((&kk[i + 2].x)[u], W[1][u], acc);
            acc = hfma2((&kk[i + 3].x)[u], W[0][u], acc);
            res[u] = hmul2(acc, (&vv[i].x)[u]);
          }
          if (i < nrow) sts128(va + i * 160, make_uint4(res[0], res[1], res[2], res[3]));
        }
      }
    }
    if (ct == 0) PROF(6);
    named_sync(3, 128);
    {
      uint4 v4[10];
#pragma unroll
      for (int k = 0; k < 10; ++k) {
        const int it = wc + 4 * k, c = it % 10, q = it / 10;
        const int tl = 32 * (r >> 1) + 31 - (8 * q + 2 * mi + (r & 1));
        ldsm4t(v4[k].x, v4[k].y, v4[k].z, v4[k].w, sb + OFF_STG + tl * 160 + c * 16);
      }
#pragma unroll
      for (int k = 0; k < 10; ++k) {
        const int it = wc + 4 * k, c = it % 10, q = it / 10;
        sts128(U + (c * 8 + g) * 256 + q * 64 + t * 16, v4[k]);
      }
    }
    fence_async_smem();
    __syncwarp();
    if (lane == 0) { mbar_arrive(bars + 8 * B_KTST); mbar_arrive(bars + 8 * B_STGFREE); }
    if (ct == 0) PROF(7);
    if (ct < 32) prefetch_line(prm.q + ((size_t)cta * 160 + 128 + ct) * 64);
    prefetch_line(prm.q + ((size_t)cta * 160 + ct) * 64);
    mbar_wait(bars + 8 * B_FRAW, 0);
    {
      uint4 fv[10]; uint32_t pv[10];
#pragma unroll
      for (int i = 0; i < 10; ++i) {
        const int cl = i >> 1, qq = ct + (i & 1) * 128;
        const uint32_t a = F + cl * CH_F + 64 + qq * 16;
        fv[i] = lds128(a);
        pv[i] = qq > 0 ? lds32(a - 4) >> 16 : 0u;
      }
#pragma unroll
      for (int i = 0; i < 10; ++i) {
        const int cl = i >> 1, qq = ct + (i & 1) * 128;
        sts128(F + cl * CH_F + 64 + qq * 16 + 4160,
               make_uint4(__byte_perm(pv[i], fv[i].x, 0x5410), __byte_perm(fv[i].x, fv[i].y, 0x5432),
                          __byte_perm(fv[i].y, fv[i].z, 0x5432), __byte_perm(fv[i].z, fv[i].w, 0x5432)));
      }
      if (ct < 40) sts128(F + (ct >> 3) * CH_F + ((ct >> 2) & 1) * 4160 + (ct & 3) * 16, make_uint4(0, 0, 0, 0));
    }
    mbar_wait(bars + 8 * B_U, 0);
    named_sync(3, 128);
    if (ct == 0) PROF(10);
    if (lane == 0) mbar_arrive(bars + 8 * B_CIN);
    constexpr int NOWN = 5;
#pragma unroll 1
    for (int i = 0; i < NOWN; ++i) {
      const int cl = NOWN == 5 ? i : (i == 0 ? 0 : i + 2);
      if (cl == 4) mbar_wait(bars + 8 * B_U4, 0);
      conv_channel(sb, cl, wc, lane, __shfl_sync(0xffffffffu, dpack, cl), 3);
      if (ct == 0 && i == 0) PROF(27);
    }
    if (ct == 0) PROF(30);
    const uint32_t YT = sb + OFF_F, YN = sb + OFF_F + 20480;
    mbar_wait(bars + 8 * B_YT, 0);
    {
      int w2 = wc, l2 = lane;
      asm volatile("" : "+r"(w2), "+r"(l2));
      const int r2 = l2 & 7, m2 = l2 >> 3;
      uint4 x[10];
#pragma unroll
      for (int k = 0; k < 10; ++k) {
        const int it = w2 + 4 * k, c = it % 10, tq = it / 10, ch = 8 * c + r2, j = 4 * tq + m2;
        ldsm4t(x[k].x, x[k].y, x[k].z, x[k].w, YT + (j >> 3) * 10240 + ch * 128 + (((j & 7) ^ (ch & 7)) << 4));
      }
#pragma unroll
      for (int k = 0; k < 10; ++k) {
        const int it = w2 + 4 * k, c = it % 10, tq = it / 10;
        const int s = (8 * (4 * tq + m2) + r2) ^ 31;
        stsm4(YN + s * 176 + c * 16, x[k].x, x[k].y, x[k].z, x[k].w);
      }
    }
    mbar_wait(bars + 8 * B_QT, 0);
    named_sync(3, 128);
#pragma unroll
    for (int i = 0; i < 10; ++i) {
      const int idx = ct + 128 * i, row = idx / 10, c = idx % 10;
      const uint4 y = lds128(YN + row * 176 + c * 16), q = lds128(U + row * 160 + c * 16);
      stg128(prm.out + (size_t)(t0 + row) * (2 * DM) + c0 + c * 8,
             make_uint4(hmul2(q.x, y.x), hmul2(q.y, y.y), hmul2(q.z, y.z), hmul2(q.w, y.w)));
    }
    if (ct == 0) PROF(13);
  } else {
    asm volatile("setmaxnreg.inc.sync.aligned.u32 168;");
    const int wq = __shfl_sync(0xffffffffu, warp, 0);
    const int mi = lane >> 3, r = lane & 7;
    const uint32_t stg = sb + OFF_STG;
    {
      float acc1[96], acc2[24];
#pragma unroll 1
      for (int it = 0; it < 10; ++it) {
        const int s = it % NST1;
        mbar_wait(bars + 8 * (B_FULL1 + s), (it / NST1) & 1);
        if (tid == 0) PROF(32 + it);
        const uint32_t st = sb + s * ST1;
        wg_fence();
#pragma unroll
        for (int kk = 0; kk < 4; ++kk) {
          const uint64_t da = make_desc(st + wg * 8192 + kk * 32, 16, 1024, 1);
          const uint64_t db1 = make_desc(st + ST1_B128 + (kk >> 1) * 12288 + (kk & 1) * 2048, 4096, 1024, 1);
          const uint64_t db2 = make_desc(st + ST1_B32 + (kk >> 1) * 3072 + (kk & 1) * 512, 1024, 256, 3);
          wgmma_n192(acc1, da, db1, (it | kk) != 0);
          wgmma_n48(acc2, da, db2, (it | kk) != 0);
        }
        wg_commit();
        wg_wait<0>();
        if (it + NST1 < 10 && lane < 2) mbar_arrive_cta(bars + 8 * (B_EMPTY1 + s), lane);
        if (it == 7 && lane == 0) mbar_arrive(bars + 8 * B_FFREE);
      }
      reg_fence(acc1); reg_fence(acc2);
      if (tid == 0) PROF(17);
      named_sync(1, 256);
      if (tid == 0) mbar_arrive(bars + 8 * B_RINGFREE);
      const uint32_t rowo = (16 * wq + 8 * (mi & 1) + r) * 16;
      const int t4 = lane & 3;
#pragma unroll
      for (int kv = 0; kv < 2; ++kv) {
#pragma unroll
        for (int tp = 0; tp < 5; ++tp) {
          uint32_t w[4];
#pragma unroll
          for (int hh = 0; hh < 2; ++hh) {
            const int tile = 2 * tp + hh;
            if (tile < 8) {
              const int o = 32 * (kv + 1) + 4 * tile;
              w[2 * hh] = pack_bf16(acc1[o], acc1[o + 1]); w[2 * hh + 1] = pack_bf16(acc1[o + 2], acc1[o + 3]);
            } else {
              const int o = 8 * (kv + 1) + 4 * (tile - 8);
              w[2 * hh] = pack_bf16(acc2[o], acc2[o + 1]); w[2 * hh + 1] = pack_bf16(acc2[o + 2], acc2[o + 3]);
            }
          }
          const int tA = 2 * tp, tB = 2 * tp + 1;
          const int plA = (tA / 5) * 33 + (kv ? 5 : 0) + tA % 5, plB = (tB / 5) * 33 + (kv ? 5 : 0) + tB % 5;
          if (kv == 1 && (tA % 5 == 2 || tB % 5 == 2)) {
            const int hh = (tA % 5 == 2) ? 0 : 1, pr = (hh ? tB : tA) / 5;
            const uint32_t x0 = w[2 * hh], x1 = w[2 * hh + 1];
            const uint32_t oneE = t4 == 2 ? 0x00003F80u : 0u, oneO = t4 == 0 ? 0x00003F80u : 0u;
            stsm2(sb + 2 * PAIR + (pr * 33 + 10) * PLANE + (16 * wq + (lane & 15)) * 16, t4 >= 2 ? x0 : oneO, t4 >= 2 ? x1 : oneO);
            w[2 * hh] = t4 < 2 ? x0 : oneE; w[2 * hh + 1] = t4 < 2 ? x1 : oneE;
          }
          stsm4(sb + 2 * PAIR + rowo + ((mi >> 1) ? plB : plA) * PLANE, w[0], w[1], w[2], w[3]);
        }
      }
      fence_async_smem();
      __syncwarp();
      if (lane == 0) mbar_arrive(bars + 8 * B_KVST);
      mbar_wait(bars + 8 * B_STGFREE, 0);
      const uint32_t rq = stg + rowo + (mi >> 1) * PLANE;
#pragma unroll
      for (int tp = 0; tp < 4; ++tp)
        stsm4(rq + tp * 2 * PLANE, pack_bf16(acc1[8 * tp], acc1[8 * tp + 1]), pack_bf16(acc1[8 * tp + 2], acc1[8 * tp + 3]),
              pack_bf16(acc1[8 * tp + 4], acc1[8 * tp + 5]), pack_bf16(acc1[8 * tp + 6], acc1[8 * tp + 7]));
      stsm4(rq + 8 * PLANE, pack_bf16(acc2[0], acc2[1]), pack_bf16(acc2[2], acc2[3]), pack_bf16(acc2[4], acc2[5]), pack_bf16(acc2[6], acc2[7]));
    }
    if (rb < 2) {
      const int nz = (2 - rb) * (PAIR / 16);
#pragma unroll 1
      for (int i = tid; i < 2 * nz; i += 256) sts128(sb + (i >= nz ? PWIN + (i - nz) * 16 : i * 16), make_uint4(0, 0, 0, 0));
      fence_async_smem();
    }
    named_sync(2, 256);
    if (tid == 0) PROF(18);
    attn_all(sb, stg, bars, wq, lane, rb >= 2 ? 0 : 4 - 2 * rb);
    if (tid == 0) PROF(19);
    float acc[40];
#pragma unroll 1
    for (int it = 0; it < 8; ++it) {
      const int s = it & 3;
      mbar_wait(bars + 8 * (B_FULL2 + s), it >> 2);
      if (it == 0 && tid == 0) PROF(21);
      if (it == 4 && tid == 0) PROF(25);
      const uint32_t st = sb + s * ST2;
      wg_fence();
#pragma unroll
      for (int kk = 0; kk < 5; ++kk)
        wgmma_n80(acc, make_desc(st + wg * 1024 + kk * 2 * PLANE, PLANE, 128, 0), make_desc(st + 20480 + kk * 256, 128, 1280, 0), (it | kk) != 0);
      wg_commit();
      wg_wait<0>();
      if (it < 4 && lane < 2) mbar_arrive_cta(bars + 8 * (B_EMPTY2 + s), lane);
    }
    reg_fence(acc);
    if (tid == 0) PROF(22);
    named_sync(1, 256);
    {
      const uint32_t rowa = sb + (16 * wq + 8 * (mi & 1) + r) * 160 + (mi >> 1) * 16;
#pragma unroll
      for (int tp = 0; tp < 5; ++tp)
        stsm4(rowa + tp * 32, pack_bf16(acc[8 * tp], acc[8 * tp + 1]), pack_bf16(acc[8 * tp + 2], acc[8 * tp + 3]),
              pack_bf16(acc[8 * tp + 4], acc[8 * tp + 5]), pack_bf16(acc[8 * tp + 6], acc[8 * tp + 7]));
      fence_async_smem();
      __syncwarp();
      if (lane == 0) {
        tma2d_store(&tmOut, DM + c2 * 80, rb2 * 128 + 16 * wq, sb + wq * 2560);
        bulk_commit();
        bulk_wait0_read();
      }
    }
    if (tid == 0) PROF(23);
  }
}

typedef CUresult (*EncodeFn)(CUtensorMap*, CUtensorMapDataType, cuuint32_t, void*, const cuuint64_t*, const cuuint64_t*,
                             const cuuint32_t*, const cuuint32_t*, CUtensorMapInterleave, CUtensorMapSwizzle,
                             CUtensorMapL2promotion, CUtensorMapFloatOOBfill);

CUtensorMap make_map(EncodeFn enc, const void* p, int rank, const cuuint64_t* dims, const cuuint64_t* strides,
                     const cuuint32_t* box, CUtensorMapSwizzle sw) {
  CUtensorMap m;
  const cuuint32_t es[5] = {1, 1, 1, 1, 1};
  enc(&m, CU_TENSOR_MAP_DATA_TYPE_BFLOAT16, rank, const_cast<void*>(p), dims, strides, box, es,
      CU_TENSOR_MAP_INTERLEAVE_NONE, sw, CU_TENSOR_MAP_L2_PROMOTION_L2_128B, CU_TENSOR_MAP_FLOAT_OOB_FILL_NONE);
  return m;
}

}

extern "C" void kernel_launch(void* const* d_in, const int* in_sizes, int n_in, void* d_out, int out_size) {
  (void)in_sizes; (void)n_in; (void)out_size;
  static EncodeFn enc = nullptr;
  static void* kt_ptr = nullptr;
  static void* yt_ptr = nullptr;
  if (!enc) {
    void* fn = nullptr;
    cudaDriverEntryPointQueryResult qr;
    cudaGetDriverEntryPoint("cuTensorMapEncodeTiled", &fn, cudaEnableDefault, &qr);
    enc = (EncodeFn)fn;
    cudaGetSymbolAddress(&kt_ptr, g_kvT);
    cudaGetSymbolAddress(&yt_ptr, g_yT);
    cudaFuncSetAttribute(h3_swa_fused_kernel, cudaFuncAttributeMaxDynamicSharedMemorySize, SMEM_BYTES);
  }
  const void* x = d_in[6];
  const void* wqkv = d_in[7];
  const void* wo = d_in[8];
  CUtensorMap tmX, tmW128, tmW32, tmOut, tmKT, tmKin, tmVin, tmQ, tmYT, tmU4, tmU1;
  { cuuint64_t d[2] = {640, 2048}, s[1] = {1280}; cuuint32_t b[2] = {64, 128};
    tmX = make_map(enc, x, 2, d, s, b, CU_TENSOR_MAP_SWIZZLE_128B); }
  { cuuint64_t d[3] = {640, 640, 3}, s[2] = {3840, 1280}; cuuint32_t b[3] = {64, 32, 3};
    tmW128 = make_map(enc, wqkv, 3, d, s, b, CU_TENSOR_MAP_SWIZZLE_128B); }
  { cuuint64_t d[3] = {640, 640, 3}, s[2] = {3840, 1280}; cuuint32_t b[3] = {16, 32, 3};
    tmW32 = make_map(enc, wqkv, 3, d, s, b, CU_TENSOR_MAP_SWIZZLE_32B); }
  { cuuint64_t d[2] = {1280, 2048}, s[1] = {2560}; cuuint32_t b[2] = {80, 16};
    tmOut = make_map(enc, d_out, 2, d, s, b, CU_TENSOR_MAP_SWIZZLE_NONE); }
  { cuuint64_t d[3] = {128, 16, 640}, s[2] = {256, 4096}; cuuint32_t b[3] = {128, 1, 80};
    tmKT = make_map(enc, kt_ptr, 3, d, s, b, CU_TENSOR_MAP_SWIZZLE_NONE); }
  { cuuint64_t d[4] = {32, 16, 4, 640}, s[3] = {256, 64, 4096}; cuuint32_t b[4] = {32, 20, 4, 4};
    tmU4 = make_map(enc, kt_ptr, 4, d, s, b, CU_TENSOR_MAP_SWIZZLE_NONE); }
  { cuuint64_t d[4] = {32, 16, 4, 640}, s[3] = {256, 64, 4096}; cuuint32_t b[4] = {32, 20, 4, 1};
    tmU1 = make_map(enc, kt_ptr, 4, d, s, b, CU_TENSOR_MAP_SWIZZLE_NONE); }
  { cuuint64_t d[2] = {640, 2048}, s[1] = {1280}; cuuint32_t b[2] = {80, 131};
    tmKin = make_map(enc, d_in[1], 2, d, s, b, CU_TENSOR_MAP_SWIZZLE_NONE); }
  { cuuint64_t d[2] = {640, 2048}, s[1] = {1280}; cuuint32_t b[2] = {80, 128};
    tmVin = make_map(enc, d_in[2], 2, d, s, b, CU_TENSOR_MAP_SWIZZLE_NONE); }
  { cuuint64_t d[2] = {640, 2048}, s[1] = {1280}; cuuint32_t b[2] = {80, 128};
    tmQ = make_map(enc, d_in[0], 2, d, s, b, CU_TENSOR_MAP_SWIZZLE_NONE); }
  { cuuint64_t d[2] = {2048, 640}, s[1] = {4096}; cuuint32_t b[2] = {64, 80};
    tmYT = make_map(enc, yt_ptr, 2, d, s, b, CU_TENSOR_MAP_SWIZZLE_128B); }
  Params prm;
  prm.q = (const uint16_t*)d_in[0]; prm.k = (const uint16_t*)d_in[1]; prm.v = (const uint16_t*)d_in[2];
  prm.x = (const uint16_t*)x; prm.wqkv = (const uint16_t*)wqkv; prm.wo = (const uint16_t*)wo;
  prm.shift_k = (const uint16_t*)d_in[3]; prm.ssm_k = (const uint16_t*)d_in[4];
  prm.ssm_D = (const uint16_t*)d_in[5]; prm.out = (uint16_t*)d_out;
  h3_swa_fused_kernel<<<128, 512, SMEM_BYTES>>>(tmX, tmW128, tmW32, tmOut, tmKT, tmKin, tmVin, tmQ, tmYT, tmU4, tmU1, prm);
}
```

```cpp
#include <cuda_runtime.h>
#include <cuda.h>
#include <cuda_bf16.h>
#include <stdint.h>

#define DEVINL __device__ __forceinline__

namespace {

constexpr int SEQ = 2048;
constexpr int DM = 640;

constexpr int ST1 = 47104;
constexpr int ST1_B128 = 16384;
constexpr int ST1_B32 = 40960;
constexpr int NST1 = 4;
constexpr int ST2 = 33280;
constexpr int NST2 = 4;
constexpr int CH_U = 5120;
constexpr int UPL = 1280;
constexpr int CH_F = 8320;
constexpr int OFF_F = 3 * ST1;
constexpr int OFF_U = 4 * ST1;
constexpr int OFF_KT = OFF_F + 3 * CH_F;
constexpr int OFF_U4 = OFF_F + 5 * CH_F;
constexpr int OFF_STG = OFF_U + 21120;
constexpr int OFF_BAR = OFF_STG + 20480;
constexpr int SMEM_BYTES = OFF_BAR + 512;

constexpr int B_FULL1 = 0, B_EMPTY1 = 4, B_RINGFREE = 8, B_HALO = 9, B_FULL2 = 11, B_EMPTY2 = 15, B_U = 19, B_KVST = 20,
              B_OST = 21, B_PRE = 23, B_KTST = 24, B_U4 = 25, B_STGFREE = 26, B_FFREE = 27, B_CIN = 28, B_YST = 29, B_OPUB = 34, B_FRAW = 35, B_QT = 36, B_YT = 37, B_P0PUB = 38, B_KVST1 = 39;

__device__ __align__(1024) uint16_t g_kv[8 * 16 * 22 * 1024];
__device__ __align__(1024) uint16_t g_o[SEQ * DM];
__device__ __align__(1024) uint16_t g_kvT[DM * SEQ];
__device__ __align__(1024) uint16_t g_yT[DM * SEQ];
__device__ __align__(1024) uint16_t g_woP[DM * DM];
constexpr int CS = 32;
constexpr int C_KV = 0, C_O = 256, C_PRE = 288, C_Y = 296, C_WO = 304, C_DONE = 312, C_NUM = 313;
__device__ unsigned g_cnt[C_NUM * CS];
__device__ unsigned g_err;
#define PROF(slot) do {} while (0)

DEVINL void mbar_init(uint32_t a, uint32_t c) { asm volatile("mbarrier.init.shared::cta.b64 [%0], %1;" ::"r"(a), "r"(c)); }
DEVINL void mbar_expect(uint32_t a, uint32_t b) {
  asm volatile("mbarrier.arrive.expect_tx.shared::cta.b64 _, [%0], %1;" ::"r"(a), "r"(b) : "memory");
}
DEVINL void mbar_arrive(uint32_t a) { asm volatile("mbarrier.arrive.shared::cta.b64 _, [%0];" ::"r"(a) : "memory"); }
DEVINL void mbar_arrive_cta(uint32_t a, uint32_t cta) {
  asm volatile("{\n.reg .b32 ra;\nmapa.shared::cluster.u32 ra, %0, %1;\nmbarrier.arrive.shared::cluster.b64 _, [ra];\n}"
               ::"r"(a), "r"(cta) : "memory");
}
DEVINL bool mbar_try(uint32_t a, uint32_t p) {
  uint32_t ok;
  asm volatile("{\n.reg .pred P;\nmbarrier.try_wait.parity.shared::cta.b64 P, [%1], %2;\nselp.u32 %0, 1, 0, P;\n}"
               : "=r"(ok) : "r"(a), "r"(p) : "memory");
  return ok;
}
DEVINL void mbar_wait(uint32_t a, uint32_t p) {
  if (mbar_try(a, p)) return;
  int n = 0;
  while (!mbar_try(a, p)) {
    if (++n > (1 << 18)) { g_err = 1; break; }
  }
}
DEVINL void poll_ge(const unsigned* p, unsigned target) {
  int n = 0;
  while (true) {
    unsigned v;
    asm volatile("ld.relaxed.gpu.global.u32 %0, [%1];" : "=r"(v) : "l"(p) : "memory");
    if (v >= target) break;
    if (++n > (1 << 20)) { g_err = 2; break; }
  }
  asm volatile("fence.acquire.gpu;\nfence.proxy.async.global;" ::: "memory");
}
DEVINL void red_publish(unsigned* p, unsigned n = 1) { asm volatile("red.release.gpu.global.add.u32 [%0], %1;" ::"l"(p), "r"(n) : "memory"); }
DEVINL void fence_async_smem() { asm volatile("fence.proxy.async.shared::cta;" ::: "memory"); }
DEVINL void named_sync(int id, int n) { asm volatile("bar.sync %0, %1;" ::"r"(id), "r"(n) : "memory"); }
DEVINL void named_arrive(int id, int n) { asm volatile("bar.arrive %0, %1;" ::"r"(id), "r"(n) : "memory"); }

DEVINL void tma2d(uint32_t dst, const CUtensorMap* m, int c0, int c1, uint32_t bar) {
  asm volatile("cp.async.bulk.tensor.2d.shared::cluster.global.mbarrier::complete_tx::bytes [%0], [%1, {%3, %4}], [%2];"
               ::"r"(dst), "l"(m), "r"(bar), "r"(c0), "r"(c1) : "memory");
}
DEVINL void tma2d_mc(uint32_t dst, const CUtensorMap* m, int c0, int c1, uint32_t bar) {
  asm volatile("cp.async.bulk.tensor.2d.shared::cluster.global.mbarrier::complete_tx::bytes.multicast::cluster [%0], [%1, {%3, %4}], [%2], %5;"
               ::"r"(dst), "l"(m), "r"(bar), "r"(c0), "r"(c1), "h"((uint16_t)3) : "memory");
}
DEVINL void tma3d(uint32_t dst, const CUtensorMap* m, int c0, int c1, int c2, uint32_t bar) {
  asm volatile("cp.async.bulk.tensor.3d.shared::cluster.global.mbarrier::complete_tx::bytes [%0], [%1, {%3, %4, %5}], [%2];"
               ::"r"(dst), "l"(m), "r"(bar), "r"(c0), "r"(c1), "r"(c2) : "memory");
}
DEVINL void tma3d_mc(uint32_t dst, const CUtensorMap* m, int c0, int c1, int c2, uint32_t bar) {
  asm volatile("cp.async.bulk.tensor.3d.shared::cluster.global.mbarrier::complete_tx::bytes.multicast::cluster [%0], [%1, {%3, %4, %5}], [%2], %6;"
               ::"r"(dst), "l"(m), "r"(bar), "r"(c0), "r"(c1), "r"(c2), "h"((uint16_t)3) : "memory");
}
DEVINL void tma2d_store(const CUtensorMap* m, int c0, int c1, uint32_t src) {
  asm volatile("cp.async.bulk.tensor.2d.global.shared::cta.bulk_group [%0, {%2, %3}], [%1];"
               ::"l"(m), "r"(src), "r"(c0), "r"(c1) : "memory");
}
DEVINL void tma3d_store(const CUtensorMap* m, int c0, int c1, int c2, uint32_t src) {
  asm volatile("cp.async.bulk.tensor.3d.global.shared::cta.bulk_group [%0, {%2, %3, %4}], [%1];"
               ::"l"(m), "r"(src), "r"(c0), "r"(c1), "r"(c2) : "memory");
}
DEVINL void bulk_load(uint32_t dst, const void* src, uint32_t bytes, uint32_t bar) {
  asm volatile("cp.async.bulk.shared::cluster.global.mbarrier::complete_tx::bytes [%0], [%1], %2, [%3];"
               ::"r"(dst), "l"(src), "r"(bytes), "r"(bar) : "memory");
}
DEVINL void bulk_load_mc(uint32_t dst, const void* src, uint32_t bytes, uint32_t bar) {
  asm volatile("cp.async.bulk.shared::cluster.global.mbarrier::complete_tx::bytes.multicast::cluster [%0], [%1], %2, [%3], %4;"
               ::"r"(dst), "l"(src), "r"(bytes), "r"(bar), "h"((uint16_t)3) : "memory");
}
DEVINL void tma4d(uint32_t dst, const CUtensorMap* m, int c0, int c1, int c2, int c3, uint32_t bar) {
  asm volatile("cp.async.bulk.tensor.4d.shared::cluster.global.mbarrier::complete_tx::bytes [%0], [%1, {%3, %4, %5, %6}], [%2];"
               ::"r"(dst), "l"(m), "r"(bar), "r"(c0), "r"(c1), "r"(c2), "r"(c3) : "memory");
}
DEVINL void tma5d(uint32_t dst, const CUtensorMap* m, int c0, int c1, int c2, int c3, int c4, uint32_t bar) {
  asm volatile("cp.async.bulk.tensor.5d.shared::cluster.global.mbarrier::complete_tx::bytes [%0], [%1, {%3, %4, %5, %6, %7}], [%2];"
               ::"r"(dst), "l"(m), "r"(bar), "r"(c0), "r"(c1), "r"(c2), "r"(c3), "r"(c4) : "memory");
}
DEVINL void prefetch_tensor2d(const CUtensorMap* m, int c0, int c1) {
  asm volatile("cp.async.bulk.prefetch.tensor.2d.L2.global.tile [%0, {%1, %2}];" ::"l"(m), "r"(c0), "r"(c1) : "memory");
}
DEVINL void prefetch_line(const void* p) { asm volatile("prefetch.global.L2 [%0];" ::"l"(p)); }
DEVINL void prefetch_l2(const void* p, uint32_t bytes) {
  asm volatile("cp.async.bulk.prefetch.L2.global [%0], %1;" ::"l"(p), "r"(bytes) : "memory");
}
template <int N> DEVINL void bulk_wait() { asm volatile("cp.async.bulk.wait_group %0;" ::"n"(N) : "memory"); }
DEVINL void bulk_store(void* dst, uint32_t src, uint32_t bytes) {
  asm volatile("cp.async.bulk.global.shared::cta.bulk_group [%0], [%1], %2;" ::"l"(dst), "r"(src), "r"(bytes) : "memory");
}
DEVINL void bulk_commit() { asm volatile("cp.async.bulk.commit_group;" ::: "memory"); }
DEVINL void bulk_wait0() { asm volatile("cp.async.bulk.wait_group 0;" ::: "memory"); }
DEVINL void bulk_wait0_read() { asm volatile("cp.async.bulk.wait_group.read 0;" ::: "memory"); }
DEVINL void prefetch_tmap(const CUtensorMap* m) { asm volatile("prefetch.tensormap [%0];" ::"l"(m) : "memory"); }

DEVINL uint64_t make_desc(uint32_t addr, uint32_t lbo, uint32_t sbo, uint32_t swz) {
  return (uint64_t)((addr & 0x3FFFF) >> 4) | ((uint64_t)(lbo >> 4) << 16) | ((uint64_t)(sbo >> 4) << 32) | ((uint64_t)swz << 62);
}
DEVINL void wg_fence() { asm volatile("wgmma.fence.sync.aligned;" ::: "memory"); }
DEVINL void wg_commit() { asm volatile("wgmma.commit_group.sync.aligned;" ::: "memory"); }
template <int N> DEVINL void wg_wait() { asm volatile("wgmma.wait_group.sync.aligned %0;" ::"n"(N) : "memory"); }

DEVINL void mma16816(float (&d)[4], uint32_t a0, uint32_t a1, uint32_t a2, uint32_t a3, uint32_t b0, uint32_t b1) {
  asm volatile("mma.sync.aligned.m16n8k16.row.col.f32.bf16.bf16.f32 {%0,%1,%2,%3},{%4,%5,%6,%7},{%8,%9},{%0,%1,%2,%3};"
               : "+f"(d[0]), "+f"(d[1]), "+f"(d[2]), "+f"(d[3]) : "r"(a0), "r"(a1), "r"(a2), "r"(a3), "r"(b0), "r"(b1));
}
DEVINL void mma16816_z(float (&d)[4], uint32_t a0, uint32_t a1, uint32_t a2, uint32_t a3, uint32_t b0, uint32_t b1) {
  asm volatile("mma.sync.aligned.m16n8k16.row.col.f32.bf16.bf16.f32 {%0,%1,%2,%3},{%4,%5,%6,%7},{%8,%9},{%10,%10,%10,%10};"
               : "=f"(d[0]), "=f"(d[1]), "=f"(d[2]), "=f"(d[3]) : "r"(a0), "r"(a1), "r"(a2), "r"(a3), "r"(b0), "r"(b1), "f"(0.f));
}
DEVINL void mma1688(float (&d)[4], uint32_t a0, uint32_t a1, uint32_t b0) {
  asm volatile("mma.sync.aligned.m16n8k8.row.col.f32.bf16.bf16.f32 {%0,%1,%2,%3},{%4,%5},{%6},{%0,%1,%2,%3};"
               : "+f"(d[0]), "+f"(d[1]), "+f"(d[2]), "+f"(d[3]) : "r"(a0), "r"(a1), "r"(b0));
}
DEVINL void ldsm4(uint32_t& r0, uint32_t& r1, uint32_t& r2, uint32_t& r3, uint32_t a) {
  asm volatile("ldmatrix.sync.aligned.m8n8.x4.shared.b16 {%0,%1,%2,%3}, [%4];" : "=r"(r0), "=r"(r1), "=r"(r2), "=r"(r3) : "r"(a));
}
DEVINL void ldsm2(uint32_t& r0, uint32_t& r1, uint32_t a) {
  asm volatile("ldmatrix.sync.aligned.m8n8.x2.shared.b16 {%0,%1}, [%2];" : "=r"(r0), "=r"(r1) : "r"(a));
}
DEVINL void ldsm4t(uint32_t& r0, uint32_t& r1, uint32_t& r2, uint32_t& r3, uint32_t a) {
  asm volatile("ldmatrix.sync.aligned.m8n8.x4.trans.shared.b16 {%0,%1,%2,%3}, [%4];" : "=r"(r0), "=r"(r1), "=r"(r2), "=r"(r3) : "r"(a));
}
DEVINL void ldsm2t(uint32_t& r0, uint32_t& r1, uint32_t a) {
  asm volatile("ldmatrix.sync.aligned.m8n8.x2.trans.shared.b16 {%0,%1}, [%2];" : "=r"(r0), "=r"(r1) : "r"(a));
}
DEVINL void stsm4(uint32_t a, uint32_t r0, uint32_t r1, uint32_t r2, uint32_t r3) {
  asm volatile("stmatrix.sync.aligned.m8n8.x4.shared.b16 [%0], {%1,%2,%3,%4};" ::"r"(a), "r"(r0), "r"(r1), "r"(r2), "r"(r3) : "memory");
}
DEVINL void stsm2(uint32_t a, uint32_t r0, uint32_t r1) {
  asm volatile("stmatrix.sync.aligned.m8n8.x2.shared.b16 [%0], {%1,%2};" ::"r"(a), "r"(r0), "r"(r1) : "memory");
}
DEVINL void stsm4t(uint32_t a, uint32_t r0, uint32_t r1, uint32_t r2, uint32_t r3) {
  asm volatile("stmatrix.sync.aligned.m8n8.x4.trans.shared.b16 [%0], {%1,%2,%3,%4};" ::"r"(a), "r"(r0), "r"(r1), "r"(r2), "r"(r3) : "memory");
}
DEVINL uint32_t lds32(uint32_t a) { uint32_t v; asm volatile("ld.shared.u32 %0, [%1];" : "=r"(v) : "r"(a)); return v; }
DEVINL uint32_t lds32v(uint32_t a) { uint32_t v; asm volatile("ld.volatile.shared.u32 %0, [%1];" : "=r"(v) : "r"(a) : "memory"); return v; }
DEVINL uint4 lds128(uint32_t a) {
  uint4 v; asm volatile("ld.shared.v4.u32 {%0,%1,%2,%3}, [%4];" : "=r"(v.x), "=r"(v.y), "=r"(v.z), "=r"(v.w) : "r"(a)); return v;
}
DEVINL void sts32(uint32_t a, uint32_t v) { asm volatile("st.shared.u32 [%0], %1;" ::"r"(a), "r"(v) : "memory"); }
DEVINL void sts128(uint32_t a, uint4 v) {
  asm volatile("st.shared.v4.u32 [%0], {%1,%2,%3,%4};" ::"r"(a), "r"(v.x), "r"(v.y), "r"(v.z), "r"(v.w) : "memory");
}
DEVINL uint4 ldg_nc(const void* p) {
  uint4 v; asm volatile("ld.global.nc.L1::no_allocate.v4.u32 {%0,%1,%2,%3}, [%4];" : "=r"(v.x), "=r"(v.y), "=r"(v.z), "=r"(v.w) : "l"(p)); return v;
}
DEVINL uint4 ldg_cg(const void* p) {
  uint4 v; asm volatile("ld.global.cg.v4.u32 {%0,%1,%2,%3}, [%4];" : "=r"(v.x), "=r"(v.y), "=r"(v.z), "=r"(v.w) : "l"(p) : "memory"); return v;
}
DEVINL void stg128(void* p, uint4 v) {
  asm volatile("st.global.v4.u32 [%0], {%1,%2,%3,%4};" ::"l"(p), "r"(v.x), "r"(v.y), "r"(v.z), "r"(v.w) : "memory");
}
DEVINL uint32_t pack_bf16(float lo, float hi) {
  uint32_t r; asm("cvt.rn.bf16x2.f32 %0, %1, %2;" : "=r"(r) : "f"(hi), "f"(lo)); return r;
}
DEVINL uint32_t hmul2(uint32_t a, uint32_t b) { uint32_t r; asm("mul.rn.bf16x2 %0, %1, %2;" : "=r"(r) : "r"(a), "r"(b)); return r; }
DEVINL uint32_t hfma2(uint32_t a, uint32_t b, uint32_t c) { uint32_t r; asm("fma.rn.bf16x2 %0, %1, %2, %3;" : "=r"(r) : "r"(a), "r"(b), "r"(c)); return r; }
DEVINL uint32_t hadd2(uint32_t a, uint32_t b) { uint32_t r; asm("add.rn.bf16x2 %0, %1, %2;" : "=r"(r) : "r"(a), "r"(b)); return r; }
DEVINL float ex2(float x) { float r; asm("ex2.approx.ftz.f32 %0, %1;" : "=f"(r) : "f"(x)); return r; }

DEVINL void wgmma_n192(float (&d)[96], uint64_t da, uint64_t db, int scale_d) {
  asm volatile("{\n.reg .pred p;\nsetp.ne.b32 p, %98, 0;\n"
    "wgmma.mma_async.sync.aligned.m64n192k16.f32.bf16.bf16 "
    "{%0,%1,%2,%3,%4,%5,%6,%7,%8,%9,%10,%11,%12,%13,%14,%15,"
    "%16,%17,%18,%19,%20,%21,%22,%23,%24,%25,%26,%27,%28,%29,%30,%31,"
    "%32,%33,%34,%35,%36,%37,%38,%39,%40,%41,%42,%43,%44,%45,%46,%47,"
    "%48,%49,%50,%51,%52,%53,%54,%55,%56,%57,%58,%59,%60,%61,%62,%63,"
    "%64,%65,%66,%67,%68,%69,%70,%71,%72,%73,%74,%75,%76,%77,%78,%79,"
    "%80,%81,%82,%83,%84,%85,%86,%87,%88,%89,%90,%91,%92,%93,%94,%95}, "
    "%96, %97, p, 1, 1, 0, 1;\n}\n"
    : "+f"(d[0]), "+f"(d[1]), "+f"(d[2]), "+f"(d[3]), "+f"(d[4]), "+f"(d[5]), "+f"(d[6]), "+f"(d[7]),
      "+f"(d[8]), "+f"(d[9]), "+f"(d[10]), "+f"(d[11]), "+f"(d[12]), "+f"(d[13]), "+f"(d[14]), "+f"(d[15]),
      "+f"(d[16]), "+f"(d[17]), "+f"(d[18]), "+f"(d[19]), "+f"(d[20]), "+f"(d[21]), "+f"(d[22]), "+f"(d[23]),
      "+f"(d[24]), "+f"(d[25]), "+f"(d[26]), "+f"(d[27]), "+f"(d[28]), "+f"(d[29]), "+f"(d[30]), "+f"(d[31]),
      "+f"(d[32]), "+f"(d[33]), "+f"(d[34]), "+f"(d[35]), "+f"(d[36]), "+f"(d[37]), "+f"(d[38]), "+f"(d[39]),
      "+f"(d[40]), "+f"(d[41]), "+f"(d[42]), "+f"(d[43]), "+f"(d[44]), "+f"(d[45]), "+f"(d[46]), "+f"(d[47]),
      "+f"(d[48]), "+f"(d[49]), "+f"(d[50]), "+f"(d[51]), "+f"(d[52]), "+f"(d[53]), "+f"(d[54]), "+f"(d[55]),
      "+f"(d[56]), "+f"(d[57]), "+f"(d[58]), "+f"(d[59]), "+f"(d[60]), "+f"(d[61]), "+f"(d[62]), "+f"(d[63]),
      "+f"(d[64]), "+f"(d[65]), "+f"(d[66]), "+f"(d[67]), "+f"(d[68]), "+f"(d[69]), "+f"(d[70]), "+f"(d[71]),
      "+f"(d[72]), "+f"(d[73]), "+f"(d[74]), "+f"(d[75]), "+f"(d[76]), "+f"(d[77]), "+f"(d[78]), "+f"(d[79]),
      "+f"(d[80]), "+f"(d[81]), "+f"(d[82]), "+f"(d[83]), "+f"(d[84]), "+f"(d[85]), "+f"(d[86]), "+f"(d[87]),
      "+f"(d[88]), "+f"(d[89]), "+f"(d[90]), "+f"(d[91]), "+f"(d[92]), "+f"(d[93]), "+f"(d[94]), "+f"(d[95])
    : "l"(da), "l"(db), "r"(scale_d));
}

DEVINL void wgmma_n48(float (&d)[24], uint64_t da, uint64_t db, int scale_d) {
  asm volatile("{\n.reg .pred p;\nsetp.ne.b32 p, %26, 0;\n"
    "wgmma.mma_async.sync.aligned.m64n48k16.f32.bf16.bf16 "
    "{%0,%1,%2,%3,%4,%5,%6,%7,%8,%9,%10,%11,%12,%13,%14,%15,"
    "%16,%17,%18,%19,%20,%21,%22,%23}, "
    "%24, %25, p, 1, 1, 0, 1;\n}\n"
    : "+f"(d[0]), "+f"(d[1]), "+f"(d[2]), "+f"(d[3]), "+f"(d[4]), "+f"(d[5]), "+f"(d[6]), "+f"(d[7]),
      "+f"(d[8]), "+f"(d[9]), "+f"(d[10]), "+f"(d[11]), "+f"(d[12]), "+f"(d[13]), "+f"(d[14]), "+f"(d[15]),
      "+f"(d[16]), "+f"(d[17]), "+f"(d[18]), "+f"(d[19]), "+f"(d[20]), "+f"(d[21]), "+f"(d[22]), "+f"(d[23])
    : "l"(da), "l"(db), "r"(scale_d));
}

DEVINL void wgmma_n80(float (&d)[40], uint64_t da, uint64_t db, int scale_d) {
  asm volatile("{\n.reg .pred p;\nsetp.ne.b32 p, %42, 0;\n"
    "wgmma.mma_async.sync.aligned.m64n80k16.f32.bf16.bf16 "
    "{%0,%1,%2,%3,%4,%5,%6,%7,%8,%9,%10,%11,%12,%13,%14,%15,"
    "%16,%17,%18,%19,%20,%21,%22,%23,%24,%25,%26,%27,%28,%29,%30,%31,"
    "%32,%33,%34,%35,%36,%37,%38,%39}, "
    "%40, %41, p, 1, 1, 0, 1;\n}\n"
    : "+f"(d[0]), "+f"(d[1]), "+f"(d[2]), "+f"(d[3]), "+f"(d[4]), "+f"(d[5]), "+f"(d[6]), "+f"(d[7]),
      "+f"(d[8]), "+f"(d[9]), "+f"(d[10]), "+f"(d[11]), "+f"(d[12]), "+f"(d[13]), "+f"(d[14]), "+f"(d[15]),
      "+f"(d[16]), "+f"(d[17]), "+f"(d[18]), "+f"(d[19]), "+f"(d[20]), "+f"(d[21]), "+f"(d[22]), "+f"(d[23]),
      "+f"(d[24]), "+f"(d[25]), "+f"(d[26]), "+f"(d[27]), "+f"(d[28]), "+f"(d[29]), "+f"(d[30]), "+f"(d[31]),
      "+f"(d[32]), "+f"(d[33]), "+f"(d[34]), "+f"(d[35]), "+f"(d[36]), "+f"(d[37]), "+f"(d[38]), "+f"(d[39])
    : "l"(da), "l"(db), "r"(scale_d));
}

DEVINL void wgmma_qk_n64(float (&d)[32], uint32_t a0, uint32_t a1, uint32_t a2, uint32_t a3, uint64_t db, int scale_d) {
  asm volatile("{\n.reg .pred p;\nsetp.ne.b32 p, %37, 0;\n"
    "wgmma.mma_async.sync.aligned.m64n64k16.f32.bf16.bf16 "
    "{%0,%1,%2,%3,%4,%5,%6,%7,%8,%9,%10,%11,%12,%13,%14,%15,"
    "%16,%17,%18,%19,%20,%21,%22,%23,%24,%25,%26,%27,%28,%29,%30,%31}, "
    "{%32,%33,%34,%35}, %36, p, 1, 1, 0;\n}\n"
    : "+f"(d[0]), "+f"(d[1]), "+f"(d[2]), "+f"(d[3]), "+f"(d[4]), "+f"(d[5]), "+f"(d[6]), "+f"(d[7]),
      "+f"(d[8]), "+f"(d[9]), "+f"(d[10]), "+f"(d[11]), "+f"(d[12]), "+f"(d[13]), "+f"(d[14]), "+f"(d[15]),
      "+f"(d[16]), "+f"(d[17]), "+f"(d[18]), "+f"(d[19]), "+f"(d[20]), "+f"(d[21]), "+f"(d[22]), "+f"(d[23]),
      "+f"(d[24]), "+f"(d[25]), "+f"(d[26]), "+f"(d[27]), "+f"(d[28]), "+f"(d[29]), "+f"(d[30]), "+f"(d[31])
    : "r"(a0), "r"(a1), "r"(a2), "r"(a3), "l"(db), "r"(scale_d));
}

DEVINL void wgmma_pv_n24(float (&d)[12], uint32_t a0, uint32_t a1, uint32_t a2, uint32_t a3, uint64_t db, int scale_d) {
  asm volatile("{\n.reg .pred p;\nsetp.ne.b32 p, %17, 0;\n"
    "wgmma.mma_async.sync.aligned.m64n24k16.f32.bf16.bf16 "
    "{%0,%1,%2,%3,%4,%5,%6,%7,%8,%9,%10,%11}, "
    "{%12,%13,%14,%15}, %16, p, 1, 1, 1;\n}\n"
    : "+f"(d[0]), "+f"(d[1]), "+f"(d[2]), "+f"(d[3]), "+f"(d[4]), "+f"(d[5]), "+f"(d[6]), "+f"(d[7]),
      "+f"(d[8]), "+f"(d[9]), "+f"(d[10]), "+f"(d[11])
    : "r"(a0), "r"(a1), "r"(a2), "r"(a3), "l"(db), "r"(scale_d));
}

DEVINL void wgmma_qk_n64_z(float (&d)[32], uint32_t a0, uint32_t a1, uint32_t a2, uint32_t a3, uint64_t db) {
  asm volatile("{\n.reg .pred p;\nsetp.ne.b32 p, 0, 0;\n"
    "wgmma.mma_async.sync.aligned.m64n64k16.f32.bf16.bf16 "
    "{%0,%1,%2,%3,%4,%5,%6,%7,%8,%9,%10,%11,%12,%13,%14,%15,"
    "%16,%17,%18,%19,%20,%21,%22,%23,%24,%25,%26,%27,%28,%29,%30,%31}, "
    "{%32,%33,%34,%35}, %36, p, 1, 1, 0;\n}\n"
    : "=f"(d[0]), "=f"(d[1]), "=f"(d[2]), "=f"(d[3]), "=f"(d[4]), "=f"(d[5]), "=f"(d[6]), "=f"(d[7]),
      "=f"(d[8]), "=f"(d[9]), "=f"(d[10]), "=f"(d[11]), "=f"(d[12]), "=f"(d[13]), "=f"(d[14]), "=f"(d[15]),
      "=f"(d[16]), "=f"(d[17]), "=f"(d[18]), "=f"(d[19]), "=f"(d[20]), "=f"(d[21]), "=f"(d[22]), "=f"(d[23]),
      "=f"(d[24]), "=f"(d[25]), "=f"(d[26]), "=f"(d[27]), "=f"(d[28]), "=f"(d[29]), "=f"(d[30]), "=f"(d[31])
    : "r"(a0), "r"(a1), "r"(a2), "r"(a3), "l"(db));
}

DEVINL void wgmma_pv_n24_z(float (&d)[12], uint32_t a0, uint32_t a1, uint32_t a2, uint32_t a3, uint64_t db) {
  asm volatile("{\n.reg .pred p;\nsetp.ne.b32 p, 0, 0;\n"
    "wgmma.mma_async.sync.aligned.m64n24k16.f32.bf16.bf16 "
    "{%0,%1,%2,%3,%4,%5,%6,%7,%8,%9,%10,%11}, "
    "{%12,%13,%14,%15}, %16, p, 1, 1, 1;\n}\n"
    : "=f"(d[0]), "=f"(d[1]), "=f"(d[2]), "=f"(d[3]), "=f"(d[4]), "=f"(d[5]), "=f"(d[6]), "=f"(d[7]),
      "=f"(d[8]), "=f"(d[9]), "=f"(d[10]), "=f"(d[11])
    : "r"(a0), "r"(a1), "r"(a2), "r"(a3), "l"(db));
}

DEVINL void wgmma_cv_n64(float (&d)[32], uint32_t a0, uint32_t a1, uint32_t a2, uint32_t a3, uint64_t db) {
  asm volatile("{\n.reg .pred p;\nsetp.ne.b32 p, 1, 0;\n"
    "wgmma.mma_async.sync.aligned.m64n64k16.f32.bf16.bf16 "
    "{%0,%1,%2,%3,%4,%5,%6,%7,%8,%9,%10,%11,%12,%13,%14,%15,"
    "%16,%17,%18,%19,%20,%21,%22,%23,%24,%25,%26,%27,%28,%29,%30,%31}, "
    "{%32,%33,%34,%35}, %36, p, 1, 1, 0;\n}\n"
    : "+f"(d[0]), "+f"(d[1]), "+f"(d[2]), "+f"(d[3]), "+f"(d[4]), "+f"(d[5]), "+f"(d[6]), "+f"(d[7]),
      "+f"(d[8]), "+f"(d[9]), "+f"(d[10]), "+f"(d[11]), "+f"(d[12]), "+f"(d[13]), "+f"(d[14]), "+f"(d[15]),
      "+f"(d[16]), "+f"(d[17]), "+f"(d[18]), "+f"(d[19]), "+f"(d[20]), "+f"(d[21]), "+f"(d[22]), "+f"(d[23]),
      "+f"(d[24]), "+f"(d[25]), "+f"(d[26]), "+f"(d[27]), "+f"(d[28]), "+f"(d[29]), "+f"(d[30]), "+f"(d[31])
    : "r"(a0), "r"(a1), "r"(a2), "r"(a3), "l"(db));
}

DEVINL void wgmma_cv_n48(float (&d)[24], uint32_t a0, uint32_t a1, uint32_t a2, uint32_t a3, uint64_t db) {
  asm volatile("{\n.reg .pred p;\nsetp.ne.b32 p, 1, 0;\n"
    "wgmma.mma_async.sync.aligned.m64n48k16.f32.bf16.bf16 "
    "{%0,%1,%2,%3,%4,%5,%6,%7,%8,%9,%10,%11,%12,%13,%14,%15,"
    "%16,%17,%18,%19,%20,%21,%22,%23}, "
    "{%24,%25,%26,%27}, %28, p, 1, 1, 0;\n}\n"
    : "+f"(d[0]), "+f"(d[1]), "+f"(d[2]), "+f"(d[3]), "+f"(d[4]), "+f"(d[5]), "+f"(d[6]), "+f"(d[7]),
      "+f"(d[8]), "+f"(d[9]), "+f"(d[10]), "+f"(d[11]), "+f"(d[12]), "+f"(d[13]), "+f"(d[14]), "+f"(d[15]),
      "+f"(d[16]), "+f"(d[17]), "+f"(d[18]), "+f"(d[19]), "+f"(d[20]), "+f"(d[21]), "+f"(d[22]), "+f"(d[23])
    : "r"(a0), "r"(a1), "r"(a2), "r"(a3), "l"(db));
}

DEVINL void wgmma_cv_n32(float (&d)[16], uint32_t a0, uint32_t a1, uint32_t a2, uint32_t a3, uint64_t db) {
  asm volatile("{\n.reg .pred p;\nsetp.ne.b32 p, 1, 0;\n"
    "wgmma.mma_async.sync.aligned.m64n32k16.f32.bf16.bf16 "
    "{%0,%1,%2,%3,%4,%5,%6,%7,%8,%9,%10,%11,%12,%13,%14,%15}, "
    "{%16,%17,%18,%19}, %20, p, 1, 1, 0;\n}\n"
    : "+f"(d[0]), "+f"(d[1]), "+f"(d[2]), "+f"(d[3]), "+f"(d[4]), "+f"(d[5]), "+f"(d[6]), "+f"(d[7]),
      "+f"(d[8]), "+f"(d[9]), "+f"(d[10]), "+f"(d[11]), "+f"(d[12]), "+f"(d[13]), "+f"(d[14]), "+f"(d[15])
    : "r"(a0), "r"(a1), "r"(a2), "r"(a3), "l"(db));
}

DEVINL void wgmma_cv_n16(float (&d)[8], uint32_t a0, uint32_t a1, uint32_t a2, uint32_t a3, uint64_t db) {
  asm volatile("{\n.reg .pred p;\nsetp.ne.b32 p, 1, 0;\n"
    "wgmma.mma_async.sync.aligned.m64n16k16.f32.bf16.bf16 "
    "{%0,%1,%2,%3,%4,%5,%6,%7}, "
    "{%8,%9,%10,%11}, %12, p, 1, 1, 0;\n}\n"
    : "+f"(d[0]), "+f"(d[1]), "+f"(d[2]), "+f"(d[3]), "+f"(d[4]), "+f"(d[5]), "+f"(d[6]), "+f"(d[7])
    : "r"(a0), "r"(a1), "r"(a2), "r"(a3), "l"(db));
}

#define ATT_T(i) do {} while (0)
#define ATT_IMAX 0
#define ATT_WAIT0 0
#define ATT_SPLIT 2
constexpr float SM_C = 0.22360679774997896f * 1.4426950408889634f;
constexpr float NEG_INF = -INFINITY;
constexpr int PLANE = 2048;
constexpr int PAIR = 11 * PLANE;
constexpr int SEG = 2 * PAIR;
constexpr int PWIN = 3 * PAIR;

template <int N> DEVINL void reg_fence(float (&d)[N]) {
#pragma unroll
  for (int i = 0; i < N; ++i) asm volatile("" : "+f"(d[i])::"memory");
}
DEVINL float ex2v(float x) { float r; asm volatile("ex2.approx.ftz.f32 %0, %1;" : "=f"(r) : "f"(x)); return r; }
DEVINL uint32_t bsel(uint32_t a, uint32_t b, uint32_t m) { return (a & m) | (b & ~m); }
DEVINL float fsel(float a, float b, uint32_t m) { return __uint_as_float(bsel(__float_as_uint(a), __float_as_uint(b), m)); }
typedef uint64_t desc_t;
DEVINL desc_t kdesc(desc_t d) { return d; }
DEVINL desc_t vdesc(desc_t d) { return d; }

DEVINL void mma_qk(float (&s)[32], const uint32_t (&a)[4], const uint32_t (&a8)[2], desc_t kmain, desc_t ktail) {
  wgmma_qk_n64_z(s, a[0], a[1], a[2], a[3], kdesc(kmain));
  wgmma_qk_n64(s, a8[0], a8[1], 0u, 0u, kdesc(ktail), 1);
}
template <bool FIRST>
DEVINL void mma_pv(float (&o)[12], const uint32_t (&p)[16], desc_t v) {
  if (FIRST) wgmma_pv_n24_z(o, p[0], p[1], p[2], p[3], vdesc(v));
  else wgmma_pv_n24(o, p[0], p[1], p[2], p[3], vdesc(v), 1);
#pragma unroll
  for (int b = 1; b < 4; ++b) wgmma_pv_n24(o, p[4 * b], p[4 * b + 1], p[4 * b + 2], p[4 * b + 3], vdesc(v + b * 16), 1);
}
DEVINL void row_max_f(const float (&s)[32], float& x0o, float& x1o) {
  float x0 = fmaxf(s[0], s[1]), x1 = fmaxf(s[2], s[3]), y0 = fmaxf(s[4], s[5]), y1 = fmaxf(s[6], s[7]);
#pragma unroll
  for (int i = 2; i < 8; i += 2) {
    x0 = fmaxf(x0, fmaxf(s[4 * i], s[4 * i + 1]));
    x1 = fmaxf(x1, fmaxf(s[4 * i + 2], s[4 * i + 3]));
    y0 = fmaxf(y0, fmaxf(s[4 * i + 4], s[4 * i + 5]));
    y1 = fmaxf(y1, fmaxf(s[4 * i + 6], s[4 * i + 7]));
  }
  x0 = fmaxf(x0, y0); x1 = fmaxf(x1, y1);
  x0 = fmaxf(x0, __shfl_xor_sync(0xffffffffu, x0, 1));
  x1 = fmaxf(x1, __shfl_xor_sync(0xffffffffu, x1, 1));
  x0o = fmaxf(x0, __shfl_xor_sync(0xffffffffu, x0, 2));
  x1o = fmaxf(x1, __shfl_xor_sync(0xffffffffu, x1, 2));
}
DEVINL void row_max(const float (&s)[32], float pm0, float pm1, float& x0o, float& x1o) {
#define FI(i) __float_as_int(s[i])
  int x0 = __vimax3_s32(FI(0), FI(1), FI(4)), x1 = __vimax3_s32(FI(2), FI(3), FI(6));
  int y0 = __vimax3_s32(FI(5), FI(8), FI(9)), y1 = __vimax3_s32(FI(7), FI(10), FI(11));
  x0 = __vimax3_s32(x0, FI(12), FI(13)); x1 = __vimax3_s32(x1, FI(14), FI(15));
  y0 = __vimax3_s32(y0, FI(16), FI(17)); y1 = __vimax3_s32(y1, FI(18), FI(19));
  x0 = __vimax3_s32(x0, FI(20), FI(21)); x1 = __vimax3_s32(x1, FI(22), FI(23));
  y0 = __vimax3_s32(y0, FI(24), FI(25)); y1 = __vimax3_s32(y1, FI(26), FI(27));
  x0 = __vimax3_s32(x0, FI(28), FI(29)); x1 = __vimax3_s32(x1, FI(30), FI(31));
#undef FI
  x0 = max(x0, y0); x1 = max(x1, y1);
  x0 = max(x0, __shfl_xor_sync(0xffffffffu, x0, 1));
  x1 = max(x1, __shfl_xor_sync(0xffffffffu, x1, 1));
  x0 = max(x0, __shfl_xor_sync(0xffffffffu, x0, 2));
  x1 = max(x1, __shfl_xor_sync(0xffffffffu, x1, 2));
  float f0 = __int_as_float(x0), f1 = __int_as_float(x1);
  if (__any_sync(0xffffffffu, (x0 < 0 && !(pm0 >= 0.f)) || (x1 < 0 && !(pm1 >= 0.f)))) {
    f0 = s[0]; f1 = s[2];
#pragma unroll
    for (int i = 0; i < 8; ++i) {
      f0 = fmaxf(f0, fmaxf(s[4 * i], s[4 * i + 1]));
      f1 = fmaxf(f1, fmaxf(s[4 * i + 2], s[4 * i + 3]));
    }
    f0 = fmaxf(f0, __shfl_xor_sync(0xffffffffu, f0, 1));
    f1 = fmaxf(f1, __shfl_xor_sync(0xffffffffu, f1, 1));
    f0 = fmaxf(f0, __shfl_xor_sync(0xffffffffu, f0, 2));
    f1 = fmaxf(f1, __shfl_xor_sync(0xffffffffu, f1, 2));
  }
  x0o = f0; x1o = f1;
}
template <int I0, int I1>
DEVINL void sm_exp(const float (&s)[32], uint32_t (&p)[16], float n0, float n1) {
#pragma unroll
  for (int i = I0; i < I1; ++i) {
    const float e0 = ex2v(fmaf(s[4 * i], SM_C, n0)), e1 = ex2v(fmaf(s[4 * i + 1], SM_C, n0));
    const float e2 = ex2v(fmaf(s[4 * i + 2], SM_C, n1)), e3 = ex2v(fmaf(s[4 * i + 3], SM_C, n1));
    p[2 * i] = pack_bf16(e0, e1);
    p[2 * i + 1] = pack_bf16(e2, e3);
  }
}
DEVINL void rescale(float (&o)[12], float al0, float al1) {
#pragma unroll
  for (int n = 0; n < 3; ++n) { o[4 * n] *= al0; o[4 * n + 1] *= al0; o[4 * n + 2] *= al1; o[4 * n + 3] *= al1; }
}
struct SoftmaxState { float m0, m1, n0, n1, al0, al1; };
DEVINL void next_max(SoftmaxState& st, float x0, float x1, bool valid) {
  x0 = fmaxf(valid ? x0 : NEG_INF, st.m0); x1 = fmaxf(valid ? x1 : NEG_INF, st.m1);
  const float c0 = -x0 * SM_C, c1 = -x1 * SM_C;
  st.al0 = ex2(fmaf(st.m0, SM_C, c0)); st.al1 = ex2(fmaf(st.m1, SM_C, c1));
  st.m0 = x0; st.m1 = x1;
  st.n0 = valid ? c0 : NEG_INF; st.n1 = valid ? c1 : NEG_INF;
}
template <bool PVPEND, int SPLIT>
DEVINL void step(const float (&cur)[32], float (&nxt)[32], float (&o)[12], uint32_t (&p)[16], SoftmaxState& st, bool valid_nxt) {
  const float n0 = st.n0, n1 = st.n1, pa0 = st.al0, pa1 = st.al1;
  sm_exp<0, SPLIT>(cur, p, n0, n1);
  wg_wait<(PVPEND && !ATT_WAIT0) ? 1 : 0>();
  reg_fence(nxt);
  float x0, x1;
  row_max_f(nxt, x0, x1);
  sm_exp<SPLIT, 8>(cur, p, n0, n1);
  next_max(st, x0, x1, valid_nxt);
  if (PVPEND) { wg_wait<0>(); reg_fence(o); rescale(o, pa0, pa1); }
}

DEVINL void attn_all(uint32_t ring, uint32_t stg, uint32_t bars, int wq, int lane, int cmin) {
  const int wg = wq >> 2, w = wq & 3;
  const int g = lane >> 2, t = lane & 3, mi = lane >> 3, r = lane & 7;
  const uint32_t T0 = (2 * t > g) ? 0xFFFFFFFFu : 0u, T1 = (2 * t + 1 > g) ? 0xFFFFFFFFu : 0u;
  const uint32_t tri = (T0 & 0xFFFFu) | (T1 & 0xFFFF0000u);
  const uint32_t rowQ = stg + (mi >> 1) * PLANE + (16 * wq + r + 8 * (mi & 1)) * 16;
  const uint32_t rowQ8 = stg + 2 * PLANE + (16 * wq + (lane & 15)) * 16;
  constexpr uint32_t S16 = PAIR >> 4, P16 = PLANE >> 4;
  const uint32_t aE = ((ring + wg * 1024) & 0x3FFFF) >> 4, aO = ((ring + wg * PAIR + (wg ^ 1) * 1024) & 0x3FFFF) >> 4;
  const desc_t kE = (desc_t)(aE | (P16 << 16)) | ((desc_t)(128 >> 4) << 32), kO = (desc_t)(aO | (P16 << 16)) | ((desc_t)(128 >> 4) << 32);
  const desc_t vE = (desc_t)(aE | ((128 >> 4) << 16)) | ((desc_t)P16 << 32), vO = (desc_t)(aO | ((128 >> 4) << 16)) | ((desc_t)P16 << 32);
  uint32_t a[4], a8[2];
  float sX[32], sY[32], o[12];
  uint32_t pA[16], pB[16];
  mbar_wait(bars + 8 * B_HALO, 0);
  ldsm4(a[0], a[1], a[2], a[3], rowQ);
  ldsm2(a8[0], a8[1], rowQ8);
  if (t >= 2) { a8[0] = 0u; a8[1] = 0u; }
  wg_fence();
  mma_qk(sX, a, a8, kE, kE + 2 * P16);
  mma_qk(sY, a, a8, kE + 2 * S16, kE + 2 * S16 + 2 * P16);
  wg_commit();
#pragma unroll 1
  for (int h = 0; h < 4; ++h) {
    const int p = h >> 1, odd = h & 1;
    const uint32_t km = (p * 33 + odd * 3) * P16, kt = (p * 33 + 2) * P16, vp = (p * 33 + 5 + odd * 3) * P16;
    SoftmaxState st;
    ATT_T(0);
    wg_wait<0>();
    reg_fence(sX); reg_fence(sY);
    ATT_T(1);
    if (cmin > 0) {
#pragma unroll
      for (int i = 0; i < 32; ++i) sX[i] = NEG_INF;
    }
#pragma unroll
    for (int b = 0; b < 4; ++b) {
      const uint32_t gt = b > w ? 0xFFFFFFFFu : 0u, ge = b >= w ? 0xFFFFFFFFu : 0u, eq = ge & ~gt;
      const uint32_t e0 = gt | (eq & T0), e1 = gt | (eq & T1);
      sX[8 * b + 0] = fsel(sX[8 * b + 0], sY[8 * b + 0], e0);
      sX[8 * b + 1] = fsel(sX[8 * b + 1], sY[8 * b + 1], e1);
      sX[8 * b + 2] = fsel(sX[8 * b + 2], sY[8 * b + 2], gt);
      sX[8 * b + 3] = fsel(sX[8 * b + 3], sY[8 * b + 3], gt);
      sX[8 * b + 4] = fsel(sX[8 * b + 4], sY[8 * b + 4], ge);
      sX[8 * b + 5] = fsel(sX[8 * b + 5], sY[8 * b + 5], ge);
      sX[8 * b + 6] = fsel(sX[8 * b + 6], sY[8 * b + 6], e0);
      sX[8 * b + 7] = fsel(sX[8 * b + 7], sY[8 * b + 7], e1);
    }
    wg_fence();
    mma_qk(sY, a, a8, kO + km, kO + kt);
    wg_commit();
    ATT_T(2);
    row_max_f(sX, st.m0, st.m1);
    st.n0 = -st.m0 * SM_C; st.n1 = -st.m1 * SM_C;
    ATT_T(3);
    step<false, ATT_SPLIT>(sX, sY, o, pA, st, wg + 1 >= cmin);
    ATT_T(4);
#pragma unroll
    for (int b = 0; b < 4; ++b) {
      const uint32_t gt = b > w ? 0xFFFFFFFFu : 0u, ge = b >= w ? 0xFFFFFFFFu : 0u, eq = ge & ~gt;
      const uint32_t mt = gt | (eq & tri);
      pB[4 * b + 0] = pA[4 * b + 0] & ~mt; pA[4 * b + 0] &= mt;
      pB[4 * b + 1] = pA[4 * b + 1] & ~gt; pA[4 * b + 1] &= gt;
      pB[4 * b + 2] = pA[4 * b + 2] & ~ge; pA[4 * b + 2] &= ge;
      pB[4 * b + 3] = pA[4 * b + 3] & ~mt; pA[4 * b + 3] &= mt;
    }
    wg_fence();
    mma_qk(sX, a, a8, kE + S16 + km, kE + S16 + kt);
    wg_commit();
    mma_pv<true>(o, pA, vE + vp);
    mma_pv<false>(o, pB, vE + 2 * S16 + vp);
    wg_commit();
    ATT_T(5);
    step<true, ATT_SPLIT>(sY, sX, o, pB, st, wg + 2 >= cmin);
    ATT_T(6);
    wg_fence();
    mma_qk(sY, a, a8, kO + S16 + km, kO + S16 + kt);
    wg_commit();
    mma_pv<false>(o, pB, vO + vp);
    wg_commit();
    ATT_T(7);
    step<true, ATT_SPLIT>(sX, sY, o, pA, st, wg + 3 >= cmin);
    ATT_T(8);
    const int hn = h < 3 ? h + 1 : h, pn = hn >> 1, on = hn & 1;
    const uint32_t kmn = (pn * 33 + on * 3) * P16, ktn = (pn * 33 + 2) * P16;
    if (h == 1) mbar_wait(bars + 8 * (B_HALO + 1), 0);
    ldsm4(a[0], a[1], a[2], a[3], rowQ + (pn * 5 + on * 3) * PLANE);
    ldsm2(a8[0], a8[1], rowQ8 + pn * 5 * PLANE);
    if ((t >= 2) != (on != 0)) { a8[0] = 0u; a8[1] = 0u; }
    wg_fence();
    mma_pv<false>(o, pA, vE + S16 + vp);
    mma_qk(sX, a, a8, kE + kmn, kE + ktn);
    wg_commit();
    ATT_T(9);
    sm_exp<0, 8>(sY, pB, st.n0, st.n1);
    ATT_T(10);
    wg_wait<0>();
    reg_fence(o); reg_fence(sX);
    rescale(o, st.al0, st.al1);
    wg_fence();
    mma_pv<false>(o, pB, vO + S16 + vp);
    wg_commit();
    wg_fence();
    mma_qk(sY, a, a8, kE + 2 * S16 + kmn, kE + 2 * S16 + ktn);
    wg_commit();
    ATT_T(11);
    wg_wait<1>();
    reg_fence(o);
    const int src = (lane & ~3) | (odd ? 0 : 2);
    const float i0 = __fdividef(1.f, __shfl_sync(0xffffffffu, o[8], src)), i1 = __fdividef(1.f, __shfl_sync(0xffffffffu, o[10], src));
    const uint32_t ob = stg + p * 5 * PLANE + (16 * wq + g) * 16 + t * 4;
    const uint32_t om = ob + odd * 3 * PLANE;
    sts32(om, pack_bf16(o[0] * i0, o[1] * i0)); sts32(om + 128, pack_bf16(o[2] * i1, o[3] * i1));
    sts32(om + PLANE, pack_bf16(o[4] * i0, o[5] * i0)); sts32(om + PLANE + 128, pack_bf16(o[6] * i1, o[7] * i1));
    if ((t >= 2) == (odd != 0)) { sts32(ob + 2 * PLANE, pack_bf16(o[8] * i0, o[9] * i0)); sts32(ob + 2 * PLANE + 128, pack_bf16(o[10] * i1, o[11] * i1)); }
    if (odd) {
      fence_async_smem();
      __syncwarp();
      if (lane == 0) mbar_arrive(bars + 8 * (B_OST + p));
      if (lane < 4) mbar_arrive_cta(bars + 8 * (B_EMPTY2 + 2 * p + (lane >> 1)), lane & 1);
    }
    ATT_T(12);
  }
  wg_wait<0>();
  reg_fence(sX); reg_fence(sY);
  __syncwarp();
}

#define NO_G 1
#define CONV_DUP 0
#define CONV_YIELD 50
#define FPF_AT 6
#define KT_GATE 0
#define XWPF 0
#define OPUB_GATE 0
#define KT_IN_F 0
#define EXP_NOLD 0
#define PF_MODE 2
#define KVPF_AT 3
#define PRE_LDG 0
#define PRE_AFTER 2
#define PRE_WAIT 1
struct Params {
  const uint16_t* q; const uint16_t* k; const uint16_t* v; const uint16_t* shift_k; const uint16_t* ssm_k;
  const uint16_t* ssm_D; const uint16_t* x; const uint16_t* wqkv; const uint16_t* wo; uint16_t* out;
};

DEVINL unsigned* cnt(int i) { return &g_cnt[i * CS]; }

DEVINL void finish_role() {
  unsigned old = atomicAdd(cnt(C_DONE), 1u);
  if (old == 255u) {
    __threadfence();
    for (int i = 0; i < C_NUM; ++i) *cnt(i) = 0u;
    __threadfence();
  }
}

DEVINL void conv_channel(uint32_t sb, int cl, int wc, int lane, uint32_t D2, int bar_id) {
  const int mi = lane >> 3, r = lane & 7, g = lane >> 2, t = lane & 3;
  const int h = wc >> 1, rr = wc & 1;
  const uint32_t Ub = cl < 4 ? sb + OFF_U + cl * CH_U : sb + OFF_U4, Fb = sb + OFF_F + cl * CH_F;
  const uint32_t fw = ((g & 1) ? Fb + 4160 + 2 * (33 - g + 2 * t) : Fb + 2 * (32 - g + 2 * t)) + 1024 * h - 32 * rr;
  const uint64_t ub = (uint64_t)((((Ub & 0x3FFFF) >> 4) + 16) | ((UPL >> 4) << 16)) | ((uint64_t)(128 >> 4) << 32);
  uint64_t bcur = ub;
  float d[32], d2[16];
#pragma unroll
  for (int i = 0; i < 32; ++i) d[i] = 0.f;
#pragma unroll
  for (int i = 0; i < 16; ++i) d2[i] = 0.f;
#pragma unroll 1
  for (int rq = 0; rq < 4; ++rq) {
#pragma unroll
    for (int bt = 0; bt < 2; ++bt) {
      const int rho = 4 * rq + 2 * bt;
      const uint32_t fb = fw + 64 * rho;
      uint32_t x[2][2][2][4];
      wg_wait<1>();
#pragma unroll
      for (int e = 0; e < 2; ++e)
#pragma unroll
        for (int nu = 0; nu < 2; ++nu) {
          const uint32_t a = fb + 64 * e + 2048 * nu;
          x[e][nu][0][0] = lds32(a); x[e][nu][0][1] = lds32(a - 16); x[e][nu][0][2] = lds32(a + 16); x[e][nu][0][3] = x[e][nu][0][0];
          x[e][nu][1][0] = lds32(a + 32); x[e][nu][1][1] = x[e][nu][0][2]; x[e][nu][1][2] = lds32(a + 48); x[e][nu][1][3] = x[e][nu][1][0];
        }
      wg_fence();
#pragma unroll
      for (int e = 0; e < 2; ++e) {
        const uint64_t b0 = bcur - e, b1 = b0 + 2 * (UPL >> 4);
        wgmma_cv_n64(d, x[e][0][0][0], x[e][0][0][1], x[e][0][0][2], x[e][0][0][3], b0);
        wgmma_cv_n64(d, x[e][0][1][0], x[e][0][1][1], x[e][0][1][2], x[e][0][1][3], b1);
        wgmma_cv_n32(d2, x[e][1][0][0], x[e][1][0][1], x[e][1][0][2], x[e][1][0][3], b0);
        wgmma_cv_n32(d2, x[e][1][1][0], x[e][1][1][1], x[e][1][1][2], x[e][1][1][3], b1);
      }
      wg_commit();
      bcur -= 2;
      __nanosleep(CONV_YIELD);
    }
  }
  wg_wait<0>();
  reg_fence(d); reg_fence(d2);
#pragma unroll
  for (int i = 0; i < 16; ++i) d[16 + i] += d2[i];
  named_sync(bar_id, 128);
  const uint32_t xb = Fb + wc * 2048 + lane * 16;
#pragma unroll
  for (int j = 0; j < 4; ++j) {
    const float4 v = h == 0 ? make_float4(d[16 + 4 * j], d[17 + 4 * j], d[18 + 4 * j], d[19 + 4 * j])
                            : make_float4(d[4 * j], d[1 + 4 * j], d[2 + 4 * j], d[3 + 4 * j]);
    sts128(xb + j * 512, make_uint4(__float_as_uint(v.x), __float_as_uint(v.y), __float_as_uint(v.z), __float_as_uint(v.w)));
  }
  named_sync(bar_id, 128);
  const uint32_t xr = Fb + (wc ^ 2) * 2048 + lane * 16;
  float f[4][4];
#pragma unroll
  for (int j = 0; j < 4; ++j) {
    const uint4 ov = lds128(xr + (h == 0 ? (j >= 2 ? j - 2 : 0) : j) * 512);
    const float z = (h == 0 && j < 2) ? 0.f : 1.f;
    f[j][0] = (h == 0 ? d[4 * j] : d[8 + 4 * j]) + z * __uint_as_float(ov.x);
    f[j][1] = (h == 0 ? d[4 * j + 1] : d[9 + 4 * j]) + z * __uint_as_float(ov.y);
    f[j][2] = (h == 0 ? d[4 * j + 2] : d[10 + 4 * j]) + z * __uint_as_float(ov.z);
    f[j][3] = (h == 0 ? d[4 * j + 3] : d[11 + 4 * j]) + z * __uint_as_float(ov.w);
  }
  uint32_t res[2][4];
#pragma unroll
  for (int jj = 0; jj < 2; ++jj) {
    const int tile = 4 * h + 2 * jj + (mi >> 1);
    uint32_t u0, u1, u2, u3;
    ldsm4t(u0, u1, u2, u3, Ub + (2 * rr + (mi & 1)) * UPL + (16 + 8 * tile + r) * 16);
    res[jj][0] = hadd2(pack_bf16(f[2 * jj][0], f[2 * jj][1]), hmul2(u0, D2));
    res[jj][1] = hadd2(pack_bf16(f[2 * jj][2], f[2 * jj][3]), hmul2(u1, D2));
    res[jj][2] = hadd2(pack_bf16(f[2 * jj + 1][0], f[2 * jj + 1][1]), hmul2(u2, D2));
    res[jj][3] = hadd2(pack_bf16(f[2 * jj + 1][2], f[2 * jj + 1][3]), hmul2(u3, D2));
  }
  named_sync(bar_id, 128);
#pragma unroll
  for (int jj = 0; jj < 2; ++jj) {
    const int tile = 4 * h + 2 * jj + (mi >> 1);
    stsm4t(Fb + ((8 * tile + r) * 32 + 16 * rr + 8 * (mi & 1)) * 2, res[jj][0], res[jj][1], res[jj][2], res[jj][3]);
  }
  fence_async_smem();
  __syncwarp();
  if (lane == 0) mbar_arrive(sb + OFF_BAR + 8 * (B_YST + cl));
}

__global__ void __cluster_dims__(2, 1, 1) __launch_bounds__(512, 1)
h3_swa_fused_kernel(const __grid_constant__ CUtensorMap tmX, const __grid_constant__ CUtensorMap tmW128,
                    const __grid_constant__ CUtensorMap tmW32,
                    const __grid_constant__ CUtensorMap tmOut, const __grid_constant__ CUtensorMap tmKT,
                    const __grid_constant__ CUtensorMap tmKin, const __grid_constant__ CUtensorMap tmVin,
                    const __grid_constant__ CUtensorMap tmQ, const __grid_constant__ CUtensorMap tmYT,
                    const __grid_constant__ CUtensorMap tmU4, const __grid_constant__ CUtensorMap tmU1,
                    const __grid_constant__ CUtensorMap tmXP,
                    const Params prm) {
  extern __shared__ uint8_t smem_raw[];
  const uint32_t sb = (uint32_t)__cvta_generic_to_shared(smem_raw);
  if ((sb & 1023u) != 0u) { g_err = 3; return; }
  const uint32_t bars = sb + OFF_BAR;
  const int tid = threadIdx.x, warp = tid >> 5, lane = tid & 31, wg = tid >> 7;
  const int cta = blockIdx.x;
  const uint32_t rank = cta & 1;
  const int g8 = (cta >> 1) & 7, rp = cta >> 4;
  const int rb = 2 * rp + rank;
  const int rb2 = 2 * rp + (g8 & 1);
  const int c2 = 2 * (g8 >> 1) + rank;
  const int tau = cta & 15, jt = cta >> 4;

  if (tid == 384) { prefetch_tmap(&tmX); prefetch_tmap(&tmW128); prefetch_tmap(&tmW32); }
  if (tid == 0) {
    PROF(0);
    for (int i = 0; i < NST1; ++i) { mbar_init(bars + 8 * (B_FULL1 + i), 1); mbar_init(bars + 8 * (B_EMPTY1 + i), 16); }
    mbar_init(bars + 8 * B_RINGFREE, 1);
    mbar_init(bars + 8 * B_HALO, 1); mbar_init(bars + 8 * (B_HALO + 1), 1);
    for (int i = 0; i < NST2; ++i) { mbar_init(bars + 8 * (B_FULL2 + i), 1); mbar_init(bars + 8 * (B_EMPTY2 + i), 16); }
    mbar_init(bars + 8 * B_U, 1);
    mbar_init(bars + 8 * B_KVST, 8); mbar_init(bars + 8 * B_KVST1, 8);
    mbar_init(bars + 8 * B_OST, 8); mbar_init(bars + 8 * (B_OST + 1), 8);
    mbar_init(bars + 8 * B_KTST, 4);
    for (int i = 0; i < 5; ++i) mbar_init(bars + 8 * (B_YST + i), 4);
    mbar_init(bars + 8 * B_CIN, 4);
    mbar_init(bars + 8 * B_OPUB, 1);
    mbar_init(bars + 8 * B_PRE, 1);
    mbar_init(bars + 8 * B_FRAW, 1);
    mbar_init(bars + 8 * B_QT, 1);
    mbar_init(bars + 8 * B_P0PUB, 1);
    mbar_init(bars + 8 * B_YT, 1);
    mbar_init(bars + 8 * B_U4, 1);
    mbar_init(bars + 8 * B_STGFREE, 4);
    mbar_init(bars + 8 * B_FFREE, 8);
    asm volatile("fence.mbarrier_init.release.cluster;" ::: "memory");
  }
  __syncthreads();
  asm volatile("barrier.cluster.arrive.relaxed.aligned;\nbarrier.cluster.wait.aligned;" ::: "memory");

  if (wg == 3) {
    asm volatile("setmaxnreg.dec.sync.aligned.u32 32;");
    if (warp == 12 && lane == 0) {
      PROF(15);
      for (int it = 0; it < 10; ++it) {
        const int s = it % NST1;
        if (it >= NST1) mbar_wait(bars + 8 * (B_EMPTY1 + s), ((it / NST1) - 1) & 1);
        PROF(44 + it);
        const uint32_t st = sb + s * ST1, fb = bars + 8 * (B_FULL1 + s);
        mbar_expect(fb, ST1);
        tma2d(st, &tmX, it * 64, rb * 128, fb);
        tma3d_mc(st + ST1_B128 + rank * 12288, &tmW128, g8 * 80, it * 64 + rank * 32, 0, fb);
        tma3d_mc(st + ST1_B32 + rank * 3072, &tmW32, g8 * 80 + 64, it * 64 + rank * 32, 0, fb);
        if (it == PRE_AFTER) {
          mbar_expect(bars + 8 * B_PRE, 131 * 160 + 128 * 160);
          tma2d(sb + OFF_U, &tmKin, jt * 80, tau * 128 - 3, bars + 8 * B_PRE);
          tma2d(sb + OFF_STG, &tmVin, jt * 80, tau * 128, bars + 8 * B_PRE);
        }
        if (it == FPF_AT) prefetch_l2(prm.ssm_k + (size_t)cta * 5 * SEQ, 5 * SEQ * 2);
      }
      PROF(1);
      mbar_wait(bars + 8 * B_RINGFREE, 0);
      for (int p = 0; p < 2; ++p) {
        const uint32_t hb = bars + 8 * (B_HALO + p);
        if (rb == 0) { mbar_arrive(hb); continue; }
        poll_ge(cnt(C_KV + (g8 * 16 + rb - 1) * 2 + p), 1);
        if (rb >= 2) poll_ge(cnt(C_KV + (g8 * 16 + rb - 2) * 2 + p), 1);
        if (p == 0) PROF(2);
        mbar_expect(hb, (rb >= 2 ? 2 : 1) * PAIR);
        bulk_load(sb + p * PWIN + PAIR, g_kv + (size_t)(g8 * 16 + rb - 1) * (SEG / 2) + p * (PAIR / 2), PAIR, hb);
        if (rb >= 2) bulk_load(sb + p * PWIN, g_kv + (size_t)(g8 * 16 + rb - 2) * (SEG / 2) + p * (PAIR / 2), PAIR, hb);
      }
      poll_ge(cnt(C_WO + c2), 16);
#pragma unroll 1
      for (int it = 0; it < 8; ++it) {
        const int s = it & 3, p = it >> 2;
        mbar_wait(bars + 8 * (B_EMPTY2 + s), p);
        const uint32_t fb = bars + 8 * (B_FULL2 + s);
        mbar_expect(fb, ST2);
        if (it == 0) { PROF(3); poll_ge(cnt(C_O + rb2 * 2), 8); }
        if (p == 0) bulk_load_mc(sb + s * ST2 + rank * 10240, g_o + (size_t)(rb2 * 80 + (2 * s + rank) * 5) * 1024, 10240, fb);
        bulk_load(sb + s * ST2 + 20480, g_woP + (size_t)(c2 * 8 + it) * 6400, 12800, fb);
      }
      poll_ge(cnt(C_O + rb2 * 2 + 1), 8);
      PROF(4);
#pragma unroll 1
      for (int s = 0; s < 4; ++s)
        bulk_load_mc(sb + s * ST2 + rank * 10240, g_o + (size_t)(rb2 * 80 + 40 + (2 * s + rank) * 5) * 1024, 10240, bars + 8 * (B_FULL2 + s));
      finish_role();
    } else if (warp == 13 && lane == 0) {
      prefetch_tmap(&tmOut);
      mbar_wait(bars + 8 * B_FFREE, 0);
      mbar_expect(bars + 8 * B_FRAW, 5 * 4096);
      for (int c = 0; c < 5; ++c) bulk_load(sb + OFF_F + c * CH_F + 64, prm.ssm_k + (size_t)(cta * 5 + c) * SEQ, 4096, bars + 8 * B_FRAW);
      mbar_wait(bars + 8 * B_KVST, 0);
      uint16_t* kd = g_kv + (size_t)(g8 * 16 + rb) * (SEG / 2);
      bulk_store(kd, sb + 2 * PAIR, PAIR); bulk_commit();
      bulk_wait<0>(); red_publish(cnt(C_KV + (g8 * 16 + rb) * 2));
      mbar_arrive(bars + 8 * B_P0PUB);
      PROF(55);
      mbar_wait(bars + 8 * B_KVST1, 0);
      bulk_store(kd + PAIR / 2, sb + PWIN + 2 * PAIR, PAIR); bulk_commit();
      bulk_wait<0>(); red_publish(cnt(C_KV + (g8 * 16 + rb) * 2 + 1));
      PROF(24);
      for (int p = 0; p < 2; ++p) {
        mbar_wait(bars + 8 * (B_OST + p), 0);
        if (p == 1) PROF(31);
        bulk_store(g_o + (size_t)(rb * 80 + p * 40 + g8 * 5) * 1024, sb + OFF_STG + p * 10240, 10240);
        bulk_commit(); bulk_wait<0>();
        if (p == 1) PROF(54);
        red_publish(cnt(C_O + rb * 2 + p));
      }
      mbar_arrive(bars + 8 * B_OPUB);
      PROF(20);
    } else if (warp == 15) {
      const int run = rp * 2 + (g8 & 1);
      const int gg = run >> 1, pp = run & 1;
      mbar_wait(bars + 8 * (B_FULL1 + 3), 0);
#pragma unroll 1
      for (int i0 = 0; i0 < 13; i0 += 4) {
        uint4 v[4];
#pragma unroll
        for (int i = 0; i < 4; ++i) {
          const int idx = lane + 32 * (i0 + i), j = idx / 10, n8 = idx % 10;
          if (idx < 400) v[i] = ldg_nc(prm.wo + (size_t)(gg * 80 + pp * 40 + j) * DM + c2 * 80 + n8 * 8);
        }
#pragma unroll
        for (int i = 0; i < 4; ++i) {
          const int idx = lane + 32 * (i0 + i), j = idx / 10, n8 = idx % 10;
          if (idx < 400) stg128(g_woP + (size_t)((c2 * 8 + pp * 4 + (gg >> 1)) * 10 + n8) * 640 + ((gg & 1) * 40 + j) * 8, v[i]);
        }
      }
      asm volatile("fence.acq_rel.gpu;" ::: "memory");
      __syncwarp();
      if (lane == 0) asm volatile("red.relaxed.gpu.global.add.u32 [%0], 1;" ::"l"(cnt(C_WO + c2)) : "memory");
    } else if (warp == 14 && lane == 0) {
      prefetch_tmap(&tmKT); prefetch_tmap(&tmU4); prefetch_tmap(&tmU1);
      mbar_wait(bars + 8 * B_KTST, 0);
      tma3d_store(&tmKT, 0, tau, jt * 80, sb + OFF_U);
      bulk_commit();
      bulk_wait<0>();
      red_publish(cnt(C_PRE + jt));
      PROF(8);
      poll_ge(cnt(C_PRE + jt), 16);
      mbar_expect(bars + 8 * B_U, 4 * CH_U);
      tma4d(sb + OFF_U, &tmU4, 0, -4, 0, cta * 5, bars + 8 * B_U);
      mbar_wait(bars + 8 * B_FFREE, 0);
      mbar_expect(bars + 8 * B_U4, CH_U);
      tma4d(sb + OFF_U4, &tmU1, 0, -4, 0, cta * 5 + 4, bars + 8 * B_U4);
      PROF(9);
      for (int c = 0; c < 5; ++c) {
        mbar_wait(bars + 8 * (B_YST + c), 0);
        bulk_store(g_yT + (size_t)(cta * 5 + c) * SEQ, sb + OFF_F + c * CH_F, 4096);
        bulk_commit();
      }
      prefetch_tmap(&tmQ); prefetch_tmap(&tmYT);
      mbar_expect(bars + 8 * B_QT, 128 * 160);
      tma2d(sb + OFF_U, &tmQ, jt * 80, tau * 128, bars + 8 * B_QT);
      bulk_wait<0>();
      red_publish(cnt(C_Y + jt), 5);
      PROF(11);
      poll_ge(cnt(C_Y + jt), 80);
      PROF(12);
      mbar_expect(bars + 8 * B_YT, 80 * 256);
      tma2d(sb + OFF_F, &tmYT, tau * 128, jt * 80, bars + 8 * B_YT);
      tma2d(sb + OFF_F + 10240, &tmYT, tau * 128 + 64, jt * 80, bars + 8 * B_YT);
      finish_role();
    }
  } else if (wg == 2) {
    asm volatile("setmaxnreg.inc.sync.aligned.u32 144;");
    const int ct = tid - 256, wc = __shfl_sync(0xffffffffu, warp, 0) - 8;
    const int t0 = tau * 128, c0 = jt * 80;
    const int mi = lane >> 3, r = lane & 7, g = lane >> 2, t = lane & 3;
    const uint32_t U = sb + OFF_U, F = sb + OFF_F;
    if (ct == 0) PROF(14);
    uint32_t dpack = lane < 5 ? (uint32_t)__ldg(prm.ssm_D + cta * 5 + lane) : 0u;
    dpack |= dpack << 16;
    {
      const int c = ct % 10, seg = ct / 10;
      uint4 wv[4];
#pragma unroll
      for (int u = 0; u < 4; ++u) wv[u] = ldg_nc(prm.shift_k + (size_t)(c0 + c * 8 + 2 * u) * 4);
      uint32_t W[4][4];
#pragma unroll
      for (int u = 0; u < 4; ++u) {
        W[0][u] = __byte_perm(wv[u].x, wv[u].z, 0x5410); W[1][u] = __byte_perm(wv[u].x, wv[u].z, 0x7632);
        W[2][u] = __byte_perm(wv[u].y, wv[u].w, 0x5410); W[3][u] = __byte_perm(wv[u].y, wv[u].w, 0x7632);
      }
      mbar_wait(bars + 8 * B_PRE, 0);
      if (ct == 0) PROF(5);
      if (ct < 120) {
        const int nrow = seg == 11 ? 7 : 11;
        const uint32_t ka = U + seg * 11 * 160 + c * 16, va = sb + OFF_STG + seg * 11 * 160 + c * 16;
        uint4 kk[14], vv[11];
#pragma unroll
        for (int i = 0; i < 14; ++i) kk[i] = i < nrow + 3 ? lds128(ka + i * 160) : make_uint4(0, 0, 0, 0);
#pragma unroll
        for (int i = 0; i < 11; ++i) vv[i] = i < nrow ? lds128(va + i * 160) : make_uint4(0, 0, 0, 0);
#pragma unroll
        for (int i = 0; i < 11; ++i) {
          uint32_t res[4];
#pragma unroll
          for (int u = 0; u < 4; ++u) {
            uint32_t acc = hmul2((&kk[i].x)[u], W[3][u]);
            acc = hfma2((&kk[i + 1].x)[u], W[2][u], acc);
            acc = hfma2((&kk[i + 2].x)[u], W[1][u], acc);
            acc = hfma2((&kk[i + 3].x)[u], W[0][u], acc);
            res[u] = hmul2(acc, (&vv[i].x)[u]);
          }
          if (i < nrow) sts128(va + i * 160, make_uint4(res[0], res[1], res[2], res[3]));
        }
      }
    }
    if (ct == 0) PROF(6);
    named_sync(3, 128);
    {
      uint4 v4[10];
#pragma unroll
      for (int k = 0; k < 10; ++k) {
        const int it = wc + 4 * k, c = it % 10, q = it / 10;
        const int tl = 32 * (r >> 1) + 31 - (8 * q + 2 * mi + (r & 1));
        ldsm4t(v4[k].x, v4[k].y, v4[k].z, v4[k].w, sb + OFF_STG + tl * 160 + c * 16);
      }
#pragma unroll
      for (int k = 0; k < 10; ++k) {
        const int it = wc + 4 * k, c = it % 10, q = it / 10;
        sts128(U + (c * 8 + g) * 256 + q * 64 + t * 16, v4[k]);
      }
    }
    fence_async_smem();
    __syncwarp();
    if (lane == 0) { mbar_arrive(bars + 8 * B_KTST); mbar_arrive(bars + 8 * B_STGFREE); }
    if (ct == 0) PROF(7);
    if (ct < 32) prefetch_line(prm.q + ((size_t)cta * 160 + 128 + ct) * 64);
    prefetch_line(prm.q + ((size_t)cta * 160 + ct) * 64);
    mbar_wait(bars + 8 * B_FRAW, 0);
    {
      uint4 fv[10]; uint32_t pv[10];
#pragma unroll
      for (int i = 0; i < 10; ++i) {
        const int cl = i >> 1, qq = ct + (i & 1) * 128;
        const uint32_t a = F + cl * CH_F + 64 + qq * 16;
        fv[i] = lds128(a);
        pv[i] = qq > 0 ? lds32(a - 4) >> 16 : 0u;
      }
#pragma unroll
      for (int i = 0; i < 10; ++i) {
        const int cl = i >> 1, qq = ct + (i & 1) * 128;
        sts128(F + cl * CH_F + 64 + qq * 16 + 4160,
               make_uint4(__byte_perm(pv[i], fv[i].x, 0x5410), __byte_perm(fv[i].x, fv[i].y, 0x5432),
                          __byte_perm(fv[i].y, fv[i].z, 0x5432), __byte_perm(fv[i].z, fv[i].w, 0x5432)));
      }
      if (ct < 40) sts128(F + (ct >> 3) * CH_F + ((ct >> 2) & 1) * 4160 + (ct & 3) * 16, make_uint4(0, 0, 0, 0));
    }
    mbar_wait(bars + 8 * B_U, 0);
    named_sync(3, 128);
    if (ct == 0) PROF(10);
    if (lane == 0) mbar_arrive(bars + 8 * B_CIN);
    constexpr int NOWN = 5;
#pragma unroll 1
    for (int i = 0; i < NOWN; ++i) {
      const int cl = NOWN == 5 ? i : (i == 0 ? 0 : i + 2);
      if (cl == 4) mbar_wait(bars + 8 * B_U4, 0);
      conv_channel(sb, cl, wc, lane, __shfl_sync(0xffffffffu, dpack, cl), 3);
      if (ct == 0 && i == 0) PROF(27);
    }
    if (ct == 0) PROF(30);
    const uint32_t YT = sb + OFF_F, YN = sb + OFF_F + 20480;
    mbar_wait(bars + 8 * B_YT, 0);
    {
      int w2 = wc, l2 = lane;
      asm volatile("" : "+r"(w2), "+r"(l2));
      const int r2 = l2 & 7, m2 = l2 >> 3;
      uint4 x[10];
#pragma unroll
      for (int k = 0; k < 10; ++k) {
        const int it = w2 + 4 * k, c = it % 10, tq = it / 10, ch = 8 * c + r2, j = 4 * tq + m2;
        ldsm4t(x[k].x, x[k].y, x[k].z, x[k].w, YT + (j >> 3) * 10240 + ch * 128 + (((j & 7) ^ (ch & 7)) << 4));
      }
#pragma unroll
      for (int k = 0; k < 10; ++k) {
        const int it = w2 + 4 * k, c = it % 10, tq = it / 10;
        const int s = (8 * (4 * tq + m2) + r2) ^ 31;
        stsm4(YN + s * 176 + c * 16, x[k].x, x[k].y, x[k].z, x[k].w);
      }
    }
    mbar_wait(bars + 8 * B_QT, 0);
    named_sync(3, 128);
#pragma unroll
    for (int i = 0; i < 10; ++i) {
      const int idx = ct + 128 * i, row = idx / 10, c = idx % 10;
      const uint4 y = lds128(YN + row * 176 + c * 16), q = lds128(U + row * 160 + c * 16);
      stg128(prm.out + (size_t)(t0 + row) * (2 * DM) + c0 + c * 8,
             make_uint4(hmul2(q.x, y.x), hmul2(q.y, y.y), hmul2(q.z, y.z), hmul2(q.w, y.w)));
    }
    if (ct == 0) PROF(13);
  } else {
    asm volatile("setmaxnreg.inc.sync.aligned.u32 168;");
    const int wq = __shfl_sync(0xffffffffu, warp, 0);
    const int mi = lane >> 3, r = lane & 7;
    const uint32_t stg = sb + OFF_STG;
    {
      float acc1[96], acc2[24];
#pragma unroll 1
      for (int it = 0; it < 10; ++it) {
        const int s = it % NST1;
        mbar_wait(bars + 8 * (B_FULL1 + s), (it / NST1) & 1);
        if (tid == 0) PROF(32 + it);
        const uint32_t st = sb + s * ST1;
        wg_fence();
#pragma unroll
        for (int kk = 0; kk < 4; ++kk) {
          const uint64_t da = make_desc(st + wg * 8192 + kk * 32, 16, 1024, 1);
          const uint64_t db1 = make_desc(st + ST1_B128 + (kk >> 1) * 12288 + (kk & 1) * 2048, 4096, 1024, 1);
          const uint64_t db2 = make_desc(st + ST1_B32 + (kk >> 1) * 3072 + (kk & 1) * 512, 1024, 256, 3);
          wgmma_n192(acc1, da, db1, (it | kk) != 0);
          wgmma_n48(acc2, da, db2, (it | kk) != 0);
        }
        wg_commit();
        wg_wait<0>();
        if (it + NST1 < 10 && lane < 2) mbar_arrive_cta(bars + 8 * (B_EMPTY1 + s), lane);
        if (it == 7 && lane == 0) mbar_arrive(bars + 8 * B_FFREE);
      }
      reg_fence(acc1); reg_fence(acc2);
      if (tid == 0) PROF(17);
      named_sync(1, 256);
      if (tid == 0) mbar_arrive(bars + 8 * B_RINGFREE);
      const uint32_t rowo = (16 * wq + 8 * (mi & 1) + r) * 16;
      const int t4 = lane & 3;
#pragma unroll
      for (int pr = 0; pr < 2; ++pr) {
#pragma unroll
        for (int kv = 0; kv < 2; ++kv) {
          uint32_t w[5][2];
#pragma unroll
          for (int c = 0; c < 5; ++c) {
            const int tile = 5 * pr + c;
            if (tile < 8) {
              const int o = 32 * (kv + 1) + 4 * tile;
              w[c][0] = pack_bf16(acc1[o], acc1[o + 1]); w[c][1] = pack_bf16(acc1[o + 2], acc1[o + 3]);
            } else {
              const int o = 8 * (kv + 1) + 4 * (tile - 8);
              w[c][0] = pack_bf16(acc2[o], acc2[o + 1]); w[c][1] = pack_bf16(acc2[o + 2], acc2[o + 3]);
            }
          }
          const uint32_t base = sb + pr * PWIN + 2 * PAIR + (kv ? 5 * PLANE : 0);
          if (kv == 0) {
            stsm4(base + rowo + (mi >> 1) * PLANE, w[0][0], w[0][1], w[1][0], w[1][1]);
            stsm4(base + rowo + (2 + (mi >> 1)) * PLANE, w[2][0], w[2][1], w[3][0], w[3][1]);
            stsm2(base + 4 * PLANE + (16 * wq + (lane & 15)) * 16, w[4][0], w[4][1]);
          } else {
            const uint32_t oneE = t4 == 2 ? 0x00003F80u : 0u, oneO = t4 == 0 ? 0x00003F80u : 0u;
            stsm4(base + rowo + (mi >> 1) * PLANE, w[0][0], w[0][1], w[1][0], w[1][1]);
            stsm4(base + rowo + (2 + (mi >> 1)) * PLANE, t4 < 2 ? w[2][0] : oneE, t4 < 2 ? w[2][1] : oneE, w[3][0], w[3][1]);
            stsm4(base + rowo + (4 + (mi >> 1)) * PLANE, w[4][0], w[4][1], t4 >= 2 ? w[2][0] : oneO, t4 >= 2 ? w[2][1] : oneO);
          }
        }
        fence_async_smem();
        __syncwarp();
        if (lane == 0) mbar_arrive(bars + 8 * (pr ? B_KVST1 : B_KVST));
      }
      mbar_wait(bars + 8 * B_STGFREE, 0);
      const uint32_t rq = stg + rowo + (mi >> 1) * PLANE;
#pragma unroll
      for (int tp = 0; tp < 4; ++tp)
        stsm4(rq + tp * 2 * PLANE, pack_bf16(acc1[8 * tp], acc1[8 * tp + 1]), pack_bf16(acc1[8 * tp + 2], acc1[8 * tp + 3]),
              pack_bf16(acc1[8 * tp + 4], acc1[8 * tp + 5]), pack_bf16(acc1[8 * tp + 6], acc1[8 * tp + 7]));
      stsm4(rq + 8 * PLANE, pack_bf16(acc2[0], acc2[1]), pack_bf16(acc2[2], acc2[3]), pack_bf16(acc2[4], acc2[5]), pack_bf16(acc2[6], acc2[7]));
    }
    if (rb < 2) {
      const int nz = (2 - rb) * (PAIR / 16);
#pragma unroll 1
      for (int i = tid; i < 2 * nz; i += 256) sts128(sb + (i >= nz ? PWIN + (i - nz) * 16 : i * 16), make_uint4(0, 0, 0, 0));
      fence_async_smem();
    }
    named_sync(2, 256);
    if (tid == 0) PROF(18);
    attn_all(sb, stg, bars, wq, lane, rb >= 2 ? 0 : 4 - 2 * rb);
    if (tid == 0) PROF(19);
    float acc[40];
#pragma unroll 1
    for (int it = 0; it < 8; ++it) {
      const int s = it & 3;
      mbar_wait(bars + 8 * (B_FULL2 + s), it >> 2);
      if (it == 0 && tid == 0) PROF(21);
      if (it == 4 && tid == 0) PROF(25);
      const uint32_t st = sb + s * ST2;
      wg_fence();
#pragma unroll
      for (int kk = 0; kk < 5; ++kk)
        wgmma_n80(acc, make_desc(st + wg * 1024 + kk * 2 * PLANE, PLANE, 128, 0), make_desc(st + 20480 + kk * 256, 128, 1280, 0), (it | kk) != 0);
      wg_commit();
      wg_wait<0>();
      if (it < 4 && lane < 2) mbar_arrive_cta(bars + 8 * (B_EMPTY2 + s), lane);
    }
    reg_fence(acc);
    if (tid == 0) PROF(22);
    mbar_wait(bars + 8 * B_OPUB, 0);
    {
      const uint32_t rowa = stg + (16 * wq + 8 * (mi & 1) + r) * 160 + (mi >> 1) * 16;
#pragma unroll
      for (int tp = 0; tp < 5; ++tp)
        stsm4(rowa + tp * 32, pack_bf16(acc[8 * tp], acc[8 * tp + 1]), pack_bf16(acc[8 * tp + 2], acc[8 * tp + 3]),
              pack_bf16(acc[8 * tp + 4], acc[8 * tp + 5]), pack_bf16(acc[8 * tp + 6], acc[8 * tp + 7]));
      fence_async_smem();
      __syncwarp();
      if (lane == 0) {
        tma2d_store(&tmOut, DM + c2 * 80, rb2 * 128 + 16 * wq, stg + wq * 2560);
        bulk_commit();
        bulk_wait0_read();
      }
    }
    if (tid == 0) PROF(23);
  }
}

typedef CUresult (*EncodeFn)(CUtensorMap*, CUtensorMapDataType, cuuint32_t, void*, const cuuint64_t*, const cuuint64_t*,
                             const cuuint32_t*, const cuuint32_t*, CUtensorMapInterleave, CUtensorMapSwizzle,
                             CUtensorMapL2promotion, CUtensorMapFloatOOBfill);

CUtensorMap make_map(EncodeFn enc, const void* p, int rank, const cuuint64_t* dims, const cuuint64_t* strides,
                     const cuuint32_t* box, CUtensorMapSwizzle sw) {
  CUtensorMap m;
  const cuuint32_t es[5] = {1, 1, 1, 1, 1};
  enc(&m, CU_TENSOR_MAP_DATA_TYPE_BFLOAT16, rank, const_cast<void*>(p), dims, strides, box, es,
      CU_TENSOR_MAP_INTERLEAVE_NONE, sw, CU_TENSOR_MAP_L2_PROMOTION_L2_128B, CU_TENSOR_MAP_FLOAT_OOB_FILL_NONE);
  return m;
}

}

extern "C" void kernel_launch(void* const* d_in, const int* in_sizes, int n_in, void* d_out, int out_size) {
  (void)in_sizes; (void)n_in; (void)out_size;
  static EncodeFn enc = nullptr;
  static void* kt_ptr = nullptr;
  static void* yt_ptr = nullptr;
  if (!enc) {
    void* fn = nullptr;
    cudaDriverEntryPointQueryResult qr;
    cudaGetDriverEntryPoint("cuTensorMapEncodeTiled", &fn, cudaEnableDefault, &qr);
    enc = (EncodeFn)fn;
    cudaGetSymbolAddress(&kt_ptr, g_kvT);
    cudaGetSymbolAddress(&yt_ptr, g_yT);
    cudaFuncSetAttribute(h3_swa_fused_kernel, cudaFuncAttributeMaxDynamicSharedMemorySize, SMEM_BYTES);
  }
  const void* x = d_in[6];
  const void* wqkv = d_in[7];
  const void* wo = d_in[8];
  CUtensorMap tmX, tmW128, tmW32, tmOut, tmKT, tmKin, tmVin, tmQ, tmYT, tmU4, tmU1, tmXP;
  { cuuint64_t d[2] = {640, 2048}, s[1] = {1280}; cuuint32_t b[2] = {64, 128};
    tmX = make_map(enc, x, 2, d, s, b, CU_TENSOR_MAP_SWIZZLE_128B); }
  { cuuint64_t d[3] = {640, 640, 3}, s[2] = {3840, 1280}; cuuint32_t b[3] = {64, 32, 3};
    tmW128 = make_map(enc, wqkv, 3, d, s, b, CU_TENSOR_MAP_SWIZZLE_128B); }
  { cuuint64_t d[3] = {640, 640, 3}, s[2] = {3840, 1280}; cuuint32_t b[3] = {16, 32, 3};
    tmW32 = make_map(enc, wqkv, 3, d, s, b, CU_TENSOR_MAP_SWIZZLE_32B); }
  { cuuint64_t d[2] = {1280, 2048}, s[1] = {2560}; cuuint32_t b[2] = {80, 16};
    tmOut = make_map(enc, d_out, 2, d, s, b, CU_TENSOR_MAP_SWIZZLE_NONE); }
  { cuuint64_t d[3] = {128, 16, 640}, s[2] = {256, 4096}; cuuint32_t b[3] = {128, 1, 80};
    tmKT = make_map(enc, kt_ptr, 3, d, s, b, CU_TENSOR_MAP_SWIZZLE_NONE); }
  { cuuint64_t d[4] = {32, 16, 4, 640}, s[3] = {256, 64, 4096}; cuuint32_t b[4] = {32, 20, 4, 4};
    tmU4 = make_map(enc, kt_ptr, 4, d, s, b, CU_TENSOR_MAP_SWIZZLE_NONE); }
  { cuuint64_t d[4] = {32, 16, 4, 640}, s[3] = {256, 64, 4096}; cuuint32_t b[4] = {32, 20, 4, 1};
    tmU1 = make_map(enc, kt_ptr, 4, d, s, b, CU_TENSOR_MAP_SWIZZLE_NONE); }
  { cuuint64_t d[2] = {640, 2048}, s[1] = {1280}; cuuint32_t b[2] = {80, 131};
    tmKin = make_map(enc, d_in[1], 2, d, s, b, CU_TENSOR_MAP_SWIZZLE_NONE); }
  { cuuint64_t d[2] = {640, 2048}, s[1] = {1280}; cuuint32_t b[2] = {80, 128};
    tmVin = make_map(enc, d_in[2], 2, d, s, b, CU_TENSOR_MAP_SWIZZLE_NONE); }
  { cuuint64_t d[2] = {640, 2048}, s[1] = {1280}; cuuint32_t b[2] = {80, 128};
    tmQ = make_map(enc, d_in[0], 2, d, s, b, CU_TENSOR_MAP_SWIZZLE_NONE); }
  { cuuint64_t d[2] = {2048, 640}, s[1] = {4096}; cuuint32_t b[2] = {64, 80};
    tmYT = make_map(enc, yt_ptr, 2, d, s, b, CU_TENSOR_MAP_SWIZZLE_128B); }
  { cuuint64_t d[2] = {640, 2048}, s[1] = {1280}; cuuint32_t b[2] = {192, 16};
    tmXP = make_map(enc, x, 2, d, s, b, CU_TENSOR_MAP_SWIZZLE_NONE); }
  Params prm;
  prm.q = (const uint16_t*)d_in[0]; prm.k = (const uint16_t*)d_in[1]; prm.v = (const uint16_t*)d_in[2];
  prm.x = (const uint16_t*)x; prm.wqkv = (const uint16_t*)wqkv; prm.wo = (const uint16_t*)wo;
  prm.shift_k = (const uint16_t*)d_in[3]; prm.ssm_k = (const uint16_t*)d_in[4];
  prm.ssm_D = (const uint16_t*)d_in[5]; prm.out = (uint16_t*)d_out;
  h3_swa_fused_kernel<<<128, 512, SMEM_BYTES>>>(tmX, tmW128, tmW32, tmOut, tmKT, tmKin, tmVin, tmQ, tmYT, tmU4, tmU1, tmXP, prm);
}
```

```cpp
#include <cuda_runtime.h>
#include <cuda.h>
#include <cuda_bf16.h>
#include <stdint.h>

#define DEVINL __device__ __forceinline__

namespace {

constexpr int SEQ = 2048;
constexpr int DM = 640;

constexpr int ST1 = 47104;
constexpr int ST1_B128 = 16384;
constexpr int ST1_B32 = 40960;
constexpr int NST1 = 4;
constexpr int ST2 = 33280;
constexpr int NST2 = 4;
constexpr int CH_U = 5120;
constexpr int UPL = 1280;
constexpr int CH_F = 8320;
constexpr int OFF_F = 3 * ST1;
constexpr int OFF_U = 4 * ST1;
constexpr int OFF_KT = OFF_F + 3 * CH_F;
constexpr int OFF_U4 = OFF_F + 5 * CH_F;
constexpr int OFF_STG = OFF_U + 21120;
constexpr int OFF_BAR = OFF_STG + 20480;
constexpr int SMEM_BYTES = OFF_BAR + 512;

constexpr int B_FULL1 = 0, B_EMPTY1 = 4, B_RINGFREE = 8, B_HALO = 9, B_FULL2 = 11, B_EMPTY2 = 15, B_U = 19, B_KVST = 20,
              B_OST = 21, B_PRE = 23, B_KTST = 24, B_U4 = 25, B_STGFREE = 26, B_FFREE = 27, B_CIN = 28, B_YST = 29, B_OPUB = 34, B_FRAW = 35, B_QT = 36, B_YT = 37, B_P0PUB = 38, B_KVST1 = 39, B_HALOV = 40;

__device__ __align__(1024) uint16_t g_kv[8 * 16 * 22 * 1024];
__device__ __align__(1024) uint16_t g_o[SEQ * DM];
__device__ __align__(1024) uint16_t g_kvT[DM * SEQ];
__device__ __align__(1024) uint16_t g_yT[DM * SEQ];
__device__ __align__(1024) uint16_t g_woP[DM * DM];
constexpr int CS = 32;
constexpr int C_KV = 0, C_O = 256, C_PRE = 288, C_Y = 296, C_WO = 304, C_DONE = 312, C_NUM = 313;
__device__ unsigned g_cnt[C_NUM * CS];
__device__ unsigned g_err;
#define PROF(slot) do {} while (0)

DEVINL void mbar_init(uint32_t a, uint32_t c) { asm volatile("mbarrier.init.shared::cta.b64 [%0], %1;" ::"r"(a), "r"(c)); }
DEVINL void mbar_expect(uint32_t a, uint32_t b) {
  asm volatile("mbarrier.arrive.expect_tx.shared::cta.b64 _, [%0], %1;" ::"r"(a), "r"(b) : "memory");
}
DEVINL void mbar_arrive(uint32_t a) { asm volatile("mbarrier.arrive.shared::cta.b64 _, [%0];" ::"r"(a) : "memory"); }
DEVINL void mbar_arrive_cta(uint32_t a, uint32_t cta) {
  asm volatile("{\n.reg .b32 ra;\nmapa.shared::cluster.u32 ra, %0, %1;\nmbarrier.arrive.shared::cluster.b64 _, [ra];\n}"
               ::"r"(a), "r"(cta) : "memory");
}
DEVINL bool mbar_try(uint32_t a, uint32_t p) {
  uint32_t ok;
  asm volatile("{\n.reg .pred P;\nmbarrier.try_wait.parity.shared::cta.b64 P, [%1], %2;\nselp.u32 %0, 1, 0, P;\n}"
               : "=r"(ok) : "r"(a), "r"(p) : "memory");
  return ok;
}
DEVINL void mbar_wait(uint32_t a, uint32_t p) {
  if (mbar_try(a, p)) return;
  int n = 0;
  while (!mbar_try(a, p)) {
    if (++n > (1 << 18)) { g_err = 1; break; }
  }
}
DEVINL void poll_ge(const unsigned* p, unsigned target) {
  int n = 0;
  while (true) {
    unsigned v;
    asm volatile("ld.relaxed.gpu.global.u32 %0, [%1];" : "=r"(v) : "l"(p) : "memory");
    if (v >= target) break;
    if (++n > (1 << 20)) { g_err = 2; break; }
  }
  asm volatile("fence.acquire.gpu;\nfence.proxy.async.global;" ::: "memory");
}
DEVINL void red_publish(unsigned* p, unsigned n = 1) { asm volatile("red.release.gpu.global.add.u32 [%0], %1;" ::"l"(p), "r"(n) : "memory"); }
DEVINL void fence_async_smem() { asm volatile("fence.proxy.async.shared::cta;" ::: "memory"); }
DEVINL void named_sync(int id, int n) { asm volatile("bar.sync %0, %1;" ::"r"(id), "r"(n) : "memory"); }
DEVINL void named_arrive(int id, int n) { asm volatile("bar.arrive %0, %1;" ::"r"(id), "r"(n) : "memory"); }

DEVINL void tma2d(uint32_t dst, const CUtensorMap* m, int c0, int c1, uint32_t bar) {
  asm volatile("cp.async.bulk.tensor.2d.shared::cluster.global.mbarrier::complete_tx::bytes [%0], [%1, {%3, %4}], [%2];"
               ::"r"(dst), "l"(m), "r"(bar), "r"(c0), "r"(c1) : "memory");
}
DEVINL void tma2d_mc(uint32_t dst, const CUtensorMap* m, int c0, int c1, uint32_t bar) {
  asm volatile("cp.async.bulk.tensor.2d.shared::cluster.global.mbarrier::complete_tx::bytes.multicast::cluster [%0], [%1, {%3, %4}], [%2], %5;"
               ::"r"(dst), "l"(m), "r"(bar), "r"(c0), "r"(c1), "h"((uint16_t)3) : "memory");
}
DEVINL void tma3d(uint32_t dst, const CUtensorMap* m, int c0, int c1, int c2, uint32_t bar) {
  asm volatile("cp.async.bulk.tensor.3d.shared::cluster.global.mbarrier::complete_tx::bytes [%0], [%1, {%3, %4, %5}], [%2];"
               ::"r"(dst), "l"(m), "r"(bar), "r"(c0), "r"(c1), "r"(c2) : "memory");
}
DEVINL void tma3d_mc(uint32_t dst, const CUtensorMap* m, int c0, int c1, int c2, uint32_t bar) {
  asm volatile("cp.async.bulk.tensor.3d.shared::cluster.global.mbarrier::complete_tx::bytes.multicast::cluster [%0], [%1, {%3, %4, %5}], [%2], %6;"
               ::"r"(dst), "l"(m), "r"(bar), "r"(c0), "r"(c1), "r"(c2), "h"((uint16_t)3) : "memory");
}
DEVINL void tma2d_store(const CUtensorMap* m, int c0, int c1, uint32_t src) {
  asm volatile("cp.async.bulk.tensor.2d.global.shared::cta.bulk_group [%0, {%2, %3}], [%1];"
               ::"l"(m), "r"(src), "r"(c0), "r"(c1) : "memory");
}
DEVINL void tma3d_store(const CUtensorMap* m, int c0, int c1, int c2, uint32_t src) {
  asm volatile("cp.async.bulk.tensor.3d.global.shared::cta.bulk_group [%0, {%2, %3, %4}], [%1];"
               ::"l"(m), "r"(src), "r"(c0), "r"(c1), "r"(c2) : "memory");
}
DEVINL void bulk_load(uint32_t dst, const void* src, uint32_t bytes, uint32_t bar) {
  asm volatile("cp.async.bulk.shared::cluster.global.mbarrier::complete_tx::bytes [%0], [%1], %2, [%3];"
               ::"r"(dst), "l"(src), "r"(bytes), "r"(bar) : "memory");
}
DEVINL void bulk_load_mc(uint32_t dst, const void* src, uint32_t bytes, uint32_t bar) {
  asm volatile("cp.async.bulk.shared::cluster.global.mbarrier::complete_tx::bytes.multicast::cluster [%0], [%1], %2, [%3], %4;"
               ::"r"(dst), "l"(src), "r"(bytes), "r"(bar), "h"((uint16_t)3) : "memory");
}
DEVINL void tma4d(uint32_t dst, const CUtensorMap* m, int c0, int c1, int c2, int c3, uint32_t bar) {
  asm volatile("cp.async.bulk.tensor.4d.shared::cluster.global.mbarrier::complete_tx::bytes [%0], [%1, {%3, %4, %5, %6}], [%2];"
               ::"r"(dst), "l"(m), "r"(bar), "r"(c0), "r"(c1), "r"(c2), "r"(c3) : "memory");
}
DEVINL void tma5d(uint32_t dst, const CUtensorMap* m, int c0, int c1, int c2, int c3, int c4, uint32_t bar) {
  asm volatile("cp.async.bulk.tensor.5d.shared::cluster.global.mbarrier::complete_tx::bytes [%0], [%1, {%3, %4, %5, %6, %7}], [%2];"
               ::"r"(dst), "l"(m), "r"(bar), "r"(c0), "r"(c1), "r"(c2), "r"(c3), "r"(c4) : "memory");
}
DEVINL void prefetch_tensor2d(const CUtensorMap* m, int c0, int c1) {
  asm volatile("cp.async.bulk.prefetch.tensor.2d.L2.global.tile [%0, {%1, %2}];" ::"l"(m), "r"(c0), "r"(c1) : "memory");
}
DEVINL void prefetch_tensor3d(const CUtensorMap* m, int c0, int c1, int c2) {
  asm volatile("cp.async.bulk.prefetch.tensor.3d.L2.global.tile [%0, {%1, %2, %3}];" ::"l"(m), "r"(c0), "r"(c1), "r"(c2) : "memory");
}
DEVINL void prefetch_line(const void* p) { asm volatile("prefetch.global.L2 [%0];" ::"l"(p)); }
DEVINL void prefetch_l2(const void* p, uint32_t bytes) {
  asm volatile("cp.async.bulk.prefetch.L2.global [%0], %1;" ::"l"(p), "r"(bytes) : "memory");
}
template <int N> DEVINL void bulk_wait() { asm volatile("cp.async.bulk.wait_group %0;" ::"n"(N) : "memory"); }
DEVINL void bulk_store(void* dst, uint32_t src, uint32_t bytes) {
  asm volatile("cp.async.bulk.global.shared::cta.bulk_group [%0], [%1], %2;" ::"l"(dst), "r"(src), "r"(bytes) : "memory");
}
DEVINL void bulk_commit() { asm volatile("cp.async.bulk.commit_group;" ::: "memory"); }
DEVINL void bulk_wait0() { asm volatile("cp.async.bulk.wait_group 0;" ::: "memory"); }
DEVINL void bulk_wait0_read() { asm volatile("cp.async.bulk.wait_group.read 0;" ::: "memory"); }
DEVINL void prefetch_tmap(const CUtensorMap* m) { asm volatile("prefetch.tensormap [%0];" ::"l"(m) : "memory"); }

DEVINL uint64_t make_desc(uint32_t addr, uint32_t lbo, uint32_t sbo, uint32_t swz) {
  return (uint64_t)((addr & 0x3FFFF) >> 4) | ((uint64_t)(lbo >> 4) << 16) | ((uint64_t)(sbo >> 4) << 32) | ((uint64_t)swz << 62);
}
DEVINL void wg_fence() { asm volatile("wgmma.fence.sync.aligned;" ::: "memory"); }
DEVINL void wg_commit() { asm volatile("wgmma.commit_group.sync.aligned;" ::: "memory"); }
template <int N> DEVINL void wg_wait() { asm volatile("wgmma.wait_group.sync.aligned %0;" ::"n"(N) : "memory"); }

DEVINL void mma16816(float (&d)[4], uint32_t a0, uint32_t a1, uint32_t a2, uint32_t a3, uint32_t b0, uint32_t b1) {
  asm volatile("mma.sync.aligned.m16n8k16.row.col.f32.bf16.bf16.f32 {%0,%1,%2,%3},{%4,%5,%6,%7},{%8,%9},{%0,%1,%2,%3};"
               : "+f"(d[0]), "+f"(d[1]), "+f"(d[2]), "+f"(d[3]) : "r"(a0), "r"(a1), "r"(a2), "r"(a3), "r"(b0), "r"(b1));
}
DEVINL void mma16816_z(float (&d)[4], uint32_t a0, uint32_t a1, uint32_t a2, uint32_t a3, uint32_t b0, uint32_t b1) {
  asm volatile("mma.sync.aligned.m16n8k16.row.col.f32.bf16.bf16.f32 {%0,%1,%2,%3},{%4,%5,%6,%7},{%8,%9},{%10,%10,%10,%10};"
               : "=f"(d[0]), "=f"(d[1]), "=f"(d[2]), "=f"(d[3]) : "r"(a0), "r"(a1), "r"(a2), "r"(a3), "r"(b0), "r"(b1), "f"(0.f));
}
DEVINL void mma1688(float (&d)[4], uint32_t a0, uint32_t a1, uint32_t b0) {
  asm volatile("mma.sync.aligned.m16n8k8.row.col.f32.bf16.bf16.f32 {%0,%1,%2,%3},{%4,%5},{%6},{%0,%1,%2,%3};"
               : "+f"(d[0]), "+f"(d[1]), "+f"(d[2]), "+f"(d[3]) : "r"(a0), "r"(a1), "r"(b0));
}
DEVINL void ldsm4(uint32_t& r0, uint32_t& r1, uint32_t& r2, uint32_t& r3, uint32_t a) {
  asm volatile("ldmatrix.sync.aligned.m8n8.x4.shared.b16 {%0,%1,%2,%3}, [%4];" : "=r"(r0), "=r"(r1), "=r"(r2), "=r"(r3) : "r"(a));
}
DEVINL void ldsm2(uint32_t& r0, uint32_t& r1, uint32_t a) {
  asm volatile("ldmatrix.sync.aligned.m8n8.x2.shared.b16 {%0,%1}, [%2];" : "=r"(r0), "=r"(r1) : "r"(a));
}
DEVINL void ldsm4t(uint32_t& r0, uint32_t& r1, uint32_t& r2, uint32_t& r3, uint32_t a) {
  asm volatile("ldmatrix.sync.aligned.m8n8.x4.trans.shared.b16 {%0,%1,%2,%3}, [%4];" : "=r"(r0), "=r"(r1), "=r"(r2), "=r"(r3) : "r"(a));
}
DEVINL void ldsm2t(uint32_t& r0, uint32_t& r1, uint32_t a) {
  asm volatile("ldmatrix.sync.aligned.m8n8.x2.trans.shared.b16 {%0,%1}, [%2];" : "=r"(r0), "=r"(r1) : "r"(a));
}
DEVINL void stsm4(uint32_t a, uint32_t r0, uint32_t r1, uint32_t r2, uint32_t r3) {
  asm volatile("stmatrix.sync.aligned.m8n8.x4.shared.b16 [%0], {%1,%2,%3,%4};" ::"r"(a), "r"(r0), "r"(r1), "r"(r2), "r"(r3) : "memory");
}
DEVINL void stsm2(uint32_t a, uint32_t r0, uint32_t r1) {
  asm volatile("stmatrix.sync.aligned.m8n8.x2.shared.b16 [%0], {%1,%2};" ::"r"(a), "r"(r0), "r"(r1) : "memory");
}
DEVINL void stsm4t(uint32_t a, uint32_t r0, uint32_t r1, uint32_t r2, uint32_t r3) {
  asm volatile("stmatrix.sync.aligned.m8n8.x4.trans.shared.b16 [%0], {%1,%2,%3,%4};" ::"r"(a), "r"(r0), "r"(r1), "r"(r2), "r"(r3) : "memory");
}
DEVINL uint32_t lds32(uint32_t a) { uint32_t v; asm volatile("ld.shared.u32 %0, [%1];" : "=r"(v) : "r"(a)); return v; }
DEVINL uint32_t lds32v(uint32_t a) { uint32_t v; asm volatile("ld.volatile.shared.u32 %0, [%1];" : "=r"(v) : "r"(a) : "memory"); return v; }
DEVINL uint4 lds128(uint32_t a) {
  uint4 v; asm volatile("ld.shared.v4.u32 {%0,%1,%2,%3}, [%4];" : "=r"(v.x), "=r"(v.y), "=r"(v.z), "=r"(v.w) : "r"(a)); return v;
}
DEVINL void sts32(uint32_t a, uint32_t v) { asm volatile("st.shared.u32 [%0], %1;" ::"r"(a), "r"(v) : "memory"); }
DEVINL void sts128(uint32_t a, uint4 v) {
  asm volatile("st.shared.v4.u32 [%0], {%1,%2,%3,%4};" ::"r"(a), "r"(v.x), "r"(v.y), "r"(v.z), "r"(v.w) : "memory");
}
DEVINL uint4 ldg_nc(const void* p) {
  uint4 v; asm volatile("ld.global.nc.L1::no_allocate.v4.u32 {%0,%1,%2,%3}, [%4];" : "=r"(v.x), "=r"(v.y), "=r"(v.z), "=r"(v.w) : "l"(p)); return v;
}
DEVINL uint4 ldg_cg(const void* p) {
  uint4 v; asm volatile("ld.global.cg.v4.u32 {%0,%1,%2,%3}, [%4];" : "=r"(v.x), "=r"(v.y), "=r"(v.z), "=r"(v.w) : "l"(p) : "memory"); return v;
}
DEVINL void stg128(void* p, uint4 v) {
  asm volatile("st.global.v4.u32 [%0], {%1,%2,%3,%4};" ::"l"(p), "r"(v.x), "r"(v.y), "r"(v.z), "r"(v.w) : "memory");
}
DEVINL uint32_t pack_bf16(float lo, float hi) {
  uint32_t r; asm("cvt.rn.bf16x2.f32 %0, %1, %2;" : "=r"(r) : "f"(hi), "f"(lo)); return r;
}
DEVINL uint32_t hmul2(uint32_t a, uint32_t b) { uint32_t r; asm("mul.rn.bf16x2 %0, %1, %2;" : "=r"(r) : "r"(a), "r"(b)); return r; }
DEVINL uint32_t hfma2(uint32_t a, uint32_t b, uint32_t c) { uint32_t r; asm("fma.rn.bf16x2 %0, %1, %2, %3;" : "=r"(r) : "r"(a), "r"(b), "r"(c)); return r; }
DEVINL uint32_t hadd2(uint32_t a, uint32_t b) { uint32_t r; asm("add.rn.bf16x2 %0, %1, %2;" : "=r"(r) : "r"(a), "r"(b)); return r; }
DEVINL float ex2(float x) { float r; asm("ex2.approx.ftz.f32 %0, %1;" : "=f"(r) : "f"(x)); return r; }

DEVINL void wgmma_n192(float (&d)[96], uint64_t da, uint64_t db, int scale_d) {
  asm volatile("{\n.reg .pred p;\nsetp.ne.b32 p, %98, 0;\n"
    "wgmma.mma_async.sync.aligned.m64n192k16.f32.bf16.bf16 "
    "{%0,%1,%2,%3,%4,%5,%6,%7,%8,%9,%10,%11,%12,%13,%14,%15,"
    "%16,%17,%18,%19,%20,%21,%22,%23,%24,%25,%26,%27,%28,%29,%30,%31,"
    "%32,%33,%34,%35,%36,%37,%38,%39,%40,%41,%42,%43,%44,%45,%46,%47,"
    "%48,%49,%50,%51,%52,%53,%54,%55,%56,%57,%58,%59,%60,%61,%62,%63,"
    "%64,%65,%66,%67,%68,%69,%70,%71,%72,%73,%74,%75,%76,%77,%78,%79,"
    "%80,%81,%82,%83,%84,%85,%86,%87,%88,%89,%90,%91,%92,%93,%94,%95}, "
    "%96, %97, p, 1, 1, 0, 1;\n}\n"
    : "+f"(d[0]), "+f"(d[1]), "+f"(d[2]), "+f"(d[3]), "+f"(d[4]), "+f"(d[5]), "+f"(d[6]), "+f"(d[7]),
      "+f"(d[8]), "+f"(d[9]), "+f"(d[10]), "+f"(d[11]), "+f"(d[12]), "+f"(d[13]), "+f"(d[14]), "+f"(d[15]),
      "+f"(d[16]), "+f"(d[17]), "+f"(d[18]), "+f"(d[19]), "+f"(d[20]), "+f"(d[21]), "+f"(d[22]), "+f"(d[23]),
      "+f"(d[24]), "+f"(d[25]), "+f"(d[26]), "+f"(d[27]), "+f"(d[28]), "+f"(d[29]), "+f"(d[30]), "+f"(d[31]),
      "+f"(d[32]), "+f"(d[33]), "+f"(d[34]), "+f"(d[35]), "+f"(d[36]), "+f"(d[37]), "+f"(d[38]), "+f"(d[39]),
      "+f"(d[40]), "+f"(d[41]), "+f"(d[42]), "+f"(d[43]), "+f"(d[44]), "+f"(d[45]), "+f"(d[46]), "+f"(d[47]),
      "+f"(d[48]), "+f"(d[49]), "+f"(d[50]), "+f"(d[51]), "+f"(d[52]), "+f"(d[53]), "+f"(d[54]), "+f"(d[55]),
      "+f"(d[56]), "+f"(d[57]), "+f"(d[58]), "+f"(d[59]), "+f"(d[60]), "+f"(d[61]), "+f"(d[62]), "+f"(d[63]),
      "+f"(d[64]), "+f"(d[65]), "+f"(d[66]), "+f"(d[67]), "+f"(d[68]), "+f"(d[69]), "+f"(d[70]), "+f"(d[71]),
      "+f"(d[72]), "+f"(d[73]), "+f"(d[74]), "+f"(d[75]), "+f"(d[76]), "+f"(d[77]), "+f"(d[78]), "+f"(d[79]),
      "+f"(d[80]), "+f"(d[81]), "+f"(d[82]), "+f"(d[83]), "+f"(d[84]), "+f"(d[85]), "+f"(d[86]), "+f"(d[87]),
      "+f"(d[88]), "+f"(d[89]), "+f"(d[90]), "+f"(d[91]), "+f"(d[92]), "+f"(d[93]), "+f"(d[94]), "+f"(d[95])
    : "l"(da), "l"(db), "r"(scale_d));
}

DEVINL void wgmma_n48(float (&d)[24], uint64_t da, uint64_t db, int scale_d) {
  asm volatile("{\n.reg .pred p;\nsetp.ne.b32 p, %26, 0;\n"
    "wgmma.mma_async.sync.aligned.m64n48k16.f32.bf16.bf16 "
    "{%0,%1,%2,%3,%4,%5,%6,%7,%8,%9,%10,%11,%12,%13,%14,%15,"
    "%16,%17,%18,%19,%20,%21,%22,%23}, "
    "%24, %25, p, 1, 1, 0, 1;\n}\n"
    : "+f"(d[0]), "+f"(d[1]), "+f"(d[2]), "+f"(d[3]), "+f"(d[4]), "+f"(d[5]), "+f"(d[6]), "+f"(d[7]),
      "+f"(d[8]), "+f"(d[9]), "+f"(d[10]), "+f"(d[11]), "+f"(d[12]), "+f"(d[13]), "+f"(d[14]), "+f"(d[15]),
      "+f"(d[16]), "+f"(d[17]), "+f"(d[18]), "+f"(d[19]), "+f"(d[20]), "+f"(d[21]), "+f"(d[22]), "+f"(d[23])
    : "l"(da), "l"(db), "r"(scale_d));
}

DEVINL void wgmma_n80(float (&d)[40], uint64_t da, uint64_t db, int scale_d) {
  asm volatile("{\n.reg .pred p;\nsetp.ne.b32 p, %42, 0;\n"
    "wgmma.mma_async.sync.aligned.m64n80k16.f32.bf16.bf16 "
    "{%0,%1,%2,%3,%4,%5,%6,%7,%8,%9,%10,%11,%12,%13,%14,%15,"
    "%16,%17,%18,%19,%20,%21,%22,%23,%24,%25,%26,%27,%28,%29,%30,%31,"
    "%32,%33,%34,%35,%36,%37,%38,%39}, "
    "%40, %41, p, 1, 1, 0, 1;\n}\n"
    : "+f"(d[0]), "+f"(d[1]), "+f"(d[2]), "+f"(d[3]), "+f"(d[4]), "+f"(d[5]), "+f"(d[6]), "+f"(d[7]),
      "+f"(d[8]), "+f"(d[9]), "+f"(d[10]), "+f"(d[11]), "+f"(d[12]), "+f"(d[13]), "+f"(d[14]), "+f"(d[15]),
      "+f"(d[16]), "+f"(d[17]), "+f"(d[18]), "+f"(d[19]), "+f"(d[20]), "+f"(d[21]), "+f"(d[22]), "+f"(d[23]),
      "+f"(d[24]), "+f"(d[25]), "+f"(d[26]), "+f"(d[27]), "+f"(d[28]), "+f"(d[29]), "+f"(d[30]), "+f"(d[31]),
      "+f"(d[32]), "+f"(d[33]), "+f"(d[34]), "+f"(d[35]), "+f"(d[36]), "+f"(d[37]), "+f"(d[38]), "+f"(d[39])
    : "l"(da), "l"(db), "r"(scale_d));
}

DEVINL void wgmma_qk_n64(float (&d)[32], uint32_t a0, uint32_t a1, uint32_t a2, uint32_t a3, uint64_t db, int scale_d) {
  asm volatile("{\n.reg .pred p;\nsetp.ne.b32 p, %37, 0;\n"
    "wgmma.mma_async.sync.aligned.m64n64k16.f32.bf16.bf16 "
    "{%0,%1,%2,%3,%4,%5,%6,%7,%8,%9,%10,%11,%12,%13,%14,%15,"
    "%16,%17,%18,%19,%20,%21,%22,%23,%24,%25,%26,%27,%28,%29,%30,%31}, "
    "{%32,%33,%34,%35}, %36, p, 1, 1, 0;\n}\n"
    : "+f"(d[0]), "+f"(d[1]), "+f"(d[2]), "+f"(d[3]), "+f"(d[4]), "+f"(d[5]), "+f"(d[6]), "+f"(d[7]),
      "+f"(d[8]), "+f"(d[9]), "+f"(d[10]), "+f"(d[11]), "+f"(d[12]), "+f"(d[13]), "+f"(d[14]), "+f"(d[15]),
      "+f"(d[16]), "+f"(d[17]), "+f"(d[18]), "+f"(d[19]), "+f"(d[20]), "+f"(d[21]), "+f"(d[22]), "+f"(d[23]),
      "+f"(d[24]), "+f"(d[25]), "+f"(d[26]), "+f"(d[27]), "+f"(d[28]), "+f"(d[29]), "+f"(d[30]), "+f"(d[31])
    : "r"(a0), "r"(a1), "r"(a2), "r"(a3), "l"(db), "r"(scale_d));
}

DEVINL void wgmma_pv_n24(float (&d)[12], uint32_t a0, uint32_t a1, uint32_t a2, uint32_t a3, uint64_t db, int scale_d) {
  asm volatile("{\n.reg .pred p;\nsetp.ne.b32 p, %17, 0;\n"
    "wgmma.mma_async.sync.aligned.m64n24k16.f32.bf16.bf16 "
    "{%0,%1,%2,%3,%4,%5,%6,%7,%8,%9,%10,%11}, "
    "{%12,%13,%14,%15}, %16, p, 1, 1, 1;\n}\n"
    : "+f"(d[0]), "+f"(d[1]), "+f"(d[2]), "+f"(d[3]), "+f"(d[4]), "+f"(d[5]), "+f"(d[6]), "+f"(d[7]),
      "+f"(d[8]), "+f"(d[9]), "+f"(d[10]), "+f"(d[11])
    : "r"(a0), "r"(a1), "r"(a2), "r"(a3), "l"(db), "r"(scale_d));
}

DEVINL void wgmma_qk_n64_z(float (&d)[32], uint32_t a0, uint32_t a1, uint32_t a2, uint32_t a3, uint64_t db) {
  asm volatile("{\n.reg .pred p;\nsetp.ne.b32 p, 0, 0;\n"
    "wgmma.mma_async.sync.aligned.m64n64k16.f32.bf16.bf16 "
    "{%0,%1,%2,%3,%4,%5,%6,%7,%8,%9,%10,%11,%12,%13,%14,%15,"
    "%16,%17,%18,%19,%20,%21,%22,%23,%24,%25,%26,%27,%28,%29,%30,%31}, "
    "{%32,%33,%34,%35}, %36, p, 1, 1, 0;\n}\n"
    : "=f"(d[0]), "=f"(d[1]), "=f"(d[2]), "=f"(d[3]), "=f"(d[4]), "=f"(d[5]), "=f"(d[6]), "=f"(d[7]),
      "=f"(d[8]), "=f"(d[9]), "=f"(d[10]), "=f"(d[11]), "=f"(d[12]), "=f"(d[13]), "=f"(d[14]), "=f"(d[15]),
      "=f"(d[16]), "=f"(d[17]), "=f"(d[18]), "=f"(d[19]), "=f"(d[20]), "=f"(d[21]), "=f"(d[22]), "=f"(d[23]),
      "=f"(d[24]), "=f"(d[25]), "=f"(d[26]), "=f"(d[27]), "=f"(d[28]), "=f"(d[29]), "=f"(d[30]), "=f"(d[31])
    : "r"(a0), "r"(a1), "r"(a2), "r"(a3), "l"(db));
}

DEVINL void wgmma_pv_n24_z(float (&d)[12], uint32_t a0, uint32_t a1, uint32_t a2, uint32_t a3, uint64_t db) {
  asm volatile("{\n.reg .pred p;\nsetp.ne.b32 p, 0, 0;\n"
    "wgmma.mma_async.sync.aligned.m64n24k16.f32.bf16.bf16 "
    "{%0,%1,%2,%3,%4,%5,%6,%7,%8,%9,%10,%11}, "
    "{%12,%13,%14,%15}, %16, p, 1, 1, 1;\n}\n"
    : "=f"(d[0]), "=f"(d[1]), "=f"(d[2]), "=f"(d[3]), "=f"(d[4]), "=f"(d[5]), "=f"(d[6]), "=f"(d[7]),
      "=f"(d[8]), "=f"(d[9]), "=f"(d[10]), "=f"(d[11])
    : "r"(a0), "r"(a1), "r"(a2), "r"(a3), "l"(db));
}

DEVINL void wgmma_cv_n64(float (&d)[32], uint32_t a0, uint32_t a1, uint32_t a2, uint32_t a3, uint64_t db) {
  asm volatile("{\n.reg .pred p;\nsetp.ne.b32 p, 1, 0;\n"
    "wgmma.mma_async.sync.aligned.m64n64k16.f32.bf16.bf16 "
    "{%0,%1,%2,%3,%4,%5,%6,%7,%8,%9,%10,%11,%12,%13,%14,%15,"
    "%16,%17,%18,%19,%20,%21,%22,%23,%24,%25,%26,%27,%28,%29,%30,%31}, "
    "{%32,%33,%34,%35}, %36, p, 1, 1, 0;\n}\n"
    : "+f"(d[0]), "+f"(d[1]), "+f"(d[2]), "+f"(d[3]), "+f"(d[4]), "+f"(d[5]), "+f"(d[6]), "+f"(d[7]),
      "+f"(d[8]), "+f"(d[9]), "+f"(d[10]), "+f"(d[11]), "+f"(d[12]), "+f"(d[13]), "+f"(d[14]), "+f"(d[15]),
      "+f"(d[16]), "+f"(d[17]), "+f"(d[18]), "+f"(d[19]), "+f"(d[20]), "+f"(d[21]), "+f"(d[22]), "+f"(d[23]),
      "+f"(d[24]), "+f"(d[25]), "+f"(d[26]), "+f"(d[27]), "+f"(d[28]), "+f"(d[29]), "+f"(d[30]), "+f"(d[31])
    : "r"(a0), "r"(a1), "r"(a2), "r"(a3), "l"(db));
}

DEVINL void wgmma_cv_n48(float (&d)[24], uint32_t a0, uint32_t a1, uint32_t a2, uint32_t a3, uint64_t db) {
  asm volatile("{\n.reg .pred p;\nsetp.ne.b32 p, 1, 0;\n"
    "wgmma.mma_async.sync.aligned.m64n48k16.f32.bf16.bf16 "
    "{%0,%1,%2,%3,%4,%5,%6,%7,%8,%9,%10,%11,%12,%13,%14,%15,"
    "%16,%17,%18,%19,%20,%21,%22,%23}, "
    "{%24,%25,%26,%27}, %28, p, 1, 1, 0;\n}\n"
    : "+f"(d[0]), "+f"(d[1]), "+f"(d[2]), "+f"(d[3]), "+f"(d[4]), "+f"(d[5]), "+f"(d[6]), "+f"(d[7]),
      "+f"(d[8]), "+f"(d[9]), "+f"(d[10]), "+f"(d[11]), "+f"(d[12]), "+f"(d[13]), "+f"(d[14]), "+f"(d[15]),
      "+f"(d[16]), "+f"(d[17]), "+f"(d[18]), "+f"(d[19]), "+f"(d[20]), "+f"(d[21]), "+f"(d[22]), "+f"(d[23])
    : "r"(a0), "r"(a1), "r"(a2), "r"(a3), "l"(db));
}

DEVINL void wgmma_cv_n32(float (&d)[16], uint32_t a0, uint32_t a1, uint32_t a2, uint32_t a3, uint64_t db) {
  asm volatile("{\n.reg .pred p;\nsetp.ne.b32 p, 1, 0;\n"
    "wgmma.mma_async.sync.aligned.m64n32k16.f32.bf16.bf16 "
    "{%0,%1,%2,%3,%4,%5,%6,%7,%8,%9,%10,%11,%12,%13,%14,%15}, "
    "{%16,%17,%18,%19}, %20, p, 1, 1, 0;\n}\n"
    : "+f"(d[0]), "+f"(d[1]), "+f"(d[2]), "+f"(d[3]), "+f"(d[4]), "+f"(d[5]), "+f"(d[6]), "+f"(d[7]),
      "+f"(d[8]), "+f"(d[9]), "+f"(d[10]), "+f"(d[11]), "+f"(d[12]), "+f"(d[13]), "+f"(d[14]), "+f"(d[15])
    : "r"(a0), "r"(a1), "r"(a2), "r"(a3), "l"(db));
}

DEVINL void wgmma_cv_n16(float (&d)[8], uint32_t a0, uint32_t a1, uint32_t a2, uint32_t a3, uint64_t db) {
  asm volatile("{\n.reg .pred p;\nsetp.ne.b32 p, 1, 0;\n"
    "wgmma.mma_async.sync.aligned.m64n16k16.f32.bf16.bf16 "
    "{%0,%1,%2,%3,%4,%5,%6,%7}, "
    "{%8,%9,%10,%11}, %12, p, 1, 1, 0;\n}\n"
    : "+f"(d[0]), "+f"(d[1]), "+f"(d[2]), "+f"(d[3]), "+f"(d[4]), "+f"(d[5]), "+f"(d[6]), "+f"(d[7])
    : "r"(a0), "r"(a1), "r"(a2), "r"(a3), "l"(db));
}

#define ATT_T(i) do {} while (0)
#define ATT_IMAX 0
#define ATT_WAIT0 0
#define ATT_SPLIT 2
constexpr float SM_C = 0.22360679774997896f * 1.4426950408889634f;
constexpr float NEG_INF = -INFINITY;
constexpr int PLANE = 2048;
constexpr int PAIR = 11 * PLANE;
constexpr int SEG = 2 * PAIR;
constexpr int PWIN = 3 * PAIR;

template <int N> DEVINL void reg_fence(float (&d)[N]) {
#pragma unroll
  for (int i = 0; i < N; ++i) asm volatile("" : "+f"(d[i])::"memory");
}
DEVINL float ex2v(float x) { float r; asm volatile("ex2.approx.ftz.f32 %0, %1;" : "=f"(r) : "f"(x)); return r; }
DEVINL uint32_t bsel(uint32_t a, uint32_t b, uint32_t m) { return (a & m) | (b & ~m); }
DEVINL float fsel(float a, float b, uint32_t m) { return __uint_as_float(bsel(__float_as_uint(a), __float_as_uint(b), m)); }
typedef uint64_t desc_t;
DEVINL desc_t kdesc(desc_t d) { return d; }
DEVINL desc_t vdesc(desc_t d) { return d; }

DEVINL void mma_qk(float (&s)[32], const uint32_t (&a)[4], const uint32_t (&a8)[2], desc_t kmain, desc_t ktail) {
  wgmma_qk_n64_z(s, a[0], a[1], a[2], a[3], kdesc(kmain));
  wgmma_qk_n64(s, a8[0], a8[1], 0u, 0u, kdesc(ktail), 1);
}
template <bool FIRST>
DEVINL void mma_pv(float (&o)[12], const uint32_t (&p)[16], desc_t v) {
  if (FIRST) wgmma_pv_n24_z(o, p[0], p[1], p[2], p[3], vdesc(v));
  else wgmma_pv_n24(o, p[0], p[1], p[2], p[3], vdesc(v), 1);
#pragma unroll
  for (int b = 1; b < 4; ++b) wgmma_pv_n24(o, p[4 * b], p[4 * b + 1], p[4 * b + 2], p[4 * b + 3], vdesc(v + b * 16), 1);
}
DEVINL void row_max_f(const float (&s)[32], float& x0o, float& x1o) {
  float x0 = fmaxf(s[0], s[1]), x1 = fmaxf(s[2], s[3]), y0 = fmaxf(s[4], s[5]), y1 = fmaxf(s[6], s[7]);
#pragma unroll
  for (int i = 2; i < 8; i += 2) {
    x0 = fmaxf(x0, fmaxf(s[4 * i], s[4 * i + 1]));
    x1 = fmaxf(x1, fmaxf(s[4 * i + 2], s[4 * i + 3]));
    y0 = fmaxf(y0, fmaxf(s[4 * i + 4], s[4 * i + 5]));
    y1 = fmaxf(y1, fmaxf(s[4 * i + 6], s[4 * i + 7]));
  }
  x0 = fmaxf(x0, y0); x1 = fmaxf(x1, y1);
  x0 = fmaxf(x0, __shfl_xor_sync(0xffffffffu, x0, 1));
  x1 = fmaxf(x1, __shfl_xor_sync(0xffffffffu, x1, 1));
  x0o = fmaxf(x0, __shfl_xor_sync(0xffffffffu, x0, 2));
  x1o = fmaxf(x1, __shfl_xor_sync(0xffffffffu, x1, 2));
}
DEVINL void row_max(const float (&s)[32], float pm0, float pm1, float& x0o, float& x1o) {
#define FI(i) __float_as_int(s[i])
  int x0 = __vimax3_s32(FI(0), FI(1), FI(4)), x1 = __vimax3_s32(FI(2), FI(3), FI(6));
  int y0 = __vimax3_s32(FI(5), FI(8), FI(9)), y1 = __vimax3_s32(FI(7), FI(10), FI(11));
  x0 = __vimax3_s32(x0, FI(12), FI(13)); x1 = __vimax3_s32(x1, FI(14), FI(15));
  y0 = __vimax3_s32(y0, FI(16), FI(17)); y1 = __vimax3_s32(y1, FI(18), FI(19));
  x0 = __vimax3_s32(x0, FI(20), FI(21)); x1 = __vimax3_s32(x1, FI(22), FI(23));
  y0 = __vimax3_s32(y0, FI(24), FI(25)); y1 = __vimax3_s32(y1, FI(26), FI(27));
  x0 = __vimax3_s32(x0, FI(28), FI(29)); x1 = __vimax3_s32(x1, FI(30), FI(31));
#undef FI
  x0 = max(x0, y0); x1 = max(x1, y1);
  x0 = max(x0, __shfl_xor_sync(0xffffffffu, x0, 1));
  x1 = max(x1, __shfl_xor_sync(0xffffffffu, x1, 1));
  x0 = max(x0, __shfl_xor_sync(0xffffffffu, x0, 2));
  x1 = max(x1, __shfl_xor_sync(0xffffffffu, x1, 2));
  float f0 = __int_as_float(x0), f1 = __int_as_float(x1);
  if (__any_sync(0xffffffffu, (x0 < 0 && !(pm0 >= 0.f)) || (x1 < 0 && !(pm1 >= 0.f)))) {
    f0 = s[0]; f1 = s[2];
#pragma unroll
    for (int i = 0; i < 8; ++i) {
      f0 = fmaxf(f0, fmaxf(s[4 * i], s[4 * i + 1]));
      f1 = fmaxf(f1, fmaxf(s[4 * i + 2], s[4 * i + 3]));
    }
    f0 = fmaxf(f0, __shfl_xor_sync(0xffffffffu, f0, 1));
    f1 = fmaxf(f1, __shfl_xor_sync(0xffffffffu, f1, 1));
    f0 = fmaxf(f0, __shfl_xor_sync(0xffffffffu, f0, 2));
    f1 = fmaxf(f1, __shfl_xor_sync(0xffffffffu, f1, 2));
  }
  x0o = f0; x1o = f1;
}
template <int I0, int I1>
DEVINL void sm_exp(const float (&s)[32], uint32_t (&p)[16], float n0, float n1) {
#pragma unroll
  for (int i = I0; i < I1; ++i) {
    const float e0 = ex2v(fmaf(s[4 * i], SM_C, n0)), e1 = ex2v(fmaf(s[4 * i + 1], SM_C, n0));
    const float e2 = ex2v(fmaf(s[4 * i + 2], SM_C, n1)), e3 = ex2v(fmaf(s[4 * i + 3], SM_C, n1));
    p[2 * i] = pack_bf16(e0, e1);
    p[2 * i + 1] = pack_bf16(e2, e3);
  }
}
DEVINL void rescale(float (&o)[12], float al0, float al1) {
#pragma unroll
  for (int n = 0; n < 3; ++n) { o[4 * n] *= al0; o[4 * n + 1] *= al0; o[4 * n + 2] *= al1; o[4 * n + 3] *= al1; }
}
struct SoftmaxState { float m0, m1, n0, n1, al0, al1; };
DEVINL void next_max(SoftmaxState& st, float x0, float x1, bool valid) {
  x0 = fmaxf(valid ? x0 : NEG_INF, st.m0); x1 = fmaxf(valid ? x1 : NEG_INF, st.m1);
  const float c0 = -x0 * SM_C, c1 = -x1 * SM_C;
  st.al0 = ex2(fmaf(st.m0, SM_C, c0)); st.al1 = ex2(fmaf(st.m1, SM_C, c1));
  st.m0 = x0; st.m1 = x1;
  st.n0 = valid ? c0 : NEG_INF; st.n1 = valid ? c1 : NEG_INF;
}
template <bool PVPEND, int SPLIT>
DEVINL void step(const float (&cur)[32], float (&nxt)[32], float (&o)[12], uint32_t (&p)[16], SoftmaxState& st, bool valid_nxt) {
  const float n0 = st.n0, n1 = st.n1, pa0 = st.al0, pa1 = st.al1;
  sm_exp<0, SPLIT>(cur, p, n0, n1);
  wg_wait<(PVPEND && !ATT_WAIT0) ? 1 : 0>();
  reg_fence(nxt);
  float x0, x1;
  row_max_f(nxt, x0, x1);
  sm_exp<SPLIT, 8>(cur, p, n0, n1);
  next_max(st, x0, x1, valid_nxt);
  if (PVPEND) { wg_wait<0>(); reg_fence(o); rescale(o, pa0, pa1); }
}

DEVINL void attn_all(uint32_t ring, uint32_t stg, uint32_t bars, int wq, int lane, int cmin) {
  const int wg = wq >> 2, w = wq & 3;
  const int g = lane >> 2, t = lane & 3, mi = lane >> 3, r = lane & 7;
  const uint32_t T0 = (2 * t > g) ? 0xFFFFFFFFu : 0u, T1 = (2 * t + 1 > g) ? 0xFFFFFFFFu : 0u;
  const uint32_t tri = (T0 & 0xFFFFu) | (T1 & 0xFFFF0000u);
  const uint32_t rowQ = stg + (mi >> 1) * PLANE + (16 * wq + r + 8 * (mi & 1)) * 16;
  const uint32_t rowQ8 = stg + 2 * PLANE + (16 * wq + (lane & 15)) * 16;
  constexpr uint32_t S16 = PAIR >> 4, P16 = PLANE >> 4;
  const uint32_t aE = ((ring + wg * 1024) & 0x3FFFF) >> 4, aO = ((ring + wg * PAIR + (wg ^ 1) * 1024) & 0x3FFFF) >> 4;
  const desc_t kE = (desc_t)(aE | (P16 << 16)) | ((desc_t)(128 >> 4) << 32), kO = (desc_t)(aO | (P16 << 16)) | ((desc_t)(128 >> 4) << 32);
  const desc_t vE = (desc_t)(aE | ((128 >> 4) << 16)) | ((desc_t)P16 << 32), vO = (desc_t)(aO | ((128 >> 4) << 16)) | ((desc_t)P16 << 32);
  uint32_t a[4], a8[2];
  float sX[32], sY[32], o[12];
  uint32_t pA[16], pB[16];
  ldsm4(a[0], a[1], a[2], a[3], rowQ);
  ldsm2(a8[0], a8[1], rowQ8);
  if (t >= 2) { a8[0] = 0u; a8[1] = 0u; }
  mbar_wait(bars + 8 * B_HALO, 0);
  if (wq == 0 && lane == 0) PROF(26);
  wg_fence();
  mma_qk(sX, a, a8, kE, kE + 2 * P16);
  mma_qk(sY, a, a8, kE + 2 * S16, kE + 2 * S16 + 2 * P16);
  wg_commit();
#pragma unroll 1
  for (int h = 0; h < 4; ++h) {
    if (wq == 0 && lane == 0) PROF(56 + h);
    const int p = h >> 1, odd = h & 1;
    const uint32_t km = (p * 33 + odd * 3) * P16, kt = (p * 33 + 2) * P16, vp = (p * 33 + 5 + odd * 3) * P16;
    SoftmaxState st;
    ATT_T(0);
    wg_wait<0>();
    reg_fence(sX); reg_fence(sY);
    ATT_T(1);
    if (cmin > 0) {
#pragma unroll
      for (int i = 0; i < 32; ++i) sX[i] = NEG_INF;
    }
#pragma unroll
    for (int b = 0; b < 4; ++b) {
      const uint32_t gt = b > w ? 0xFFFFFFFFu : 0u, ge = b >= w ? 0xFFFFFFFFu : 0u, eq = ge & ~gt;
      const uint32_t e0 = gt | (eq & T0), e1 = gt | (eq & T1);
      sX[8 * b + 0] = fsel(sX[8 * b + 0], sY[8 * b + 0], e0);
      sX[8 * b + 1] = fsel(sX[8 * b + 1], sY[8 * b + 1], e1);
      sX[8 * b + 2] = fsel(sX[8 * b + 2], sY[8 * b + 2], gt);
      sX[8 * b + 3] = fsel(sX[8 * b + 3], sY[8 * b + 3], gt);
      sX[8 * b + 4] = fsel(sX[8 * b + 4], sY[8 * b + 4], ge);
      sX[8 * b + 5] = fsel(sX[8 * b + 5], sY[8 * b + 5], ge);
      sX[8 * b + 6] = fsel(sX[8 * b + 6], sY[8 * b + 6], e0);
      sX[8 * b + 7] = fsel(sX[8 * b + 7], sY[8 * b + 7], e1);
    }
    wg_fence();
    mma_qk(sY, a, a8, kO + km, kO + kt);
    wg_commit();
    ATT_T(2);
    row_max_f(sX, st.m0, st.m1);
    st.n0 = -st.m0 * SM_C; st.n1 = -st.m1 * SM_C;
    ATT_T(3);
    step<false, ATT_SPLIT>(sX, sY, o, pA, st, wg + 1 >= cmin);
    ATT_T(4);
#pragma unroll
    for (int b = 0; b < 4; ++b) {
      const uint32_t gt = b > w ? 0xFFFFFFFFu : 0u, ge = b >= w ? 0xFFFFFFFFu : 0u, eq = ge & ~gt;
      const uint32_t mt = gt | (eq & tri);
      pB[4 * b + 0] = pA[4 * b + 0] & ~mt; pA[4 * b + 0] &= mt;
      pB[4 * b + 1] = pA[4 * b + 1] & ~gt; pA[4 * b + 1] &= gt;
      pB[4 * b + 2] = pA[4 * b + 2] & ~ge; pA[4 * b + 2] &= ge;
      pB[4 * b + 3] = pA[4 * b + 3] & ~mt; pA[4 * b + 3] &= mt;
    }
    if (h == 0) mbar_wait(bars + 8 * B_HALOV, 0);
    wg_fence();
    mma_qk(sX, a, a8, kE + S16 + km, kE + S16 + kt);
    wg_commit();
    mma_pv<true>(o, pA, vE + vp);
    mma_pv<false>(o, pB, vE + 2 * S16 + vp);
    wg_commit();
    ATT_T(5);
    step<true, ATT_SPLIT>(sY, sX, o, pB, st, wg + 2 >= cmin);
    ATT_T(6);
    wg_fence();
    mma_qk(sY, a, a8, kO + S16 + km, kO + S16 + kt);
    wg_commit();
    mma_pv<false>(o, pB, vO + vp);
    wg_commit();
    ATT_T(7);
    step<true, ATT_SPLIT>(sX, sY, o, pA, st, wg + 3 >= cmin);
    ATT_T(8);
    const int hn = h < 3 ? h + 1 : h, pn = hn >> 1, on = hn & 1;
    const uint32_t kmn = (pn * 33 + on * 3) * P16, ktn = (pn * 33 + 2) * P16;
    if (h == 1) mbar_wait(bars + 8 * (B_HALO + 1), 0);
    ldsm4(a[0], a[1], a[2], a[3], rowQ + (pn * 5 + on * 3) * PLANE);
    ldsm2(a8[0], a8[1], rowQ8 + pn * 5 * PLANE);
    if ((t >= 2) != (on != 0)) { a8[0] = 0u; a8[1] = 0u; }
    wg_fence();
    mma_pv<false>(o, pA, vE + S16 + vp);
    mma_qk(sX, a, a8, kE + kmn, kE + ktn);
    wg_commit();
    ATT_T(9);
    sm_exp<0, 8>(sY, pB, st.n0, st.n1);
    ATT_T(10);
    wg_wait<0>();
    reg_fence(o); reg_fence(sX);
    rescale(o, st.al0, st.al1);
    wg_fence();
    mma_pv<false>(o, pB, vO + S16 + vp);
    wg_commit();
    wg_fence();
    mma_qk(sY, a, a8, kE + 2 * S16 + kmn, kE + 2 * S16 + ktn);
    wg_commit();
    ATT_T(11);
    wg_wait<1>();
    reg_fence(o);
    const int src = (lane & ~3) | (odd ? 0 : 2);
    const float i0 = __fdividef(1.f, __shfl_sync(0xffffffffu, o[8], src)), i1 = __fdividef(1.f, __shfl_sync(0xffffffffu, o[10], src));
    const uint32_t ob = stg + p * 5 * PLANE + (16 * wq + g) * 16 + t * 4;
    const uint32_t om = ob + odd * 3 * PLANE;
    sts32(om, pack_bf16(o[0] * i0, o[1] * i0)); sts32(om + 128, pack_bf16(o[2] * i1, o[3] * i1));
    sts32(om + PLANE, pack_bf16(o[4] * i0, o[5] * i0)); sts32(om + PLANE + 128, pack_bf16(o[6] * i1, o[7] * i1));
    if ((t >= 2) == (odd != 0)) { sts32(ob + 2 * PLANE, pack_bf16(o[8] * i0, o[9] * i0)); sts32(ob + 2 * PLANE + 128, pack_bf16(o[10] * i1, o[11] * i1)); }
    if (odd) {
      fence_async_smem();
      __syncwarp();
      if (lane == 0) mbar_arrive(bars + 8 * (B_OST + p));
      if (lane < 4) mbar_arrive_cta(bars + 8 * (B_EMPTY2 + 2 * p + (lane >> 1)), lane & 1);
    }
    ATT_T(12);
  }
  wg_wait<0>();
  reg_fence(sX); reg_fence(sY);
  __syncwarp();
}

#define NO_G 1
#define CONV_DUP 0
#define CONV_YIELD 25
#define FPF_AT 6
#define KT_GATE 0
#define XWPF 0
#define PRE_FMA 0
#define EARLY_PF 0
#define QKV_LAG 0
#define OP_ORDER 1
#define OPUB_GATE 0
#define KT_IN_F 0
#define EXP_NOLD 0
#define PF_MODE 2
#define KVPF_AT 3
#define PRE_LDG 0
#define PRE_AFTER 2
#define PRE_WAIT 1
struct Params {
  const uint16_t* q; const uint16_t* k; const uint16_t* v; const uint16_t* shift_k; const uint16_t* ssm_k;
  const uint16_t* ssm_D; const uint16_t* x; const uint16_t* wqkv; const uint16_t* wo; uint16_t* out;
};

DEVINL unsigned* cnt(int i) { return &g_cnt[i * CS]; }

DEVINL void finish_role() {
  unsigned old = atomicAdd(cnt(C_DONE), 1u);
  if (old == 255u) {
    __threadfence();
    for (int i = 0; i < C_NUM; ++i) *cnt(i) = 0u;
    __threadfence();
  }
}

DEVINL void conv_channel(uint32_t sb, int cl, int wc, int lane, uint32_t D2, int bar_id) {
  const int mi = lane >> 3, r = lane & 7, g = lane >> 2, t = lane & 3;
  const int h = wc >> 1, rr = wc & 1;
  const uint32_t Ub = cl < 4 ? sb + OFF_U + cl * CH_U : sb + OFF_U4, Fb = sb + OFF_F + cl * CH_F;
  const uint32_t fw = ((g & 1) ? Fb + 4160 + 2 * (33 - g + 2 * t) : Fb + 2 * (32 - g + 2 * t)) + 1024 * h - 32 * rr;
  const uint64_t ub = (uint64_t)((((Ub & 0x3FFFF) >> 4) + 16) | ((UPL >> 4) << 16)) | ((uint64_t)(128 >> 4) << 32);
  uint64_t bcur = ub;
  float d[32], d2[16];
#pragma unroll
  for (int i = 0; i < 32; ++i) d[i] = 0.f;
#pragma unroll
  for (int i = 0; i < 16; ++i) d2[i] = 0.f;
#pragma unroll 1
  for (int rq = 0; rq < 4; ++rq) {
#pragma unroll
    for (int bt = 0; bt < 2; ++bt) {
      const int rho = 4 * rq + 2 * bt;
      const uint32_t fb = fw + 64 * rho;
      uint32_t x[2][2][2][4];
      wg_wait<1>();
#pragma unroll
      for (int e = 0; e < 2; ++e)
#pragma unroll
        for (int nu = 0; nu < 2; ++nu) {
          const uint32_t a = fb + 64 * e + 2048 * nu;
          x[e][nu][0][0] = lds32(a); x[e][nu][0][1] = lds32(a - 16); x[e][nu][0][2] = lds32(a + 16); x[e][nu][0][3] = x[e][nu][0][0];
          x[e][nu][1][0] = lds32(a + 32); x[e][nu][1][1] = x[e][nu][0][2]; x[e][nu][1][2] = lds32(a + 48); x[e][nu][1][3] = x[e][nu][1][0];
        }
      wg_fence();
#pragma unroll
      for (int e = 0; e < 2; ++e) {
        const uint64_t b0 = bcur - e, b1 = b0 + 2 * (UPL >> 4);
        wgmma_cv_n64(d, x[e][0][0][0], x[e][0][0][1], x[e][0][0][2], x[e][0][0][3], b0);
        wgmma_cv_n64(d, x[e][0][1][0], x[e][0][1][1], x[e][0][1][2], x[e][0][1][3], b1);
        wgmma_cv_n32(d2, x[e][1][0][0], x[e][1][0][1], x[e][1][0][2], x[e][1][0][3], b0);
        wgmma_cv_n32(d2, x[e][1][1][0], x[e][1][1][1], x[e][1][1][2], x[e][1][1][3], b1);
      }
      wg_commit();
      bcur -= 2;
      __nanosleep(CONV_YIELD);
    }
  }
  wg_wait<0>();
  reg_fence(d); reg_fence(d2);
#pragma unroll
  for (int i = 0; i < 16; ++i) d[16 + i] += d2[i];
  named_sync(bar_id, 128);
  const uint32_t xb = Fb + wc * 2048 + lane * 16;
#pragma unroll
  for (int j = 0; j < 4; ++j) {
    const float4 v = h == 0 ? make_float4(d[16 + 4 * j], d[17 + 4 * j], d[18 + 4 * j], d[19 + 4 * j])
                            : make_float4(d[4 * j], d[1 + 4 * j], d[2 + 4 * j], d[3 + 4 * j]);
    sts128(xb + j * 512, make_uint4(__float_as_uint(v.x), __float_as_uint(v.y), __float_as_uint(v.z), __float_as_uint(v.w)));
  }
  named_sync(bar_id, 128);
  const uint32_t xr = Fb + (wc ^ 2) * 2048 + lane * 16;
  float f[4][4];
#pragma unroll
  for (int j = 0; j < 4; ++j) {
    const uint4 ov = lds128(xr + (h == 0 ? (j >= 2 ? j - 2 : 0) : j) * 512);
    const float z = (h == 0 && j < 2) ? 0.f : 1.f;
    f[j][0] = (h == 0 ? d[4 * j] : d[8 + 4 * j]) + z * __uint_as_float(ov.x);
    f[j][1] = (h == 0 ? d[4 * j + 1] : d[9 + 4 * j]) + z * __uint_as_float(ov.y);
    f[j][2] = (h == 0 ? d[4 * j + 2] : d[10 + 4 * j]) + z * __uint_as_float(ov.z);
    f[j][3] = (h == 0 ? d[4 * j + 3] : d[11 + 4 * j]) + z * __uint_as_float(ov.w);
  }
  uint32_t res[2][4];
#pragma unroll
  for (int jj = 0; jj < 2; ++jj) {
    const int tile = 4 * h + 2 * jj + (mi >> 1);
    uint32_t u0, u1, u2, u3;
    ldsm4t(u0, u1, u2, u3, Ub + (2 * rr + (mi & 1)) * UPL + (16 + 8 * tile + r) * 16);
    res[jj][0] = hadd2(pack_bf16(f[2 * jj][0], f[2 * jj][1]), hmul2(u0, D2));
    res[jj][1] = hadd2(pack_bf16(f[2 * jj][2], f[2 * jj][3]), hmul2(u1, D2));
    res[jj][2] = hadd2(pack_bf16(f[2 * jj + 1][0], f[2 * jj + 1][1]), hmul2(u2, D2));
    res[jj][3] = hadd2(pack_bf16(f[2 * jj + 1][2], f[2 * jj + 1][3]), hmul2(u3, D2));
  }
  named_sync(bar_id, 128);
#pragma unroll
  for (int jj = 0; jj < 2; ++jj) {
    const int tile = 4 * h + 2 * jj + (mi >> 1);
    stsm4t(Fb + ((8 * tile + r) * 32 + 16 * rr + 8 * (mi & 1)) * 2, res[jj][0], res[jj][1], res[jj][2], res[jj][3]);
  }
  fence_async_smem();
  __syncwarp();
  if (lane == 0) mbar_arrive(sb + OFF_BAR + 8 * (B_YST + cl));
}

__global__ void __cluster_dims__(2, 1, 1) __launch_bounds__(512, 1)
h3_swa_fused_kernel(const __grid_constant__ CUtensorMap tmX, const __grid_constant__ CUtensorMap tmW128,
                    const __grid_constant__ CUtensorMap tmW32,
                    const __grid_constant__ CUtensorMap tmOut, const __grid_constant__ CUtensorMap tmKT,
                    const __grid_constant__ CUtensorMap tmKin, const __grid_constant__ CUtensorMap tmVin,
                    const __grid_constant__ CUtensorMap tmQ, const __grid_constant__ CUtensorMap tmYT,
                    const __grid_constant__ CUtensorMap tmU4, const __grid_constant__ CUtensorMap tmU1,
                    const __grid_constant__ CUtensorMap tmXP,
                    const Params prm) {
  extern __shared__ uint8_t smem_raw[];
  const uint32_t sb = (uint32_t)__cvta_generic_to_shared(smem_raw);
  if ((sb & 1023u) != 0u) { g_err = 3; return; }
  const uint32_t bars = sb + OFF_BAR;
  const int tid = threadIdx.x, warp = tid >> 5, lane = tid & 31, wg = tid >> 7;
  const int cta = blockIdx.x;
  const uint32_t rank = cta & 1;
  const int g8 = (cta >> 1) & 7, rp = cta >> 4;
  const int rb = 2 * rp + rank;
  const int rb2 = 2 * rp + (g8 & 1);
  const int c2 = 2 * (g8 >> 1) + rank;
  const int tau = cta & 15, jt = cta >> 4;

  if (tid == 384) {
    prefetch_tmap(&tmX); prefetch_tmap(&tmW128); prefetch_tmap(&tmW32);
  }
  if (tid == 0) {
    PROF(0);
    for (int i = 0; i < NST1; ++i) { mbar_init(bars + 8 * (B_FULL1 + i), 1); mbar_init(bars + 8 * (B_EMPTY1 + i), 16); }
    mbar_init(bars + 8 * B_RINGFREE, 1);
    mbar_init(bars + 8 * B_HALO, 1); mbar_init(bars + 8 * (B_HALO + 1), 1); mbar_init(bars + 8 * B_HALOV, 1);
    for (int i = 0; i < NST2; ++i) { mbar_init(bars + 8 * (B_FULL2 + i), 1); mbar_init(bars + 8 * (B_EMPTY2 + i), 16); }
    mbar_init(bars + 8 * B_U, 1);
    mbar_init(bars + 8 * B_KVST, 8); mbar_init(bars + 8 * B_KVST1, 8);
    mbar_init(bars + 8 * B_OST, 8); mbar_init(bars + 8 * (B_OST + 1), 8);
    mbar_init(bars + 8 * B_KTST, 4);
    for (int i = 0; i < 5; ++i) mbar_init(bars + 8 * (B_YST + i), 4);
    mbar_init(bars + 8 * B_CIN, 4);
    mbar_init(bars + 8 * B_OPUB, 1);
    mbar_init(bars + 8 * B_PRE, 1);
    mbar_init(bars + 8 * B_FRAW, 1);
    mbar_init(bars + 8 * B_QT, 1);
    mbar_init(bars + 8 * B_P0PUB, 1);
    mbar_init(bars + 8 * B_YT, 1);
    mbar_init(bars + 8 * B_U4, 1);
    mbar_init(bars + 8 * B_STGFREE, 4);
    mbar_init(bars + 8 * B_FFREE, 8);
    asm volatile("fence.mbarrier_init.release.cluster;" ::: "memory");
  }
  __syncthreads();
  asm volatile("barrier.cluster.arrive.relaxed.aligned;\nbarrier.cluster.wait.aligned;" ::: "memory");

  if (wg == 3) {
    asm volatile("setmaxnreg.dec.sync.aligned.u32 32;");
    if (warp == 12 && lane == 0) {
      PROF(15);
      for (int it = 0; it < 10; ++it) {
        const int s = it % NST1;
        if (it >= NST1) mbar_wait(bars + 8 * (B_EMPTY1 + s), ((it / NST1) - 1) & 1);
        PROF(44 + it);
        const uint32_t st = sb + s * ST1, fb = bars + 8 * (B_FULL1 + s);
        mbar_expect(fb, ST1);
        tma2d(st, &tmX, it * 64, rb * 128, fb);
        tma3d_mc(st + ST1_B128 + rank * 12288, &tmW128, g8 * 80, it * 64 + rank * 32, 0, fb);
        tma3d_mc(st + ST1_B32 + rank * 3072, &tmW32, g8 * 80 + 64, it * 64 + rank * 32, 0, fb);
        if (it == PRE_AFTER) {
          mbar_expect(bars + 8 * B_PRE, 131 * 160 + 128 * 160);
          tma2d(sb + OFF_U, &tmKin, jt * 80, tau * 128 - 3, bars + 8 * B_PRE);
          tma2d(sb + OFF_STG, &tmVin, jt * 80, tau * 128, bars + 8 * B_PRE);
        }
        if (it == FPF_AT) prefetch_l2(prm.ssm_k + (size_t)cta * 5 * SEQ, 5 * SEQ * 2);
      }
      PROF(1);
      mbar_wait(bars + 8 * B_RINGFREE, 0);
      for (int p = 0; p < 2; ++p) {
        const uint32_t hb = bars + 8 * (B_HALO + p);
        if (rb == 0) { mbar_arrive(hb); if (p == 0) mbar_arrive(bars + 8 * B_HALOV); continue; }
        poll_ge(cnt(C_KV + (g8 * 16 + rb - 1) * 2 + p), 1);
        if (rb >= 2) poll_ge(cnt(C_KV + (g8 * 16 + rb - 2) * 2 + p), 1);
        if (p == 0) PROF(2);
        const uint16_t* s1 = g_kv + (size_t)(g8 * 16 + rb - 1) * (SEG / 2) + p * (PAIR / 2);
        const uint16_t* s0 = s1 - 1 * (SEG / 2);
        const int nseg = rb >= 2 ? 2 : 1;
        if (p == 0) {
          mbar_expect(hb, nseg * 5 * PLANE);
          bulk_load(sb + PAIR, s1, 5 * PLANE, hb);
          if (rb >= 2) bulk_load(sb, s0, 5 * PLANE, hb);
          const uint32_t vb = bars + 8 * B_HALOV;
          mbar_expect(vb, nseg * 6 * PLANE);
          bulk_load(sb + PAIR + 5 * PLANE, s1 + 5 * (PLANE / 2), 6 * PLANE, vb);
          if (rb >= 2) bulk_load(sb + 5 * PLANE, s0 + 5 * (PLANE / 2), 6 * PLANE, vb);
        } else {
          mbar_expect(hb, nseg * PAIR);
          bulk_load(sb + PWIN + PAIR, s1, PAIR, hb);
          if (rb >= 2) bulk_load(sb + PWIN, s0, PAIR, hb);
        }
      }
      poll_ge(cnt(C_WO + c2), 16);
#pragma unroll 1
      for (int it = 0; it < 8; ++it) {
        const int s = it & 3, p = it >> 2;
        mbar_wait(bars + 8 * (B_EMPTY2 + s), p);
        const uint32_t fb = bars + 8 * (B_FULL2 + s);
        mbar_expect(fb, ST2);
        if (it == 0) { PROF(3); poll_ge(cnt(C_O + rb2 * 2), 8); }
        if (p == 0 || it >= 6) bulk_load_mc(sb + s * ST2 + rank * 10240, g_o + (size_t)(rb2 * 80 + p * 40 + (2 * s + rank) * 5) * 1024, 10240, fb);
        bulk_load(sb + s * ST2 + 20480, g_woP + (size_t)(c2 * 8 + it) * 6400, 12800, fb);
        if (it == 5) {
          poll_ge(cnt(C_O + rb2 * 2 + 1), 8);
          PROF(4);
          for (int s2 = 0; s2 < 2; ++s2)
            bulk_load_mc(sb + s2 * ST2 + rank * 10240, g_o + (size_t)(rb2 * 80 + 40 + (2 * s2 + rank) * 5) * 1024, 10240, bars + 8 * (B_FULL2 + s2));
        }
      }
      finish_role();
    } else if (warp == 13 && lane == 0) {
      prefetch_tmap(&tmOut);
      mbar_wait(bars + 8 * B_FFREE, 0);
      mbar_expect(bars + 8 * B_FRAW, 5 * 4096);
      for (int c = 0; c < 5; ++c) bulk_load(sb + OFF_F + c * CH_F + 64, prm.ssm_k + (size_t)(cta * 5 + c) * SEQ, 4096, bars + 8 * B_FRAW);
      mbar_wait(bars + 8 * B_KVST, 0);
      uint16_t* kd = g_kv + (size_t)(g8 * 16 + rb) * (SEG / 2);
      bulk_store(kd, sb + 2 * PAIR, PAIR); bulk_commit();
      bulk_wait<0>(); red_publish(cnt(C_KV + (g8 * 16 + rb) * 2));
      mbar_arrive(bars + 8 * B_P0PUB);
      PROF(55);
      mbar_wait(bars + 8 * B_KVST1, 0);
      bulk_store(kd + PAIR / 2, sb + PWIN + 2 * PAIR, PAIR); bulk_commit();
      bulk_wait<0>(); red_publish(cnt(C_KV + (g8 * 16 + rb) * 2 + 1));
      PROF(24);
      for (int p = 0; p < 2; ++p) {
        mbar_wait(bars + 8 * (B_OST + p), 0);
        if (p == 1) PROF(31);
        bulk_store(g_o + (size_t)(rb * 80 + p * 40 + g8 * 5) * 1024, sb + OFF_STG + p * 10240, 10240);
        bulk_commit(); bulk_wait<0>();
        if (p == 1) PROF(54);
        red_publish(cnt(C_O + rb * 2 + p));
      }
      mbar_arrive(bars + 8 * B_OPUB);
      PROF(20);
    } else if (warp == 15) {
      const int run = rp * 2 + (g8 & 1);
      const int gg = run >> 1, pp = run & 1;
      mbar_wait(bars + 8 * (B_FULL1 + 3), 0);
#pragma unroll 1
      for (int i0 = 0; i0 < 13; i0 += 4) {
        uint4 v[4];
#pragma unroll
        for (int i = 0; i < 4; ++i) {
          const int idx = lane + 32 * (i0 + i), j = idx / 10, n8 = idx % 10;
          if (idx < 400) v[i] = ldg_nc(prm.wo + (size_t)(gg * 80 + pp * 40 + j) * DM + c2 * 80 + n8 * 8);
        }
#pragma unroll
        for (int i = 0; i < 4; ++i) {
          const int idx = lane + 32 * (i0 + i), j = idx / 10, n8 = idx % 10;
          if (idx < 400) stg128(g_woP + (size_t)((c2 * 8 + pp * 4 + (gg >> 1)) * 10 + n8) * 640 + ((gg & 1) * 40 + j) * 8, v[i]);
        }
      }
      asm volatile("fence.acq_rel.gpu;" ::: "memory");
      __syncwarp();
      if (lane == 0) asm volatile("red.relaxed.gpu.global.add.u32 [%0], 1;" ::"l"(cnt(C_WO + c2)) : "memory");
    } else if (warp == 14 && lane == 0) {
      prefetch_tmap(&tmKT); prefetch_tmap(&tmU4); prefetch_tmap(&tmU1);
      mbar_wait(bars + 8 * B_KTST, 0);
      tma3d_store(&tmKT, 0, tau, jt * 80, sb + OFF_U);
      bulk_commit();
      bulk_wait<0>();
      red_publish(cnt(C_PRE + jt));
      PROF(8);
      poll_ge(cnt(C_PRE + jt), 16);
      mbar_expect(bars + 8 * B_U, 4 * CH_U);
      tma4d(sb + OFF_U, &tmU4, 0, -4, 0, cta * 5, bars + 8 * B_U);
      mbar_wait(bars + 8 * B_FFREE, 0);
      mbar_expect(bars + 8 * B_U4, CH_U);
      tma4d(sb + OFF_U4, &tmU1, 0, -4, 0, cta * 5 + 4, bars + 8 * B_U4);
      PROF(9);
      for (int c = 0; c < 5; ++c) {
        mbar_wait(bars + 8 * (B_YST + c), 0);
        bulk_store(g_yT + (size_t)(cta * 5 + c) * SEQ, sb + OFF_F + c * CH_F, 4096);
        bulk_commit();
      }
      prefetch_tmap(&tmQ); prefetch_tmap(&tmYT);
      mbar_expect(bars + 8 * B_QT, 128 * 160);
      tma2d(sb + OFF_U, &tmQ, jt * 80, tau * 128, bars + 8 * B_QT);
      bulk_wait<0>();
      red_publish(cnt(C_Y + jt), 5);
      PROF(11);
      poll_ge(cnt(C_Y + jt), 80);
      PROF(12);
      mbar_expect(bars + 8 * B_YT, 80 * 256);
      tma2d(sb + OFF_F, &tmYT, tau * 128, jt * 80, bars + 8 * B_YT);
      tma2d(sb + OFF_F + 10240, &tmYT, tau * 128 + 64, jt * 80, bars + 8 * B_YT);
      finish_role();
    }
  } else if (wg == 2) {
    asm volatile("setmaxnreg.inc.sync.aligned.u32 144;");
    const int ct = tid - 256, wc = __shfl_sync(0xffffffffu, warp, 0) - 8;
    const int t0 = tau * 128, c0 = jt * 80;
    const int mi = lane >> 3, r = lane & 7, g = lane >> 2, t = lane & 3;
    const uint32_t U = sb + OFF_U, F = sb + OFF_F;
    if (ct == 0) PROF(14);
    uint32_t dpack = lane < 5 ? (uint32_t)__ldg(prm.ssm_D + cta * 5 + lane) : 0u;
    dpack |= dpack << 16;
    {
      const int c = ct % 10, seg = ct / 10;
      uint4 wv[4];
#pragma unroll
      for (int u = 0; u < 4; ++u) wv[u] = ldg_nc(prm.shift_k + (size_t)(c0 + c * 8 + 2 * u) * 4);
      uint32_t W[4][4];
#pragma unroll
      for (int u = 0; u < 4; ++u) {
        W[0][u] = __byte_perm(wv[u].x, wv[u].z, 0x5410); W[1][u] = __byte_perm(wv[u].x, wv[u].z, 0x7632);
        W[2][u] = __byte_perm(wv[u].y, wv[u].w, 0x5410); W[3][u] = __byte_perm(wv[u].y, wv[u].w, 0x7632);
      }
      mbar_wait(bars + 8 * B_PRE, 0);
      if (ct == 0) PROF(5);
      if (ct < 120) {
        const int nrow = seg == 11 ? 7 : 11;
        const uint32_t ka = U + seg * 11 * 160 + c * 16, va = sb + OFF_STG + seg * 11 * 160 + c * 16;
        uint4 kk[14], vv[11];
#pragma unroll
        for (int i = 0; i < 14; ++i) kk[i] = i < nrow + 3 ? lds128(ka + i * 160) : make_uint4(0, 0, 0, 0);
#pragma unroll
        for (int i = 0; i < 11; ++i) vv[i] = i < nrow ? lds128(va + i * 160) : make_uint4(0, 0, 0, 0);
#pragma unroll
        for (int i = 0; i < 11; ++i) {
          uint32_t res[4];
#pragma unroll
          for (int u = 0; u < 4; ++u) {
            uint32_t acc = hadd2(hmul2((&kk[i].x)[u], W[3][u]), hmul2((&kk[i + 1].x)[u], W[2][u]));
            acc = hadd2(acc, hmul2((&kk[i + 2].x)[u], W[1][u]));
            acc = hadd2(acc, hmul2((&kk[i + 3].x)[u], W[0][u]));
            res[u] = hmul2(acc, (&vv[i].x)[u]);
          }
          if (i < nrow) sts128(va + i * 160, make_uint4(res[0], res[1], res[2], res[3]));
        }
      }
    }
    if (ct == 0) PROF(6);
    named_sync(3, 128);
    {
      uint4 v4[10];
#pragma unroll
      for (int k = 0; k < 10; ++k) {
        const int it = wc + 4 * k, c = it % 10, q = it / 10;
        const int tl = 32 * (r >> 1) + 31 - (8 * q + 2 * mi + (r & 1));
        ldsm4t(v4[k].x, v4[k].y, v4[k].z, v4[k].w, sb + OFF_STG + tl * 160 + c * 16);
      }
#pragma unroll
      for (int k = 0; k < 10; ++k) {
        const int it = wc + 4 * k, c = it % 10, q = it / 10;
        sts128(U + (c * 8 + g) * 256 + q * 64 + t * 16, v4[k]);
      }
    }
    fence_async_smem();
    __syncwarp();
    if (lane == 0) { mbar_arrive(bars + 8 * B_KTST); mbar_arrive(bars + 8 * B_STGFREE); }
    if (ct == 0) PROF(7);
    if (ct < 32) prefetch_line(prm.q + ((size_t)cta * 160 + 128 + ct) * 64);
    prefetch_line(prm.q + ((size_t)cta * 160 + ct) * 64);
    mbar_wait(bars + 8 * B_FRAW, 0);
    {
      uint4 fv[10]; uint32_t pv[10];
#pragma unroll
      for (int i = 0; i < 10; ++i) {
        const int cl = i >> 1, qq = ct + (i & 1) * 128;
        const uint32_t a = F + cl * CH_F + 64 + qq * 16;
        fv[i] = lds128(a);
        pv[i] = qq > 0 ? lds32(a - 4) >> 16 : 0u;
      }
#pragma unroll
      for (int i = 0; i < 10; ++i) {
        const int cl = i >> 1, qq = ct + (i & 1) * 128;
        sts128(F + cl * CH_F + 64 + qq * 16 + 4160,
               make_uint4(__byte_perm(pv[i], fv[i].x, 0x5410), __byte_perm(fv[i].x, fv[i].y, 0x5432),
                          __byte_perm(fv[i].y, fv[i].z, 0x5432), __byte_perm(fv[i].z, fv[i].w, 0x5432)));
      }
      if (ct < 40) sts128(F + (ct >> 3) * CH_F + ((ct >> 2) & 1) * 4160 + (ct & 3) * 16, make_uint4(0, 0, 0, 0));
    }
    mbar_wait(bars + 8 * B_U, 0);
    named_sync(3, 128);
    if (ct == 0) PROF(10);
    if (lane == 0) mbar_arrive(bars + 8 * B_CIN);
    constexpr int NOWN = 5;
#pragma unroll 1
    for (int i = 0; i < NOWN; ++i) {
      const int cl = NOWN == 5 ? i : (i == 0 ? 0 : i + 2);
      if (cl == 4) mbar_wait(bars + 8 * B_U4, 0);
      conv_channel(sb, cl, wc, lane, __shfl_sync(0xffffffffu, dpack, cl), 3);
      if (ct == 0 && i == 0) PROF(27);
    }
    if (ct == 0) PROF(30);
    const uint32_t YT = sb + OFF_F, YN = sb + OFF_F + 20480;
    mbar_wait(bars + 8 * B_YT, 0);
    {
      int w2 = wc, l2 = lane;
      asm volatile("" : "+r"(w2), "+r"(l2));
      const int r2 = l2 & 7, m2 = l2 >> 3;
      uint4 x[10];
#pragma unroll
      for (int k = 0; k < 10; ++k) {
        const int it = w2 + 4 * k, c = it % 10, tq = it / 10, ch = 8 * c + r2, j = 4 * tq + m2;
        ldsm4t(x[k].x, x[k].y, x[k].z, x[k].w, YT + (j >> 3) * 10240 + ch * 128 + (((j & 7) ^ (ch & 7)) << 4));
      }
#pragma unroll
      for (int k = 0; k < 10; ++k) {
        const int it = w2 + 4 * k, c = it % 10, tq = it / 10;
        const int s = (8 * (4 * tq + m2) + r2) ^ 31;
        stsm4(YN + s * 176 + c * 16, x[k].x, x[k].y, x[k].z, x[k].w);
      }
    }
    mbar_wait(bars + 8 * B_QT, 0);
    named_sync(3, 128);
#pragma unroll
    for (int i = 0; i < 10; ++i) {
      const int idx = ct + 128 * i, row = idx / 10, c = idx % 10;
      const uint4 y = lds128(YN + row * 176 + c * 16), q = lds128(U + row * 160 + c * 16);
      stg128(prm.out + (size_t)(t0 + row) * (2 * DM) + c0 + c * 8,
             make_uint4(hmul2(q.x, y.x), hmul2(q.y, y.y), hmul2(q.z, y.z), hmul2(q.w, y.w)));
    }
    if (ct == 0) PROF(13);
  } else {
    asm volatile("setmaxnreg.inc.sync.aligned.u32 168;");
    const int wq = __shfl_sync(0xffffffffu, warp, 0);
    const int mi = lane >> 3, r = lane & 7;
    const uint32_t stg = sb + OFF_STG;
    {
      float acc1[96], acc2[24];
#pragma unroll 1
      for (int it = 0; it < 10; ++it) {
        const int s = it % NST1;
        mbar_wait(bars + 8 * (B_FULL1 + s), (it / NST1) & 1);
        if (tid == 0) PROF(32 + it);
        const uint32_t st = sb + s * ST1;
        wg_fence();
#pragma unroll
        for (int kk = 0; kk < 4; ++kk) {
          const uint64_t da = make_desc(st + wg * 8192 + kk * 32, 16, 1024, 1);
          const uint64_t db1 = make_desc(st + ST1_B128 + (kk >> 1) * 12288 + (kk & 1) * 2048, 4096, 1024, 1);
          const uint64_t db2 = make_desc(st + ST1_B32 + (kk >> 1) * 3072 + (kk & 1) * 512, 1024, 256, 3);
          wgmma_n192(acc1, da, db1, (it | kk) != 0);
          wgmma_n48(acc2, da, db2, (it | kk) != 0);
        }
        wg_commit();
        wg_wait<0>();
        if (it + NST1 < 10 && lane < 2) mbar_arrive_cta(bars + 8 * (B_EMPTY1 + s), lane);
        if (it == 7 && lane == 0) mbar_arrive(bars + 8 * B_FFREE);
      }
      wg_wait<0>();
      reg_fence(acc1); reg_fence(acc2);
      if (tid == 0) PROF(17);
      named_sync(1, 256);
      if (tid == 0) mbar_arrive(bars + 8 * B_RINGFREE);
      const uint32_t rowo = (16 * wq + 8 * (mi & 1) + r) * 16;
      const int t4 = lane & 3;
#pragma unroll
      for (int pr = 0; pr < 2; ++pr) {
#pragma unroll
        for (int kv = 0; kv < 2; ++kv) {
          uint32_t w[5][2];
#pragma unroll
          for (int c = 0; c < 5; ++c) {
            const int tile = 5 * pr + c;
            if (tile < 8) {
              const int o = 32 * (kv + 1) + 4 * tile;
              w[c][0] = pack_bf16(acc1[o], acc1[o + 1]); w[c][1] = pack_bf16(acc1[o + 2], acc1[o + 3]);
            } else {
              const int o = 8 * (kv + 1) + 4 * (tile - 8);
              w[c][0] = pack_bf16(acc2[o], acc2[o + 1]); w[c][1] = pack_bf16(acc2[o + 2], acc2[o + 3]);
            }
          }
          const uint32_t base = sb + pr * PWIN + 2 * PAIR + (kv ? 5 * PLANE : 0);
          if (kv == 0) {
            stsm4(base + rowo + (mi >> 1) * PLANE, w[0][0], w[0][1], w[1][0], w[1][1]);
            stsm4(base + rowo + (2 + (mi >> 1)) * PLANE, w[2][0], w[2][1], w[3][0], w[3][1]);
            stsm2(base + 4 * PLANE + (16 * wq + (lane & 15)) * 16, w[4][0], w[4][1]);
          } else {
            const uint32_t oneE = t4 == 2 ? 0x00003F80u : 0u, oneO = t4 == 0 ? 0x00003F80u : 0u;
            stsm4(base + rowo + (mi >> 1) * PLANE, w[0][0], w[0][1], w[1][0], w[1][1]);
            stsm4(base + rowo + (2 + (mi >> 1)) * PLANE, t4 < 2 ? w[2][0] : oneE, t4 < 2 ? w[2][1] : oneE, w[3][0], w[3][1]);
            stsm4(base + rowo + (4 + (mi >> 1)) * PLANE, w[4][0], w[4][1], t4 >= 2 ? w[2][0] : oneO, t4 >= 2 ? w[2][1] : oneO);
          }
        }
        fence_async_smem();
        __syncwarp();
        if (lane == 0) mbar_arrive(bars + 8 * (pr ? B_KVST1 : B_KVST));
      }
      mbar_wait(bars + 8 * B_STGFREE, 0);
      const uint32_t rq = stg + rowo + (mi >> 1) * PLANE;
#pragma unroll
      for (int tp = 0; tp < 4; ++tp)
        stsm4(rq + tp * 2 * PLANE, pack_bf16(acc1[8 * tp], acc1[8 * tp + 1]), pack_bf16(acc1[8 * tp + 2], acc1[8 * tp + 3]),
              pack_bf16(acc1[8 * tp + 4], acc1[8 * tp + 5]), pack_bf16(acc1[8 * tp + 6], acc1[8 * tp + 7]));
      stsm4(rq + 8 * PLANE, pack_bf16(acc2[0], acc2[1]), pack_bf16(acc2[2], acc2[3]), pack_bf16(acc2[4], acc2[5]), pack_bf16(acc2[6], acc2[7]));
    }
    if (rb < 2) {
      const int nz = (2 - rb) * (PAIR / 16);
#pragma unroll 1
      for (int i = tid; i < 2 * nz; i += 256) sts128(sb + (i >= nz ? PWIN + (i - nz) * 16 : i * 16), make_uint4(0, 0, 0, 0));
      fence_async_smem();
    }
    named_sync(2, 256);
    if (tid == 0) PROF(18);
    attn_all(sb, stg, bars, wq, lane, rb >= 2 ? 0 : 4 - 2 * rb);
    if (tid == 0) PROF(19);
    float acc[40];
#pragma unroll 1
    for (int it = 0; it < 8; ++it) {
      const int s = it & 3;
      mbar_wait(bars + 8 * (B_FULL2 + s), it >> 2);
      if (it == 0 && tid == 0) PROF(21);
      if (it == 4 && tid == 0) PROF(25);
      const uint32_t st = sb + s * ST2;
      wg_fence();
#pragma unroll
      for (int kk = 0; kk < 5; ++kk)
        wgmma_n80(acc, make_desc(st + wg * 1024 + kk * 2 * PLANE, PLANE, 128, 0), make_desc(st + 20480 + kk * 256, 128, 1280, 0), (it | kk) != 0);
      wg_commit();
      if (it < 4) {
        wg_wait<0>();
        if (lane < 2) mbar_arrive_cta(bars + 8 * (B_EMPTY2 + s), lane);
      }
    }
    wg_wait<0>();
    reg_fence(acc);
    if (tid == 0) PROF(22);
    mbar_wait(bars + 8 * B_OPUB, 0);
    {
      const uint32_t rowa = stg + (16 * wq + 8 * (mi & 1) + r) * 160 + (mi >> 1) * 16;
#pragma unroll
      for (int tp = 0; tp < 5; ++tp)
        stsm4(rowa + tp * 32, pack_bf16(acc[8 * tp], acc[8 * tp + 1]), pack_bf16(acc[8 * tp + 2], acc[8 * tp + 3]),
              pack_bf16(acc[8 * tp + 4], acc[8 * tp + 5]), pack_bf16(acc[8 * tp + 6], acc[8 * tp + 7]));
      fence_async_smem();
      __syncwarp();
      if (lane == 0) {
        tma2d_store(&tmOut, DM + c2 * 80, rb2 * 128 + 16 * wq, stg + wq * 2560);
        bulk_commit();
        bulk_wait0_read();
      }
    }
    if (tid == 0) PROF(23);
  }
}

typedef CUresult (*EncodeFn)(CUtensorMap*, CUtensorMapDataType, cuuint32_t, void*, const cuuint64_t*, const cuuint64_t*,
                             const cuuint32_t*, const cuuint32_t*, CUtensorMapInterleave, CUtensorMapSwizzle,
                             CUtensorMapL2promotion, CUtensorMapFloatOOBfill);

CUtensorMap make_map(EncodeFn enc, const void* p, int rank, const cuuint64_t* dims, const cuuint64_t* strides,
                     const cuuint32_t* box, CUtensorMapSwizzle sw) {
  CUtensorMap m;
  const cuuint32_t es[5] = {1, 1, 1, 1, 1};
  enc(&m, CU_TENSOR_MAP_DATA_TYPE_BFLOAT16, rank, const_cast<void*>(p), dims, strides, box, es,
      CU_TENSOR_MAP_INTERLEAVE_NONE, sw, CU_TENSOR_MAP_L2_PROMOTION_L2_128B, CU_TENSOR_MAP_FLOAT_OOB_FILL_NONE);
  return m;
}

}

extern "C" void kernel_launch(void* const* d_in, const int* in_sizes, int n_in, void* d_out, int out_size) {
  (void)in_sizes; (void)n_in; (void)out_size;
  static EncodeFn enc = nullptr;
  static void* kt_ptr = nullptr;
  static void* yt_ptr = nullptr;
  if (!enc) {
    void* fn = nullptr;
    cudaDriverEntryPointQueryResult qr;
    cudaGetDriverEntryPoint("cuTensorMapEncodeTiled", &fn, cudaEnableDefault, &qr);
    enc = (EncodeFn)fn;
    cudaGetSymbolAddress(&kt_ptr, g_kvT);
    cudaGetSymbolAddress(&yt_ptr, g_yT);
    cudaFuncSetAttribute(h3_swa_fused_kernel, cudaFuncAttributeMaxDynamicSharedMemorySize, SMEM_BYTES);
  }
  const void* x = d_in[6];
  const void* wqkv = d_in[7];
  const void* wo = d_in[8];
  CUtensorMap tmX, tmW128, tmW32, tmOut, tmKT, tmKin, tmVin, tmQ, tmYT, tmU4, tmU1, tmXP;
  { cuuint64_t d[2] = {640, 2048}, s[1] = {1280}; cuuint32_t b[2] = {64, 128};
    tmX = make_map(enc, x, 2, d, s, b, CU_TENSOR_MAP_SWIZZLE_128B); }
  { cuuint64_t d[3] = {640, 640, 3}, s[2] = {3840, 1280}; cuuint32_t b[3] = {64, 32, 3};
    tmW128 = make_map(enc, wqkv, 3, d, s, b, CU_TENSOR_MAP_SWIZZLE_128B); }
  { cuuint64_t d[3] = {640, 640, 3}, s[2] = {3840, 1280}; cuuint32_t b[3] = {16, 32, 3};
    tmW32 = make_map(enc, wqkv, 3, d, s, b, CU_TENSOR_MAP_SWIZZLE_32B); }
  { cuuint64_t d[2] = {1280, 2048}, s[1] = {2560}; cuuint32_t b[2] = {80, 16};
    tmOut = make_map(enc, d_out, 2, d, s, b, CU_TENSOR_MAP_SWIZZLE_NONE); }
  { cuuint64_t d[3] = {128, 16, 640}, s[2] = {256, 4096}; cuuint32_t b[3] = {128, 1, 80};
    tmKT = make_map(enc, kt_ptr, 3, d, s, b, CU_TENSOR_MAP_SWIZZLE_NONE); }
  { cuuint64_t d[4] = {32, 16, 4, 640}, s[3] = {256, 64, 4096}; cuuint32_t b[4] = {32, 20, 4, 4};
    tmU4 = make_map(enc, kt_ptr, 4, d, s, b, CU_TENSOR_MAP_SWIZZLE_NONE); }
  { cuuint64_t d[4] = {32, 16, 4, 640}, s[3] = {256, 64, 4096}; cuuint32_t b[4] = {32, 20, 4, 1};
    tmU1 = make_map(enc, kt_ptr, 4, d, s, b, CU_TENSOR_MAP_SWIZZLE_NONE); }
  { cuuint64_t d[2] = {640, 2048}, s[1] = {1280}; cuuint32_t b[2] = {80, 131};
    tmKin = make_map(enc, d_in[1], 2, d, s, b, CU_TENSOR_MAP_SWIZZLE_NONE); }
  { cuuint64_t d[2] = {640, 2048}, s[1] = {1280}; cuuint32_t b[2] = {80, 128};
    tmVin = make_map(enc, d_in[2], 2, d, s, b, CU_TENSOR_MAP_SWIZZLE_NONE); }
  { cuuint64_t d[2] = {640, 2048}, s[1] = {1280}; cuuint32_t b[2] = {80, 128};
    tmQ = make_map(enc, d_in[0], 2, d, s, b, CU_TENSOR_MAP_SWIZZLE_NONE); }
  { cuuint64_t d[2] = {2048, 640}, s[1] = {4096}; cuuint32_t b[2] = {64, 80};
    tmYT = make_map(enc, yt_ptr, 2, d, s, b, CU_TENSOR_MAP_SWIZZLE_128B); }
  { cuuint64_t d[2] = {640, 2048}, s[1] = {1280}; cuuint32_t b[2] = {192, 16};
    tmXP = make_map(enc, x, 2, d, s, b, CU_TENSOR_MAP_SWIZZLE_NONE); }
  Params prm;
  prm.q = (const uint16_t*)d_in[0]; prm.k = (const uint16_t*)d_in[1]; prm.v = (const uint16_t*)d_in[2];
  prm.x = (const uint16_t*)x; prm.wqkv = (const uint16_t*)wqkv; prm.wo = (const uint16_t*)wo;
  prm.shift_k = (const uint16_t*)d_in[3]; prm.ssm_k = (const uint16_t*)d_in[4];
  prm.ssm_D = (const uint16_t*)d_in[5]; prm.out = (uint16_t*)d_out;
  h3_swa_fused_kernel<<<128, 512, SMEM_BYTES>>>(tmX, tmW128, tmW32, tmOut, tmKT, tmKin, tmVin, tmQ, tmYT, tmU4, tmU1, tmXP, prm);
}
```
